```python
import torch

def _softmax(x, axis=-1):
    return torch.softmax(x, dim=axis)
def _gelu(x):
    return torch.nn.functional.gelu(x, approximate="tanh")
def _silu(x):
    return torch.nn.functional.silu(x)
def _sigmoid(x):
    return torch.sigmoid(x)
def _layernorm(x, axis=-1, eps=1e-5):
    m = x.mean(dim=axis, keepdim=True)
    v = x.var(dim=axis, keepdim=True, unbiased=False)
    return (x - m) / torch.sqrt(v + eps)
def _scatter_add(tgt, idx, src, axis=0):
    return tgt.clone().index_add_(axis, idx, src)
def _segment_sum(src, seg, n):
    out = torch.zeros((n,) + src.shape[1:], dtype=src.dtype)
    return out.index_add_(0, seg, src)
def _pad(x, pw):
    flat = tuple(v for pair in reversed(pw) for v in pair)
    return torch.nn.functional.pad(x, flat)

kernel_name = 'gated_mix__softmax_full_mha__geglu_ffn__prompt'

def setup_inputs():

    _w = (lambda a: (lambda t: t.to(torch.bfloat16) if t.is_floating_point() else t)(torch.as_tensor(a)))
    def _A_setup():
        B, S, D = 1, 2048, 576
        return {
            "x": _w((lambda *s: torch.randn(*s, dtype=torch.bfloat16) * 0.05)(B, S, D)),
            "wqkv": _w((lambda *s: torch.randn(*s, dtype=torch.bfloat16) * 0.8)(D, 3 * D)),
            "wo": _w((lambda *s: torch.randn(*s, dtype=torch.bfloat16) * 0.05)(D, D)),
        }
    _A_in = _A_setup()

    def _B_setup():
        B, S, D, F = 1, 2048, 576, 4608
        return {
            "x": _w((lambda *s: torch.randn(*s, dtype=torch.bfloat16) * 0.05)(B, S, D)),
            "w_gate": _w((lambda *s: torch.randn(*s, dtype=torch.bfloat16) * 0.1)(D, F)),
            "w_up": _w((lambda *s: torch.randn(*s, dtype=torch.bfloat16) * 0.1)(D, F)),
            "w_down": _w((lambda *s: torch.randn(*s, dtype=torch.bfloat16) * 0.1)(F, D)),
        }
    _B_in = _B_setup()

    return {
        "A_x": _A_in["x"],
        "A_wqkv": _A_in["wqkv"],
        "A_wo": _A_in["wo"],
        "B_x": _B_in["x"],
        "B_w_gate": _B_in["w_gate"],
        "B_w_up": _B_in["w_up"],
        "B_w_down": _B_in["w_down"],
        "gate_w": _w((lambda *s: torch.randn(*s, dtype=torch.bfloat16) * 0.05)(576) * 16.0),
    }

def reference(A_x, A_wqkv, A_wo, B_x, B_w_gate, B_w_up, B_w_down, gate_w):
    def _A_ref(x, wqkv, wo):
        B, S, D = x.shape
        H = 32; Dh = D // H
        qkv = (lambda x, *d: x.permute(*d))((x @ wqkv).reshape(B, S, 3, H, Dh), 2, 0, 3, 1, 4)
        q, k, v = qkv[0], qkv[1], qkv[2]
        scale = Dh ** -0.5
        scores = torch.einsum("bhqd,bhkd->bhqk", q, k) * scale
        p = _softmax(scores, axis=-1)
        o = torch.einsum("bhqk,bhkd->bhqd", p, v)
        return (lambda x, *d: x.permute(*d))(o, 0, 2, 1, 3).reshape(B, S, D) @ wo

    def _B_ref(x, w_gate, w_up, w_down):
        return (_gelu(x @ w_gate) * (x @ w_up)) @ w_down

    x = A_x
    g = _sigmoid((x * gate_w).sum(-1, keepdims=True))
    a = _A_ref(x, A_wqkv, A_wo)
    b = _B_ref(x, B_w_gate, B_w_up, B_w_down)
    return g * a + (1 - g) * b
```

```cpp
#include <cuda_runtime.h>
#include <cuda.h>
#include <cuda_bf16.h>
#include <stdint.h>

#define PROFILE 0
#define WAITPOS 1
#define PF_X 0
#define DOTRACE 0
#define SLEEPNS "1000"

namespace {

constexpr int SEQ = 2048, DM = 576, FF = 4608;
constexpr int NCTA = 128;
constexpr int NSTAGE = 6;
constexpr int SLOT = 35 * 1024;
constexpr int OFF_AX = 22528;
constexpr int OFF_A2 = 18432;
constexpr int OFF_TL = 20480;
constexpr int OFF_KV = 30720;
constexpr int OFF_Q = NSTAGE * SLOT - 4608;
constexpr int OFF_BAR = NSTAGE * SLOT + 3 * 4608;
constexpr int SMEM_BYTES = OFF_BAR + 1024 + 1024;

constexpr int HEAD_BYTES = 256 * 640;
constexpr int A2_TILE = 336 * 4096;

constexpr int FL_KV = 0;
constexpr int FL_M = FL_KV + 8 * 32;
constexpr int FM_H = 0;
constexpr int FM_G = 6, FM_LATE = 7;
constexpr int FM_R = 16;
constexpr int FL_E = FL_M + 16 * 64;
constexpr int FL_N = FL_E + NCTA * 32;

__device__ __align__(1024) uint8_t g_kv[32 * HEAD_BYTES];
__device__ __align__(1024) uint8_t g_a2[16 * A2_TILE];
__device__ __align__(1024) float4 g_part[NCTA * 2 * 9 * 128];
__device__ float g_gate[SEQ];
__device__ __align__(256) uint32_t g_flags[FL_N];

template <uint32_t BHI>
__device__ __forceinline__ void wgmma_rs_n24_t1(float (&d)[12], uint32_t a0, uint32_t a1, uint32_t a2, uint32_t a3, uint32_t db, int scale_d) {
  asm volatile("{\n.reg .pred p;\n.reg .b64 da, db;\n"
    "mov.b64 db, {%16, %18};\n"
    "setp.ne.b32 p, %17, 0;\n"
    "wgmma.mma_async.sync.aligned.m64n24k16.f32.bf16.bf16 "
    "{%0, %1, %2, %3, %4, %5, %6, %7, %8, %9, %10, %11}, "
    "{%12, %13, %14, %15}, db, p, 1, 1, 1;\n}\n"
    : "+f"(d[0]), "+f"(d[1]), "+f"(d[2]), "+f"(d[3]), "+f"(d[4]), "+f"(d[5]), "+f"(d[6]), "+f"(d[7]),
      "+f"(d[8]), "+f"(d[9]), "+f"(d[10]), "+f"(d[11])
    : "r"(a0), "r"(a1), "r"(a2), "r"(a3), "r"(db), "r"(scale_d), "n"(BHI));
}
template <uint32_t BHI>
__device__ __forceinline__ void wgmma_rs_n64_t0(float (&d)[32], uint32_t a0, uint32_t a1, uint32_t a2, uint32_t a3, uint32_t db, int scale_d) {
  asm volatile("{\n.reg .pred p;\n.reg .b64 da, db;\n"
    "mov.b64 db, {%36, %38};\n"
    "setp.ne.b32 p, %37, 0;\n"
    "wgmma.mma_async.sync.aligned.m64n64k16.f32.bf16.bf16 "
    "{%0, %1, %2, %3, %4, %5, %6, %7, %8, %9, %10, %11, %12, %13, %14, %15, "
    "%16, %17, %18, %19, %20, %21, %22, %23, %24, %25, %26, %27, %28, %29, %30, %31}, "
    "{%32, %33, %34, %35}, db, p, 1, 1, 0;\n}\n"
    : "+f"(d[0]), "+f"(d[1]), "+f"(d[2]), "+f"(d[3]), "+f"(d[4]), "+f"(d[5]), "+f"(d[6]), "+f"(d[7]),
      "+f"(d[8]), "+f"(d[9]), "+f"(d[10]), "+f"(d[11]), "+f"(d[12]), "+f"(d[13]), "+f"(d[14]), "+f"(d[15]),
      "+f"(d[16]), "+f"(d[17]), "+f"(d[18]), "+f"(d[19]), "+f"(d[20]), "+f"(d[21]), "+f"(d[22]), "+f"(d[23]),
      "+f"(d[24]), "+f"(d[25]), "+f"(d[26]), "+f"(d[27]), "+f"(d[28]), "+f"(d[29]), "+f"(d[30]), "+f"(d[31])
    : "r"(a0), "r"(a1), "r"(a2), "r"(a3), "r"(db), "r"(scale_d), "n"(BHI));
}
template <uint32_t AHI, uint32_t BHI>
__device__ __forceinline__ void wgmma_ss_n24_t1(float (&d)[12], uint32_t da, uint32_t db, int scale_d) {
  asm volatile("{\n.reg .pred p;\n.reg .b64 da, db;\n"
    "mov.b64 da, {%12, %15};\nmov.b64 db, {%13, %16};\n"
    "setp.ne.b32 p, %14, 0;\n"
    "wgmma.mma_async.sync.aligned.m64n24k16.f32.bf16.bf16 "
    "{%0, %1, %2, %3, %4, %5, %6, %7, %8, %9, %10, %11}, "
    "da, db, p, 1, 1, 0, 1;\n}\n"
    : "+f"(d[0]), "+f"(d[1]), "+f"(d[2]), "+f"(d[3]), "+f"(d[4]), "+f"(d[5]), "+f"(d[6]), "+f"(d[7]),
      "+f"(d[8]), "+f"(d[9]), "+f"(d[10]), "+f"(d[11])
    : "r"(da), "r"(db), "r"(scale_d), "n"(AHI), "n"(BHI));
}
template <uint32_t AHI, uint32_t BHI>
__device__ __forceinline__ void wgmma_ss_n72_t1(float (&d)[36], uint32_t da, uint32_t db, int scale_d) {
  asm volatile("{\n.reg .pred p;\n.reg .b64 da, db;\n"
    "mov.b64 da, {%36, %39};\nmov.b64 db, {%37, %40};\n"
    "setp.ne.b32 p, %38, 0;\n"
    "wgmma.mma_async.sync.aligned.m64n72k16.f32.bf16.bf16 "
    "{%0, %1, %2, %3, %4, %5, %6, %7, %8, %9, %10, %11, %12, %13, %14, %15, "
    "%16, %17, %18, %19, %20, %21, %22, %23, %24, %25, %26, %27, %28, %29, %30, %31, "
    "%32, %33, %34, %35}, "
    "da, db, p, 1, 1, 0, 1;\n}\n"
    : "+f"(d[0]), "+f"(d[1]), "+f"(d[2]), "+f"(d[3]), "+f"(d[4]), "+f"(d[5]), "+f"(d[6]), "+f"(d[7]),
      "+f"(d[8]), "+f"(d[9]), "+f"(d[10]), "+f"(d[11]), "+f"(d[12]), "+f"(d[13]), "+f"(d[14]), "+f"(d[15]),
      "+f"(d[16]), "+f"(d[17]), "+f"(d[18]), "+f"(d[19]), "+f"(d[20]), "+f"(d[21]), "+f"(d[22]), "+f"(d[23]),
      "+f"(d[24]), "+f"(d[25]), "+f"(d[26]), "+f"(d[27]), "+f"(d[28]), "+f"(d[29]), "+f"(d[30]), "+f"(d[31]),
      "+f"(d[32]), "+f"(d[33]), "+f"(d[34]), "+f"(d[35])
    : "r"(da), "r"(db), "r"(scale_d), "n"(AHI), "n"(BHI));
}
template <uint32_t AHI, uint32_t BHI>
__device__ __forceinline__ void wgmma_ss_n128_t1(float (&d)[64], uint32_t da, uint32_t db, int scale_d) {
  asm volatile("{\n.reg .pred p;\n.reg .b64 da, db;\n"
    "mov.b64 da, {%64, %67};\nmov.b64 db, {%65, %68};\n"
    "setp.ne.b32 p, %66, 0;\n"
    "wgmma.mma_async.sync.aligned.m64n128k16.f32.bf16.bf16 "
    "{%0, %1, %2, %3, %4, %5, %6, %7, %8, %9, %10, %11, %12, %13, %14, %15, "
    "%16, %17, %18, %19, %20, %21, %22, %23, %24, %25, %26, %27, %28, %29, %30, %31, "
    "%32, %33, %34, %35, %36, %37, %38, %39, %40, %41, %42, %43, %44, %45, %46, %47, "
    "%48, %49, %50, %51, %52, %53, %54, %55, %56, %57, %58, %59, %60, %61, %62, %63}, "
    "da, db, p, 1, 1, 0, 1;\n}\n"
    : "+f"(d[0]), "+f"(d[1]), "+f"(d[2]), "+f"(d[3]), "+f"(d[4]), "+f"(d[5]), "+f"(d[6]), "+f"(d[7]),
      "+f"(d[8]), "+f"(d[9]), "+f"(d[10]), "+f"(d[11]), "+f"(d[12]), "+f"(d[13]), "+f"(d[14]), "+f"(d[15]),
      "+f"(d[16]), "+f"(d[17]), "+f"(d[18]), "+f"(d[19]), "+f"(d[20]), "+f"(d[21]), "+f"(d[22]), "+f"(d[23]),
      "+f"(d[24]), "+f"(d[25]), "+f"(d[26]), "+f"(d[27]), "+f"(d[28]), "+f"(d[29]), "+f"(d[30]), "+f"(d[31]),
      "+f"(d[32]), "+f"(d[33]), "+f"(d[34]), "+f"(d[35]), "+f"(d[36]), "+f"(d[37]), "+f"(d[38]), "+f"(d[39]),
      "+f"(d[40]), "+f"(d[41]), "+f"(d[42]), "+f"(d[43]), "+f"(d[44]), "+f"(d[45]), "+f"(d[46]), "+f"(d[47]),
      "+f"(d[48]), "+f"(d[49]), "+f"(d[50]), "+f"(d[51]), "+f"(d[52]), "+f"(d[53]), "+f"(d[54]), "+f"(d[55]),
      "+f"(d[56]), "+f"(d[57]), "+f"(d[58]), "+f"(d[59]), "+f"(d[60]), "+f"(d[61]), "+f"(d[62]), "+f"(d[63])
    : "r"(da), "r"(db), "r"(scale_d), "n"(AHI), "n"(BHI));
}
template <uint32_t AHI, uint32_t BHI>
__device__ __forceinline__ void wgmma_ss_n192_t1(float (&d)[96], uint32_t da, uint32_t db, int scale_d) {
  asm volatile("{\n.reg .pred p;\n.reg .b64 da, db;\n"
    "mov.b64 da, {%96, %99};\nmov.b64 db, {%97, %100};\n"
    "setp.ne.b32 p, %98, 0;\n"
    "wgmma.mma_async.sync.aligned.m64n192k16.f32.bf16.bf16 "
    "{%0, %1, %2, %3, %4, %5, %6, %7, %8, %9, %10, %11, %12, %13, %14, %15, "
    "%16, %17, %18, %19, %20, %21, %22, %23, %24, %25, %26, %27, %28, %29, %30, %31, "
    "%32, %33, %34, %35, %36, %37, %38, %39, %40, %41, %42, %43, %44, %45, %46, %47, "
    "%48, %49, %50, %51, %52, %53, %54, %55, %56, %57, %58, %59, %60, %61, %62, %63, "
    "%64, %65, %66, %67, %68, %69, %70, %71, %72, %73, %74, %75, %76, %77, %78, %79, "
    "%80, %81, %82, %83, %84, %85, %86, %87, %88, %89, %90, %91, %92, %93, %94, %95}, "
    "da, db, p, 1, 1, 0, 1;\n}\n"
    : "+f"(d[0]), "+f"(d[1]), "+f"(d[2]), "+f"(d[3]), "+f"(d[4]), "+f"(d[5]), "+f"(d[6]), "+f"(d[7]),
      "+f"(d[8]), "+f"(d[9]), "+f"(d[10]), "+f"(d[11]), "+f"(d[12]), "+f"(d[13]), "+f"(d[14]), "+f"(d[15]),
      "+f"(d[16]), "+f"(d[17]), "+f"(d[18]), "+f"(d[19]), "+f"(d[20]), "+f"(d[21]), "+f"(d[22]), "+f"(d[23]),
      "+f"(d[24]), "+f"(d[25]), "+f"(d[26]), "+f"(d[27]), "+f"(d[28]), "+f"(d[29]), "+f"(d[30]), "+f"(d[31]),
      "+f"(d[32]), "+f"(d[33]), "+f"(d[34]), "+f"(d[35]), "+f"(d[36]), "+f"(d[37]), "+f"(d[38]), "+f"(d[39]),
      "+f"(d[40]), "+f"(d[41]), "+f"(d[42]), "+f"(d[43]), "+f"(d[44]), "+f"(d[45]), "+f"(d[46]), "+f"(d[47]),
      "+f"(d[48]), "+f"(d[49]), "+f"(d[50]), "+f"(d[51]), "+f"(d[52]), "+f"(d[53]), "+f"(d[54]), "+f"(d[55]),
      "+f"(d[56]), "+f"(d[57]), "+f"(d[58]), "+f"(d[59]), "+f"(d[60]), "+f"(d[61]), "+f"(d[62]), "+f"(d[63]),
      "+f"(d[64]), "+f"(d[65]), "+f"(d[66]), "+f"(d[67]), "+f"(d[68]), "+f"(d[69]), "+f"(d[70]), "+f"(d[71]),
      "+f"(d[72]), "+f"(d[73]), "+f"(d[74]), "+f"(d[75]), "+f"(d[76]), "+f"(d[77]), "+f"(d[78]), "+f"(d[79]),
      "+f"(d[80]), "+f"(d[81]), "+f"(d[82]), "+f"(d[83]), "+f"(d[84]), "+f"(d[85]), "+f"(d[86]), "+f"(d[87]),
      "+f"(d[88]), "+f"(d[89]), "+f"(d[90]), "+f"(d[91]), "+f"(d[92]), "+f"(d[93]), "+f"(d[94]), "+f"(d[95])
    : "r"(da), "r"(db), "r"(scale_d), "n"(AHI), "n"(BHI));
}
__device__ __forceinline__ void wgmma6_rs_n24_t1(float (&d)[12], uint32_t a0, uint32_t a1, uint32_t a2, uint32_t a3, uint64_t db, int scale_d) {
  asm volatile("{\n.reg .pred p;\n"
    "setp.ne.b32 p, %17, 0;\n"
    "wgmma.mma_async.sync.aligned.m64n24k16.f32.bf16.bf16 "
    "{%0, %1, %2, %3, %4, %5, %6, %7, %8, %9, %10, %11}, "
    "{%12, %13, %14, %15}, %16, p, 1, 1, 1;\n}\n"
    : "+f"(d[0]), "+f"(d[1]), "+f"(d[2]), "+f"(d[3]), "+f"(d[4]), "+f"(d[5]), "+f"(d[6]), "+f"(d[7]),
      "+f"(d[8]), "+f"(d[9]), "+f"(d[10]), "+f"(d[11])
    : "r"(a0), "r"(a1), "r"(a2), "r"(a3), "l"(db), "r"(scale_d));
}
__device__ __forceinline__ void wgmma6_rs_n64_t0(float (&d)[32], uint32_t a0, uint32_t a1, uint32_t a2, uint32_t a3, uint64_t db, int scale_d) {
  asm volatile("{\n.reg .pred p;\n"
    "setp.ne.b32 p, %37, 0;\n"
    "wgmma.mma_async.sync.aligned.m64n64k16.f32.bf16.bf16 "
    "{%0, %1, %2, %3, %4, %5, %6, %7, %8, %9, %10, %11, %12, %13, %14, %15, "
    "%16, %17, %18, %19, %20, %21, %22, %23, %24, %25, %26, %27, %28, %29, %30, %31}, "
    "{%32, %33, %34, %35}, %36, p, 1, 1, 0;\n}\n"
    : "+f"(d[0]), "+f"(d[1]), "+f"(d[2]), "+f"(d[3]), "+f"(d[4]), "+f"(d[5]), "+f"(d[6]), "+f"(d[7]),
      "+f"(d[8]), "+f"(d[9]), "+f"(d[10]), "+f"(d[11]), "+f"(d[12]), "+f"(d[13]), "+f"(d[14]), "+f"(d[15]),
      "+f"(d[16]), "+f"(d[17]), "+f"(d[18]), "+f"(d[19]), "+f"(d[20]), "+f"(d[21]), "+f"(d[22]), "+f"(d[23]),
      "+f"(d[24]), "+f"(d[25]), "+f"(d[26]), "+f"(d[27]), "+f"(d[28]), "+f"(d[29]), "+f"(d[30]), "+f"(d[31])
    : "r"(a0), "r"(a1), "r"(a2), "r"(a3), "l"(db), "r"(scale_d));
}
__device__ __forceinline__ void wgmma6_ss_n144_t1(float (&d)[72], uint64_t da, uint64_t db, int scale_d) {
  asm volatile("{\n.reg .pred p;\n"
    "setp.ne.b32 p, %74, 0;\n"
    "wgmma.mma_async.sync.aligned.m64n144k16.f32.bf16.bf16 "
    "{%0, %1, %2, %3, %4, %5, %6, %7, %8, %9, %10, %11, %12, %13, %14, %15, "
    "%16, %17, %18, %19, %20, %21, %22, %23, %24, %25, %26, %27, %28, %29, %30, %31, "
    "%32, %33, %34, %35, %36, %37, %38, %39, %40, %41, %42, %43, %44, %45, %46, %47, "
    "%48, %49, %50, %51, %52, %53, %54, %55, %56, %57, %58, %59, %60, %61, %62, %63, "
    "%64, %65, %66, %67, %68, %69, %70, %71}, "
    "%72, %73, p, 1, 1, 0, 1;\n}\n"
    : "+f"(d[0]), "+f"(d[1]), "+f"(d[2]), "+f"(d[3]), "+f"(d[4]), "+f"(d[5]), "+f"(d[6]), "+f"(d[7]),
      "+f"(d[8]), "+f"(d[9]), "+f"(d[10]), "+f"(d[11]), "+f"(d[12]), "+f"(d[13]), "+f"(d[14]), "+f"(d[15]),
      "+f"(d[16]), "+f"(d[17]), "+f"(d[18]), "+f"(d[19]), "+f"(d[20]), "+f"(d[21]), "+f"(d[22]), "+f"(d[23]),
      "+f"(d[24]), "+f"(d[25]), "+f"(d[26]), "+f"(d[27]), "+f"(d[28]), "+f"(d[29]), "+f"(d[30]), "+f"(d[31]),
      "+f"(d[32]), "+f"(d[33]), "+f"(d[34]), "+f"(d[35]), "+f"(d[36]), "+f"(d[37]), "+f"(d[38]), "+f"(d[39]),
      "+f"(d[40]), "+f"(d[41]), "+f"(d[42]), "+f"(d[43]), "+f"(d[44]), "+f"(d[45]), "+f"(d[46]), "+f"(d[47]),
      "+f"(d[48]), "+f"(d[49]), "+f"(d[50]), "+f"(d[51]), "+f"(d[52]), "+f"(d[53]), "+f"(d[54]), "+f"(d[55]),
      "+f"(d[56]), "+f"(d[57]), "+f"(d[58]), "+f"(d[59]), "+f"(d[60]), "+f"(d[61]), "+f"(d[62]), "+f"(d[63]),
      "+f"(d[64]), "+f"(d[65]), "+f"(d[66]), "+f"(d[67]), "+f"(d[68]), "+f"(d[69]), "+f"(d[70]), "+f"(d[71])
    : "l"(da), "l"(db), "r"(scale_d));
}
__device__ __forceinline__ void wgmma6_ss_n256_t1(float (&d)[128], uint64_t da, uint64_t db, int scale_d) {
  asm volatile("{\n.reg .pred p;\n"
    "setp.ne.b32 p, %130, 0;\n"
    "wgmma.mma_async.sync.aligned.m64n256k16.f32.bf16.bf16 "
    "{%0, %1, %2, %3, %4, %5, %6, %7, %8, %9, %10, %11, %12, %13, %14, %15, "
    "%16, %17, %18, %19, %20, %21, %22, %23, %24, %25, %26, %27, %28, %29, %30, %31, "
    "%32, %33, %34, %35, %36, %37, %38, %39, %40, %41, %42, %43, %44, %45, %46, %47, "
    "%48, %49, %50, %51, %52, %53, %54, %55, %56, %57, %58, %59, %60, %61, %62, %63, "
    "%64, %65, %66, %67, %68, %69, %70, %71, %72, %73, %74, %75, %76, %77, %78, %79, "
    "%80, %81, %82, %83, %84, %85, %86, %87, %88, %89, %90, %91, %92, %93, %94, %95, "
    "%96, %97, %98, %99, %100, %101, %102, %103, %104, %105, %106, %107, %108, %109, %110, %111, "
    "%112, %113, %114, %115, %116, %117, %118, %119, %120, %121, %122, %123, %124, %125, %126, %127}, "
    "%128, %129, p, 1, 1, 0, 1;\n}\n"
    : "+f"(d[0]), "+f"(d[1]), "+f"(d[2]), "+f"(d[3]), "+f"(d[4]), "+f"(d[5]), "+f"(d[6]), "+f"(d[7]),
      "+f"(d[8]), "+f"(d[9]), "+f"(d[10]), "+f"(d[11]), "+f"(d[12]), "+f"(d[13]), "+f"(d[14]), "+f"(d[15]),
      "+f"(d[16]), "+f"(d[17]), "+f"(d[18]), "+f"(d[19]), "+f"(d[20]), "+f"(d[21]), "+f"(d[22]), "+f"(d[23]),
      "+f"(d[24]), "+f"(d[25]), "+f"(d[26]), "+f"(d[27]), "+f"(d[28]), "+f"(d[29]), "+f"(d[30]), "+f"(d[31]),
      "+f"(d[32]), "+f"(d[33]), "+f"(d[34]), "+f"(d[35]), "+f"(d[36]), "+f"(d[37]), "+f"(d[38]), "+f"(d[39]),
      "+f"(d[40]), "+f"(d[41]), "+f"(d[42]), "+f"(d[43]), "+f"(d[44]), "+f"(d[45]), "+f"(d[46]), "+f"(d[47]),
      "+f"(d[48]), "+f"(d[49]), "+f"(d[50]), "+f"(d[51]), "+f"(d[52]), "+f"(d[53]), "+f"(d[54]), "+f"(d[55]),
      "+f"(d[56]), "+f"(d[57]), "+f"(d[58]), "+f"(d[59]), "+f"(d[60]), "+f"(d[61]), "+f"(d[62]), "+f"(d[63]),
      "+f"(d[64]), "+f"(d[65]), "+f"(d[66]), "+f"(d[67]), "+f"(d[68]), "+f"(d[69]), "+f"(d[70]), "+f"(d[71]),
      "+f"(d[72]), "+f"(d[73]), "+f"(d[74]), "+f"(d[75]), "+f"(d[76]), "+f"(d[77]), "+f"(d[78]), "+f"(d[79]),
      "+f"(d[80]), "+f"(d[81]), "+f"(d[82]), "+f"(d[83]), "+f"(d[84]), "+f"(d[85]), "+f"(d[86]), "+f"(d[87]),
      "+f"(d[88]), "+f"(d[89]), "+f"(d[90]), "+f"(d[91]), "+f"(d[92]), "+f"(d[93]), "+f"(d[94]), "+f"(d[95]),
      "+f"(d[96]), "+f"(d[97]), "+f"(d[98]), "+f"(d[99]), "+f"(d[100]), "+f"(d[101]), "+f"(d[102]), "+f"(d[103]),
      "+f"(d[104]), "+f"(d[105]), "+f"(d[106]), "+f"(d[107]), "+f"(d[108]), "+f"(d[109]), "+f"(d[110]), "+f"(d[111]),
      "+f"(d[112]), "+f"(d[113]), "+f"(d[114]), "+f"(d[115]), "+f"(d[116]), "+f"(d[117]), "+f"(d[118]), "+f"(d[119]),
      "+f"(d[120]), "+f"(d[121]), "+f"(d[122]), "+f"(d[123]), "+f"(d[124]), "+f"(d[125]), "+f"(d[126]), "+f"(d[127])
    : "l"(da), "l"(db), "r"(scale_d));
}

__device__ __forceinline__ void wg_fence() { asm volatile("wgmma.fence.sync.aligned;" ::: "memory"); }
__device__ __forceinline__ void wg_commit() { asm volatile("wgmma.commit_group.sync.aligned;" ::: "memory"); }
template <int N> __device__ __forceinline__ void wg_wait() { asm volatile("wgmma.wait_group.sync.aligned %0;" ::"n"(N) : "memory"); }
__host__ __device__ constexpr uint32_t dlo(uint32_t off, uint32_t lbo) { return (off >> 4) | ((lbo >> 4) << 16); }
__host__ __device__ constexpr uint32_t dhi(uint32_t sbo, uint32_t swz) { return (sbo >> 4) | (swz << 30); }
constexpr uint32_t HI_X = dhi(512, 2), HI_W = dhi(1024, 1), HI_A2 = dhi(256, 0), HI_K = dhi(640, 0), HI_V = dhi(128, 0), HI_T = dhi(512, 0);
__device__ __forceinline__ float ex2(float x) { float y; asm volatile("ex2.approx.ftz.f32 %0, %1;" : "=f"(y) : "f"(x)); return y; }
template <uint32_t HI> __device__ __forceinline__ uint64_t mkdesc(uint32_t lo) {
    uint64_t d;
    asm("mov.b64 %0, {%1, %2};" : "=l"(d) : "r"(lo), "n"(HI));
    return d;
}
__device__ __forceinline__ float rcp_fast(float x) { float y; asm("rcp.approx.ftz.f32 %0, %1;" : "=f"(y) : "f"(x)); return y; }
__device__ __forceinline__ float tanh_fast(float x) { float y; asm("tanh.approx.f32 %0, %1;" : "=f"(y) : "f"(x)); return y; }
__device__ __forceinline__ uint32_t pack(float lo, float hi) { uint32_t y; asm("cvt.rn.bf16x2.f32 %0, %1, %2;" : "=r"(y) : "f"(hi), "f"(lo)); return y; }
template <int N> __device__ __forceinline__ void fence_regs(float (&d)[N]) {
#pragma unroll
    for (int i = 0; i < N; i++) asm volatile("" : "+f"(d[i])::"memory");
}
template <int N> __device__ __forceinline__ void fence_regs(uint32_t (&d)[N]) {
#pragma unroll
    for (int i = 0; i < N; i++) asm volatile("" : "+r"(d[i])::"memory");
}
template <int N> __device__ __forceinline__ void undef_regs(float (&d)[N]) {
#pragma unroll
    for (int i = 0; i < N; i++) asm volatile("" : "=f"(d[i]));
}
__device__ __forceinline__ void mbar_init(uint32_t bar, uint32_t cnt) { asm volatile("mbarrier.init.shared::cta.b64 [%0], %1;" ::"r"(bar), "r"(cnt) : "memory"); }
__device__ __forceinline__ void mbar_expect_tx(uint32_t bar, uint32_t bytes) { asm volatile("mbarrier.arrive.expect_tx.shared::cta.b64 _, [%0], %1;" ::"r"(bar), "r"(bytes) : "memory"); }
__device__ __forceinline__ void mbar_arrive(uint32_t bar) { asm volatile("mbarrier.arrive.shared::cta.b64 _, [%0];" ::"r"(bar) : "memory"); }
__device__ __forceinline__ void mbar_arrive_cluster(uint32_t bar, uint32_t cta) {
    asm volatile("{\n.reg .b32 ra;\nmapa.shared::cluster.u32 ra, %0, %1;\nmbarrier.arrive.shared::cluster.b64 _, [ra];\n}" ::"r"(bar), "r"(cta) : "memory");
}
__device__ __forceinline__ void mbar_wait(uint32_t bar, uint32_t parity) {
    asm volatile(
        "{\n.reg .pred p;\n.reg .u32 n;\n"
        "mbarrier.try_wait.parity.shared::cta.b64 p, [%0], %1;\n"
        "@p bra.uni LAB_DONE;\n"
        "mov.u32 n, 0;\n"
        "LAB_WAIT:\n"
        "mbarrier.try_wait.parity.shared::cta.b64 p, [%0], %1, " SLEEPNS ";\n"
        "@p bra.uni LAB_DONE;\n"
        "add.u32 n, n, 1;\n"
        "setp.ge.u32 p, n, 0x400000;\n"
        "@p trap;\n"
        "bra.uni LAB_WAIT;\n"
        "LAB_DONE:\n}" ::"r"(bar), "r"(parity) : "memory");
}
__device__ __forceinline__ void flag_wait(const uint32_t* p, uint32_t target) {
    asm volatile(
        "{\n.reg .pred p;\n.reg .u32 n;\n.reg .s32 v;\n"
        "mov.u32 n, 0;\n"
        "LAB_WAIT:\n"
        "ld.acquire.gpu.global.s32 v, [%0];\n"
        "sub.s32 v, v, %1;\n"
        "setp.ge.s32 p, v, 0;\n"
        "@p bra.uni LAB_DONE;\n"
        "add.u32 n, n, 1;\n"
        "setp.ge.u32 p, n, 0x800000;\n"
        "@p trap;\n"
        "bra.uni LAB_WAIT;\n"
        "LAB_DONE:\n}" ::"l"(p), "r"(target) : "memory");
}
__device__ __forceinline__ void flag_add(uint32_t* p) { asm volatile("red.release.gpu.global.add.u32 [%0], 1;" ::"l"(p) : "memory"); }
__device__ __forceinline__ void flag_addv(uint32_t* p, uint32_t v) { asm volatile("red.release.gpu.global.add.u32 [%0], %1;" ::"l"(p), "r"(v) : "memory"); }
__device__ __forceinline__ uint32_t flag_ld(const uint32_t* p) { uint32_t v; asm volatile("ld.acquire.gpu.global.u32 %0, [%1];" : "=r"(v) : "l"(p) : "memory"); return v; }
__device__ __forceinline__ void fence_async_global() { asm volatile("fence.proxy.async.global;" ::: "memory"); }
__device__ __forceinline__ void fence_async_shared() { asm volatile("fence.proxy.async.shared::cta;" ::: "memory"); }
__device__ __forceinline__ bool elect_one() {
    uint32_t p;
    asm volatile("{\n.reg .pred p;\nelect.sync _|p, 0xffffffff;\nselp.u32 %0, 1, 0, p;\n}" : "=r"(p));
    return p != 0;
}
__device__ __forceinline__ uint32_t mbar_test(uint32_t bar, uint32_t parity) {
    uint32_t p;
    asm volatile("{\n.reg .pred p;\nmbarrier.test_wait.parity.shared::cta.b64 p, [%1], %2;\nselp.u32 %0, 1, 0, p;\n}" : "=r"(p) : "r"(bar), "r"(parity) : "memory");
    return p;
}
__device__ __forceinline__ void mbar_wait_unless(uint32_t done, uint32_t bar, uint32_t parity) {
    asm volatile(
        "{\n.reg .pred p;\n.reg .u32 n;\n"
        "setp.ne.u32 p, %2, 0;\n"
        "@p bra.uni LAB_DONE;\n"
        "mov.u32 n, 0;\n"
        "LAB_WAIT:\n"
        "mbarrier.try_wait.parity.shared::cta.b64 p, [%0], %1, 1000;\n"
        "@p bra.uni LAB_DONE;\n"
        "add.u32 n, n, 1;\n"
        "setp.ge.u32 p, n, 0x400000;\n"
        "@p trap;\n"
        "bra.uni LAB_WAIT;\n"
        "LAB_DONE:\n}" ::"r"(bar), "r"(parity), "r"(done) : "memory");
}
__device__ __forceinline__ void bulk_s2g(void* dst, uint32_t src, uint32_t bytes) {
    asm volatile("cp.async.bulk.global.shared::cta.bulk_group [%0], [%1], %2;" ::"l"(dst), "r"(src), "r"(bytes) : "memory");
}
__device__ __forceinline__ void bulk_s2c(uint32_t addr, uint32_t bytes, uint32_t bar, uint32_t cta) {
    asm volatile("{\n.reg .b32 d, b;\nmapa.shared::cluster.u32 d, %0, %3;\nmapa.shared::cluster.u32 b, %2, %3;\n"
                 "cp.async.bulk.shared::cluster.shared::cta.mbarrier::complete_tx::bytes [d], [%0], %1, [b];\n}"
                 ::"r"(addr), "r"(bytes), "r"(bar), "r"(cta) : "memory");
}
__device__ __forceinline__ void sts32(uint32_t a, uint32_t v) { asm volatile("st.shared.u32 [%0], %1;" ::"r"(a), "r"(v) : "memory"); }
__device__ __forceinline__ void sts128(uint32_t a, uint32_t x, uint32_t y, uint32_t z, uint32_t w) { asm volatile("st.shared.v4.u32 [%0], {%1, %2, %3, %4};" ::"r"(a), "r"(x), "r"(y), "r"(z), "r"(w) : "memory"); }
__device__ __forceinline__ uint32_t lds32(uint32_t a) { uint32_t v; asm volatile("ld.shared.u32 %0, [%1];" : "=r"(v) : "r"(a) : "memory"); return v; }
__device__ __forceinline__ void tma_2d(uint32_t dst, const CUtensorMap* tm, int c0, int c1, uint32_t bar) {
    asm volatile("cp.async.bulk.tensor.2d.shared::cluster.global.mbarrier::complete_tx::bytes [%0], [%1, {%3, %4}], [%2];"
                 ::"r"(dst), "l"(tm), "r"(bar), "r"(c0), "r"(c1) : "memory");
}
__device__ __forceinline__ void tma_2d_mc(uint32_t dst, const CUtensorMap* tm, int c0, int c1, uint32_t bar) {
    asm volatile("cp.async.bulk.tensor.2d.shared::cluster.global.mbarrier::complete_tx::bytes.multicast::cluster [%0], [%1, {%3, %4}], [%2], %5;"
                 ::"r"(dst), "l"(tm), "r"(bar), "r"(c0), "r"(c1), "h"((uint16_t)3) : "memory");
}
__device__ __forceinline__ void tma_3d_mc(uint32_t dst, const CUtensorMap* tm, int c1, int c2, uint32_t bar) {
    asm volatile("cp.async.bulk.tensor.3d.shared::cluster.global.mbarrier::complete_tx::bytes.multicast::cluster [%0], [%1, {0, %3, %4}], [%2], %5;"
                 ::"r"(dst), "l"(tm), "r"(bar), "r"(c1), "r"(c2), "h"((uint16_t)3) : "memory");
}
__device__ __forceinline__ void bulk_g2s(uint32_t dst, const void* src, uint32_t bytes, uint32_t bar) {
    asm volatile("cp.async.bulk.shared::cluster.global.mbarrier::complete_tx::bytes [%0], [%1], %2, [%3];"
                 ::"r"(dst), "l"(src), "r"(bytes), "r"(bar) : "memory");
}
__device__ __forceinline__ void bulk_g2s_mc(uint32_t dst, const void* src, uint32_t bytes, uint32_t bar) {
    asm volatile("cp.async.bulk.shared::cluster.global.mbarrier::complete_tx::bytes.multicast::cluster [%0], [%1], %2, [%3], %4;"
                 ::"r"(dst), "l"(src), "r"(bytes), "r"(bar), "h"((uint16_t)3) : "memory");
}
__device__ __forceinline__ void mma_16816(float* d, uint32_t a0, uint32_t a1, uint32_t a2, uint32_t a3, uint32_t b0, uint32_t b1) {
    asm volatile("mma.sync.aligned.m16n8k16.row.col.f32.bf16.bf16.f32 {%0,%1,%2,%3}, {%4,%5,%6,%7}, {%8,%9}, {%0,%1,%2,%3};"
                 : "+f"(d[0]), "+f"(d[1]), "+f"(d[2]), "+f"(d[3]) : "r"(a0), "r"(a1), "r"(a2), "r"(a3), "r"(b0), "r"(b1));
}
__device__ __forceinline__ uint32_t movm_t(uint32_t a) { uint32_t d; asm volatile("movmatrix.sync.aligned.m8n8.trans.b16 %0, %1;" : "=r"(d) : "r"(a)); return d; }
__device__ __forceinline__ uint32_t ldg32(const uint8_t* p) { uint32_t v; asm volatile("ld.global.u32 %0, [%1];" : "=r"(v) : "l"(p) : "memory"); return v; }
__device__ __forceinline__ void stg32(uint8_t* p, uint32_t v) { asm volatile("st.global.u32 [%0], %1;" ::"l"(p), "r"(v) : "memory"); }
#define PROF(i) do {} while (0)
#define TRACE() do {} while (0)
#define PROFX(w, i) do {} while (0)

struct Ring {
    uint32_t slot;
    uint32_t phase;
    __device__ __forceinline__ void next() { if (++slot == NSTAGE) { slot = 0; phase ^= 1; } }
};

__device__ __forceinline__ void load_q(uint32_t (&q)[8], uint32_t qa, int lane) {
    q[0] = lds32(qa + lane * 4);       q[1] = lds32(qa + lane * 4 + 256);
    q[2] = lds32(qa + lane * 4 + 128); q[3] = lds32(qa + lane * 4 + 384);
    const uint32_t t0 = lds32(qa + 512 + (lane & ~3)), t1 = lds32(qa + 544 + (lane & ~3));
    q[4] = (lane & 3) == 2 ? t0 : 0u;  q[5] = (lane & 3) == 2 ? t1 : 0u;
}

__device__ __forceinline__ bool store_o(const float (&o)[12], uint8_t* op, int hp, int lane, uint32_t gaddr) {
    const float l0 = __shfl_sync(0xffffffffu, o[8], (lane & ~3) | 1);
    const float l1 = __shfl_sync(0xffffffffu, o[10], (lane & ~3) | 1);
    const float i0 = rcp_fast(l0) * __uint_as_float(lds32(gaddr)), i1 = rcp_fast(l1) * __uint_as_float(lds32(gaddr + 32));
    bool ok = (l0 >= 0x1p-30f) && (l0 <= 0x1p60f) && (l1 >= 0x1p-30f) && (l1 <= 0x1p60f);
#pragma unroll
    for (int b = 0; b < 3; b++) {
        const int q8 = hp * 3 + b;
        uint8_t* p = op + (q8 >> 1) * 4096 + (q8 & 1) * 128;
        float a0 = o[4 * b] * i0, a1 = o[4 * b + 1] * i0, a2 = o[4 * b + 2] * i1, a3 = o[4 * b + 3] * i1;
        if (b == 2 && (lane & 3) != 0) a0 = a1 = a2 = a3 = 0.f;
        ok = ok && (fabsf(a0) + fabsf(a1) + fabsf(a2) + fabsf(a3) <= 0x1p126f);
        stg32(p, pack(a0, a1));
        stg32(p + 256, pack(a2, a3));
    }
    return !__all_sync(0xffffffffu, ok);
}

__device__ __forceinline__ void attn_true_max(float (&o)[12], const uint32_t (&q)[8], const uint8_t* kv) {
    float m0 = -INFINITY, m1 = -INFINITY;
#pragma unroll
    for (int i = 0; i < 12; i++) o[i] = 0.f;
#pragma unroll 1
    for (int kb = 0; kb < SEQ / 16; kb++) {
        uint32_t t[2][5];
#pragma unroll
        for (int g = 0; g < 2; g++)
#pragma unroll
            for (int ch = 0; ch < 5; ch++) t[g][ch] = ldg32(kv + (kb * 2 + g) * 640 + ch * 128);
        float s[2][4];
#pragma unroll
        for (int g = 0; g < 2; g++) {
            s[g][0] = s[g][1] = s[g][2] = s[g][3] = 0.f;
            mma_16816(s[g], q[0], q[1], q[2], q[3], t[g][0], t[g][1]);
            mma_16816(s[g], q[4], q[5], 0u, 0u, t[g][4], 0u);
        }
        float x0 = fmaxf(fmaxf(s[0][0], s[0][1]), fmaxf(s[1][0], s[1][1]));
        float x1 = fmaxf(fmaxf(s[0][2], s[0][3]), fmaxf(s[1][2], s[1][3]));
        x0 = fmaxf(x0, __shfl_xor_sync(0xffffffffu, x0, 1)); x0 = fmaxf(x0, __shfl_xor_sync(0xffffffffu, x0, 2));
        x1 = fmaxf(x1, __shfl_xor_sync(0xffffffffu, x1, 1)); x1 = fmaxf(x1, __shfl_xor_sync(0xffffffffu, x1, 2));
        const float n0 = fmaxf(m0, x0), n1 = fmaxf(m1, x1);
        const float u0 = (n0 == -INFINITY) ? 0.f : n0, u1 = (n1 == -INFINITY) ? 0.f : n1;
        const float c0 = ex2(m0 - u0), c1 = ex2(m1 - u1);
        m0 = n0; m1 = n1;
#pragma unroll
        for (int b = 0; b < 3; b++) { o[4 * b] *= c0; o[4 * b + 1] *= c0; o[4 * b + 2] *= c1; o[4 * b + 3] *= c1; }
        const uint32_t a0 = pack(ex2(s[0][0] - u0), ex2(s[0][1] - u0)), a1 = pack(ex2(s[0][2] - u1), ex2(s[0][3] - u1));
        const uint32_t a2 = pack(ex2(s[1][0] - u0), ex2(s[1][1] - u0)), a3 = pack(ex2(s[1][2] - u1), ex2(s[1][3] - u1));
#pragma unroll
        for (int b = 0; b < 3; b++) mma_16816(&o[4 * b], a0, a1, a2, a3, movm_t(t[0][2 + b]), movm_t(t[1][2 + b]));
    }
}

__device__ __forceinline__ float geglu2(float g, float u) {
    const float p = fmaf(g * g, 0.044715f * 0.7978845608028654f, 0.7978845608028654f);
    const float th = tanh_fast(g * p);
    const float y = g * u;
    return fmaf(y, th, y);
}

struct Attn {
    float s[32];
    float o[12];
    uint32_t p[16];
    uint32_t q[8];
};

__global__ void __cluster_dims__(2, 1, 1) __launch_bounds__(384, 1)
fused_kernel(const __grid_constant__ CUtensorMap tm_x, const __grid_constant__ CUtensorMap tm_qkv,
             const __grid_constant__ CUtensorMap tm_qkv8,
             const __grid_constant__ CUtensorMap tm_wg, const __grid_constant__ CUtensorMap tm_wu,
             const __grid_constant__ CUtensorMap tm_wd, const __grid_constant__ CUtensorMap tm_wo,
             const __grid_constant__ CUtensorMap tm_wd16, const __grid_constant__ CUtensorMap tm_wo16,
             const __nv_bfloat16* __restrict__ x, const __nv_bfloat16* __restrict__ gate_w,
             const uint8_t* __restrict__ wqkv, const uint8_t* __restrict__ wgt, const uint8_t* __restrict__ wu,
             __nv_bfloat16* __restrict__ out) {
    extern __shared__ uint8_t smem_raw[];
    const uint32_t sb = ((uint32_t)__cvta_generic_to_shared(smem_raw) + 1023) & ~1023u;
    const uint32_t bars = sb + OFF_BAR;
    const uint32_t bar_full = bars, bar_empty = bars + 64;
    const uint32_t bar_ev = bars + 128;
    const uint32_t bar_rdy = bars + 256;
    const uint32_t bar_ep = bars + 320, bar_gate = bars + 328;
    const uint32_t bar_st = bars + 336;
    const uint32_t bar_dummy = bars + 368, s_epoch = bars + 384, s_zero = bars + 388, s_gate = bars + 512;

    const int cta = blockIdx.x;
    const int rank = cta & 1;
    const int j = (cta >> 1) & 7;
    const int m = (cta >> 4) * 2 + rank;
    const int hf = j >> 2, nt = j & 3;
    const int warp = __shfl_sync(0xffffffffu, threadIdx.x >> 5, 0);
    const int lane = threadIdx.x & 31;
    const int wg = warp >> 2;

    if (elect_one()) {
        const uint32_t lo = warp < 2 ? 2 : (warp >= 8 && warp <= 10) ? 1 : 4, hi = warp == 10 ? 4 : lo;
        mbar_init(bars + warp * 32, lo); mbar_init(bars + warp * 32 + 8, lo);
        mbar_init(bars + warp * 32 + 16, hi); mbar_init(bars + warp * 32 + 24, hi);
        sts32(s_zero, 0u);
        asm volatile("fence.mbarrier_init.release.cluster;" ::: "memory");
    }
    asm volatile("barrier.cluster.arrive.relaxed.aligned;" ::: "memory");
    if (PF_X) {
        const int t = threadIdx.x;
        const uint8_t* p = t < 128 ? (const uint8_t*)x + (size_t)(m * 128 + t) * (DM * 2)
                         : t < 224 ? wqkv + (size_t)(t & 31) * (3 * DM * 2) + ((t >> 5) - 4) * (DM * 2) + j * 144 + rank * 128
                                   : (rank ? wu : wgt) + (size_t)(t - 224) * (FF * 2) + (j * 576 + 512) * 2;
        if (t < 256) asm volatile("prefetch.global.L2 [%0];" ::"l"(p));
        else if (t == 288) {
            asm volatile("prefetch.tensormap [%0];" ::"l"(&tm_x) : "memory");
            asm volatile("prefetch.tensormap [%0];" ::"l"(&tm_qkv) : "memory");
            asm volatile("prefetch.tensormap [%0];" ::"l"(&tm_qkv8) : "memory");
            asm volatile("prefetch.tensormap [%0];" ::"l"(rank ? &tm_wu : &tm_wg) : "memory");
        }
    }
    asm volatile("barrier.cluster.wait.acquire.aligned;" ::: "memory");

    if (wg == 2) {
        asm volatile("setmaxnreg.dec.sync.aligned.u32 24;");
        if (warp == 8) {
            if (elect_one()) {
                Ring r{0, 1};
                const int row0 = m * 128;
                const CUtensorMap* tw = rank ? &tm_wu : &tm_wg;
                PROFX(0, 40); PROFX(1, 40);
#pragma unroll 1
                for (int kk = 0; kk < 18; kk++) {
                    if (kk == 1) { PROFX(0, 41); PROFX(1, 41); }
                    if (kk == 6) { PROFX(0, 42); PROFX(1, 42); }
                    const uint32_t st = sb + r.slot * SLOT, fb = bar_full + r.slot * 8;
                    mbar_wait(bar_empty + r.slot * 8, r.phase);
                    mbar_arrive(fb);
                    mbar_expect_tx(fb, 8192 + 12288 + 8192 + 1536);
                    tma_2d(st + OFF_AX, &tm_x, kk * 32, row0, fb);
#pragma unroll
                    for (int b = 0; b < 3; b++) tma_2d_mc(st + b * 4096 + rank * 2048, &tm_qkv, b * 576 + j * 72, kk * 32 + rank * 16, fb);
                    tma_2d_mc(st + 12288 + rank * 4096, tw, j * 576 + 512, kk * 32, fb);
#pragma unroll
                    for (int b = 0; b < 3; b++) tma_2d_mc(st + OFF_TL + b * 512 + rank * 256, &tm_qkv8, b * 576 + j * 72 + 64, kk * 32 + rank * 16, fb);
                    r.next();
                }
#pragma unroll 1
                for (int t = 0; t < 4; t++)
#pragma unroll 1
                    for (int kk = 0; kk < 18; kk++) {
                        const uint32_t st = sb + r.slot * SLOT, fb = bar_full + r.slot * 8;
                        mbar_wait(bar_empty + r.slot * 8, r.phase);
                        mbar_expect_tx(fb, 8192 + 16384);
                        tma_2d_mc(st + rank * 8192, tw, j * 576 + t * 128, kk * 32, fb);
                        tma_2d_mc(st + rank * 8192 + 4096, tw, j * 576 + t * 128 + 64, kk * 32, fb);
                        tma_2d(st + OFF_AX, &tm_x, kk * 32, row0, fb);
                        r.next();
                    }
                const uint8_t* a2 = g_a2 + (size_t)m * A2_TILE;
                mbar_wait(bar_rdy + 4 * 8, 0);
#pragma unroll 1
                for (int n = 0; n < 48; n++) {
                    const int u = n >> 2, jj = n & 3;
                    const uint32_t st = sb + r.slot * SLOT, fb = bar_full + r.slot * 8;
                    mbar_wait(bar_empty + r.slot * 8, r.phase);
                    mbar_expect_tx(fb, 12288 + 18432);
                    const int ks = (hf * 4 + jj) * 36 + u * 3;
#pragma unroll
                    for (int b = 0; b < 2; b++) tma_2d_mc(st + b * 6144 + rank * 3072, &tm_wd, nt * 128 + b * 64, ks * 16 + rank * 24, fb);
                    tma_3d_mc(st + 12288 + rank * 3072, &tm_wd16, ks * 16 + rank * 24, 64 + nt * 2, fb);
                    if (jj == 0) { mbar_wait(bar_rdy + ((3 * u + 2) >> 3) * 8, 0); fence_async_global(); }
                    bulk_g2s(st + OFF_A2, a2 + ks * 4096, 12288, fb);
                    r.next();
                }
#pragma unroll 1
                for (int n = 0; n < 6; n++) {
                    const uint32_t st = sb + r.slot * SLOT, fb = bar_full + r.slot * 8;
                    mbar_wait(bar_empty + r.slot * 8, r.phase);
                    mbar_expect_tx(fb, 12288 + 18432);
                    const int head = hf * 16 + ((n & 1) * 2 + rank) * 4 + (n >> 1);
#pragma unroll
                    for (int b = 0; b < 2; b++) tma_2d_mc(st + b * 6144 + rank * 3072, &tm_wo, nt * 128 + b * 64, head * 18, fb);
                    tma_3d_mc(st + 12288 + rank * 3072, &tm_wo16, head * 18, 64 + nt * 2, fb);
                    if (n == 0) { mbar_wait(bar_rdy + 5 * 8, 0); fence_async_global(); }
                    bulk_g2s(st + OFF_A2, a2 + (288 + (hf * 8 + n) * 3) * 4096, 12288, fb);
                    r.next();
                }
#pragma unroll 1
                for (int n = 0; n < 2; n++) {
                    mbar_wait(bar_empty + r.slot * 8, r.phase);
                    mbar_arrive(bar_full + r.slot * 8);
                    r.next();
                }
#pragma unroll 1
                for (int n = 0; n < 4; n++) {
                    const uint32_t st = sb + r.slot * SLOT, fb = bar_full + r.slot * 8;
                    mbar_wait(bar_empty + r.slot * 8, r.phase);
                    mbar_arrive(fb);
                    mbar_expect_tx(fb, 12288 + 12288);
                    const int head = ((((j >> 1) + n) & 3) * 2 + rank) * 4 + 3;
                    tma_2d_mc(st + rank * 3072, &tm_wo, nt * 128 + hf * 64, head * 18, fb);
                    tma_2d_mc(st + 6144 + rank * 3072, &tm_wo, 512 + nt * 16 + hf * 8, head * 18, fb);
                    r.next();
                }
                mbar_arrive(bar_rdy + 7 * 8);
            }
        } else if (warp == 9) {
            if (elect_one()) {
                const uint32_t ep = g_flags[FL_E + cta * 32] + 1;
                g_flags[FL_E + cta * 32] = ep;
                sts32(s_epoch, ep);
                mbar_arrive(bar_ep);
                Ring r{4, 0};
                const uint8_t* kv = g_kv + (size_t)(j * 4) * HEAD_BYTES + rank * 2560;
                const int rot = (cta >> 4) * 4;
                flag_wait(&g_flags[FL_KV + j * 32], ep * 32);
                fence_async_global();
                PROFX(0, 37); PROFX(1, 37);
#pragma unroll 1
                for (int it = 4; it < 128; it++) {
                    const uint32_t fb = bar_full + r.slot * 8;
                    if (it == 24) { flag_wait(&g_flags[FL_KV + j * 32 + 1], ep * 32); fence_async_global(); }
                    mbar_wait(bar_empty + r.slot * 8, r.phase);
                    mbar_expect_tx(fb, 5120);
                    bulk_g2s_mc(sb + r.slot * SLOT + OFF_KV + rank * 2560, kv + ((it & 96) + ((it + rot) & 31)) * 5120, 2560, fb);
                    r.next();
                }
                uint32_t* fr = &g_flags[FL_M + m * 64 + FM_R];
                mbar_wait(bar_ev + 6 * 8, 0);
                mbar_wait(bar_ev + 14 * 8, 0);
                flag_add(fr + j);
                flag_wait(fr + (j ^ 4), ep);
                mbar_arrive(bar_rdy + 6 * 8);
            }
        } else {
            const int w = warp - 10;
            if (elect_one()) {
                const uint32_t mine = rank * 2 + w, other = (rank ^ 1) * 2 + w;
                mbar_wait(bar_st + w * 8, 0);
                PROFX(w, 32);
                bulk_s2g(g_kv + (size_t)(j * 4) * HEAD_BYTES + (m * 16 + w * 8) * 640, sb + mine * SLOT + OFF_KV, 5120);
                asm volatile("cp.async.bulk.commit_group;" ::: "memory");
                mbar_arrive(bar_full + mine * 8);
                mbar_expect_tx(bar_full + other * 8, 5120);
                mbar_wait(bar_empty + mine * 8, 0);
                bulk_s2c(sb + mine * SLOT + OFF_KV, 5120, bar_full + mine * 8, rank ^ 1);
                asm volatile("cp.async.bulk.wait_group 0;" ::: "memory");
                flag_add(&g_flags[FL_KV + j * 32]);
                PROFX(w, 34);
                mbar_wait(bar_ev + (w * 8 + 4) * 8, 0);
                flag_add(&g_flags[FL_KV + j * 32 + 1]);
            }
            __syncwarp();
#pragma unroll 1
            for (int b = 0; b < 2; b++) {
                const int row = m * 128 + j * 16 + w * 8 + b * 4 + (lane >> 3);
                const uint4* xp = (const uint4*)(x + (size_t)row * DM) + (lane & 7);
                const uint4* wp = (const uint4*)gate_w + (lane & 7);
                float z = 0.f;
#pragma unroll 1
                for (int i = 0; i < 9; i++) {
                    const uint4 a = __ldg(xp + i * 8), c = __ldg(wp + i * 8);
                    z = fmaf(__uint_as_float(a.x << 16), __uint_as_float(c.x << 16), z); z = fmaf(__uint_as_float(a.x & 0xffff0000u), __uint_as_float(c.x & 0xffff0000u), z);
                    z = fmaf(__uint_as_float(a.y << 16), __uint_as_float(c.y << 16), z); z = fmaf(__uint_as_float(a.y & 0xffff0000u), __uint_as_float(c.y & 0xffff0000u), z);
                    z = fmaf(__uint_as_float(a.z << 16), __uint_as_float(c.z << 16), z); z = fmaf(__uint_as_float(a.z & 0xffff0000u), __uint_as_float(c.z & 0xffff0000u), z);
                    z = fmaf(__uint_as_float(a.w << 16), __uint_as_float(c.w << 16), z); z = fmaf(__uint_as_float(a.w & 0xffff0000u), __uint_as_float(c.w & 0xffff0000u), z);
                }
                z += __shfl_xor_sync(0xffffffffu, z, 1); z += __shfl_xor_sync(0xffffffffu, z, 2); z += __shfl_xor_sync(0xffffffffu, z, 4);
                if ((lane & 7) == 0) g_gate[row] = rcp_fast(1.f + ex2(-1.4426950408889634f * z));
            }
            __syncwarp();
            uint32_t* fm = &g_flags[FL_M + m * 64];
            if (lane == 0) flag_add(fm + FM_G);
            mbar_wait(bar_ep, 0);
            const uint32_t ep = lds32(s_epoch);
            if (w == 1) {
                flag_wait(fm + FM_G, ep * 16);
                const uint4 gv = __ldcg((const uint4*)(g_gate + m * 128) + lane);
                sts128(s_gate + lane * 16, gv.x, gv.y, gv.z, gv.w);
                __syncwarp();
                if (lane == 0) mbar_arrive(bar_gate);
            }
            if (elect_one()) {
#pragma unroll 1
                for (int i = 0; i < 6; i++) {
                    const int e = i == 0 ? 4 : i == 5 ? 5 : i - 1;
                    mbar_wait(bar_ev + (w * 8 + e) * 8, 0);
                    flag_add(fm + FM_H + hf * 8 + e);
                    if (w == 0) { flag_wait(fm + FM_H + hf * 8 + e, ep * 8); mbar_arrive(bar_rdy + e * 8); }
                }
                mbar_wait(bar_ev + (w * 8 + 7) * 8, 0);
                PROFX(w, 48);
                flag_addv(fm + FM_LATE, 1u << ((j >> 1) * 8));
                PROFX(w, 49);
                mbar_wait(bar_rdy + 7 * 8, 0);
                const uint32_t base = (ep - 1) * 0x04040404u;
                uint32_t todo = 5u << w, tries = 0;
#pragma unroll 1
                while (todo) {
                    const uint32_t got = flag_ld(fm + FM_LATE) - base;
                    fence_async_global();
#pragma unroll 1
                    for (int n = w; n < 4; n += 2) {
                        const int pr = ((j >> 1) + n) & 3;
                        if (((todo >> n) & 1) && ((got >> (pr * 8)) & 4)) {
                            bulk_g2s(sb + (2 + n) * SLOT + OFF_A2, g_a2 + (size_t)m * A2_TILE + (288 + ((pr >> 1) * 8 + 6 + (pr & 1)) * 3) * 4096, 12288, bar_full + (2 + n) * 8);
                            todo &= ~(1u << n);
                        }
                    }
                    asm volatile("{\n.reg .pred p;\nsetp.gt.u32 p, %0, 0x800000;\n@p trap;\n}" ::"r"(++tries));
                }
                PROFX(w, 50);
            }
        }
    } else {
        asm volatile("setmaxnreg.inc.sync.aligned.u32 240;");
        const int wq = warp & 3;
        const int c = lane & 3;
        const int tid = threadIdx.x & 127;
        const int grp = wg * 8 + wq * 2;
        const uint32_t sbd = (sb & 0x3FFFF) >> 4;
        uint32_t sd = sbd, pd = sbd, fb = bar_full, pb = bar_full, ph = 0;
#define STAGE_NEXT do { pd = sd; sd = (sd == sbd + (NSTAGE - 1) * (SLOT >> 4)) ? sbd : sd + (SLOT >> 4);   \
                        pb = fb; fb += 8; if (fb == bar_full + NSTAGE * 8) { fb = bar_full; ph ^= 1; } } while (0)
        auto release = [&]() { if (tid < 2) mbar_arrive_cluster(pb + 64, tid); };
        auto signal = [&](int e) { __syncwarp(); if (lane == 0) mbar_arrive(bar_ev + (wg * 8 + e) * 8); };
        Attn at;
        PROF(0);

        uint8_t* a2w = g_a2 + (size_t)m * A2_TILE + grp * 256 + lane * 4;
        const uint32_t qa = sb + OFF_Q + warp * 576;
        {
            float acc[96], tl[12], gu[64];
#pragma unroll 1
            for (int kk = 0; kk < 18; kk++) {
                mbar_wait(fb, ph);
                if (kk == 0) PROF(21);
                if (kk == 6) PROF(22);
                if (kk == 12) PROF(23);
                const uint32_t da = sd + wg * 256 + dlo(OFF_AX, 16), db = sd + dlo(0, 4096), dt = sd + dlo(OFF_TL, 128);
                wg_fence();
                wgmma_ss_n192_t1<HI_X, HI_W>(acc, da, db, kk != 0);
                wgmma_ss_n24_t1<HI_X, HI_T>(tl, da, dt, kk != 0);
                wgmma_ss_n128_t1<HI_X, HI_W>(gu, da, db + 768, kk != 0);
                wgmma_ss_n192_t1<HI_X, HI_W>(acc, da + 2, db + 128, 1);
                wgmma_ss_n24_t1<HI_X, HI_T>(tl, da + 2, dt + 16, 1);
                wgmma_ss_n128_t1<HI_X, HI_W>(gu, da + 2, db + 768 + 128, 1);
                wg_commit();
                wg_wait<1>();
                if (kk > 0) release();
                STAGE_NEXT;
            }
            wg_wait<0>();
            fence_regs(acc); fence_regs(tl); fence_regs(gu);
            release();
            PROF(1);
            constexpr float QS = 0.23570226039551584f * 1.4426950408889634f;
            uint32_t kp[9][2], vp[9][2];
#pragma unroll
            for (int i = 0; i < 9; i++) {
                const float* k4 = i < 8 ? &acc[32 + 4 * i] : &tl[4];
                const float* v4 = i < 8 ? &acc[64 + 4 * i] : &tl[8];
                kp[i][0] = pack(k4[0], k4[1]); kp[i][1] = pack(k4[2], k4[3]);
                vp[i][0] = pack(v4[0], v4[1]); vp[i][1] = pack(v4[2], v4[3]);
            }
            const int quad = lane & ~3;
            const uint32_t cst = c == 1 ? 0x3F80u : 0u;
            {
                const uint32_t a = sb + (rank * 2 + wg) * SLOT + OFF_KV + wq * 1280 + lane * 4;
#pragma unroll
                for (int r = 0; r < 2; r++) {
                    const uint32_t kt = __shfl_sync(0xffffffffu, kp[2][r], quad);
                    sts32(a + r * 640, kp[0][r]);       sts32(a + r * 640 + 128, kp[1][r]);
                    sts32(a + r * 640 + 256, vp[0][r]); sts32(a + r * 640 + 384, vp[1][r]);
                    sts32(a + r * 640 + 512, c == 0 ? vp[2][r] : c == 2 ? kt : cst);
                }
                fence_async_shared();
                __syncwarp();
                if (lane == 0) mbar_arrive(bar_st + wg * 8);
            }
            PROF(2);
#pragma unroll
            for (int i = 0; i < 9; i++) {
                const float* q4 = i < 8 ? &acc[4 * i] : &tl[0];
                const uint32_t q0 = pack(q4[0] * QS, q4[1] * QS), q1 = pack(q4[2] * QS, q4[3] * QS);
                if (i < 2) { at.q[2 * i] = q0; at.q[2 * i + 1] = q1; }
                else {
                    if (i == 2) {
                        const uint32_t t0 = __shfl_sync(0xffffffffu, q0, quad), t1 = __shfl_sync(0xffffffffu, q1, quad);
                        at.q[4] = c == 2 ? t0 : 0u; at.q[5] = c == 2 ? t1 : 0u;
                    }
                    const int lc = 8 * i + 2 * c;
                    const int hd = (lc * 3641) >> 16;
                    const int d = lc - hd * 18;
                    const bool last = (i & 1) == 0 && c == i / 2 - 1;
                    const uint32_t aq = qa + hd * 4608 + (last ? 512 + (lane >> 2) * 4 : (d >> 3) * 128 + (d & 7) * 2 + (lane >> 2) * 16);
                    if (i > 2 || c > 0) { sts32(aq, q0); sts32(aq + (last ? 32 : 256), q1); }
                }
            }
            uint32_t hv[16];
#pragma unroll
            for (int i = 0; i < 16; i++) hv[i] = pack(geglu2(gu[2 * i], gu[32 + 2 * i]), geglu2(gu[2 * i + 1], gu[32 + 2 * i + 1]));
            fence_regs(hv);
            uint8_t* kg = g_kv + (size_t)(j * 4) * HEAD_BYTES + (m * 16 + grp) * 640 + lane * 4;
#pragma unroll
            for (int h = 1; h < 4; h++) {
                const int src = quad | ((c + h) & 3);
#pragma unroll
                for (int r = 0; r < 2; r++) {
                    uint8_t* p = kg + h * HEAD_BYTES + r * 640;
#pragma unroll
                    for (int q = 0; q < 2; q++) {
                        stg32(p + q * 128, __shfl_sync(0xffffffffu, c >= h ? kp[2 * h + q][r] : kp[2 * h + q + 1][r], src));
                        stg32(p + 256 + q * 128, __shfl_sync(0xffffffffu, c >= h ? vp[2 * h + q][r] : vp[2 * h + q + 1][r], src));
                    }
                    const uint32_t kt = __shfl_sync(0xffffffffu, kp[2 * h + 2][r], quad | h), vt = __shfl_sync(0xffffffffu, vp[2 * h + 2][r], quad | h);
                    stg32(p + 512, c == 0 ? vt : c == 2 ? kt : cst);
                }
            }
            uint8_t* hp = a2w + (j * 36 + 32) * 4096;
#pragma unroll
            for (int i = 0; i < 16; i++) stg32(hp + (i >> 2) * 4096 + ((i >> 1) & 1) * 128 + (i & 1) * 256, hv[i]);
            signal(4);
            PROF(3);
            mbar_wait(fb, ph);
            PROF(38);
        }

        const uint32_t gaddr = s_gate + (grp * 8 + (lane >> 2)) * 4;
        at.q[6] = lds32(s_zero); at.q[7] = lds32(s_zero);
#pragma unroll
        for (int i = 0; i < 16; i++) at.p[i] = 0u;
#pragma unroll
        for (int i = 0; i < 12; i++) at.o[i] = 0.f;
        fence_regs(at.q); fence_regs(at.p); fence_regs(at.o);
        pd = sd;
        uint32_t rel = bar_dummy;
        asm volatile("mapa.shared::cluster.u32 %0, %0, %1;" : "+r"(rel) : "r"(tid & 1));
        const uint32_t rel_off = rel - bar_dummy + 64;

#define O_PTR(item) (a2w + (288 + (hf * 8 + (item) * 2 + (nt >> 1)) * 3) * 4096)
#define ISSUE_PV() do {                                                                                    \
            const uint32_t dv = pd + dlo(OFF_KV + 256, 640);                                               \
            wgmma_rs_n24_t1<HI_V>(at.o, at.p[0], at.p[1], at.p[2], at.p[3], dv, 1);                        \
            wgmma_rs_n24_t1<HI_V>(at.o, at.p[4], at.p[5], at.p[6], at.p[7], dv + 80, 1);                   \
            wgmma_rs_n24_t1<HI_V>(at.o, at.p[8], at.p[9], at.p[10], at.p[11], dv + 160, 1);                \
            wgmma_rs_n24_t1<HI_V>(at.o, at.p[12], at.p[13], at.p[14], at.p[15], dv + 240, 1);              \
        } while (0)
#define ISSUE_QK() do {                                                                                    \
            wgmma_rs_n64_t0<HI_K>(at.s, at.q[0], at.q[1], at.q[2], at.q[3], sd + dlo(OFF_KV, 128), 0);     \
            wgmma_rs_n64_t0<HI_K>(at.s, at.q[4], at.q[5], at.q[6], at.q[7], sd + dlo(OFF_KV + 512, 0), 1); \
        } while (0)
#define RELEASE_PREV() do {                                                                                \
            if (tid < 2) asm volatile("mbarrier.arrive.shared::cluster.b64 _, [%0];" ::"r"(rel) : "memory"); \
            rel = pb + rel_off;                                                                            \
        } while (0)
#define EXPS() do {                                                                                        \
            _Pragma("unroll") for (int i = 0; i < 16; i++) at.p[i] = pack(ex2(at.s[2 * i]), ex2(at.s[2 * i + 1])); \
            fence_regs(at.p);                                                                              \
        } while (0)
#define FUSED_STEP(DV, DK, NB, NPH, REL, GEMM_CODE) do {                                                   \
            uint32_t rdy;                                                                                  \
            if (WAITPOS == 0) rdy = mbar_test(NB, NPH);                                                    \
            wg_fence();                                                                                    \
            wgmma6_rs_n24_t1(at.o, at.p[0], at.p[1], at.p[2], at.p[3], (DV), 1);                           \
            wgmma6_rs_n24_t1(at.o, at.p[4], at.p[5], at.p[6], at.p[7], (DV) + 80, 1);                      \
            wgmma6_rs_n24_t1(at.o, at.p[8], at.p[9], at.p[10], at.p[11], (DV) + 160, 1);                   \
            wgmma6_rs_n24_t1(at.o, at.p[12], at.p[13], at.p[14], at.p[15], (DV) + 240, 1);                 \
            wgmma6_rs_n64_t0(at.s, at.q[0], at.q[1], at.q[2], at.q[3], (DK) + dlo(0, 128), 0);             \
            wgmma6_rs_n64_t0(at.s, at.q[4], at.q[5], at.q[6], at.q[7], (DK) + 32, 1);                      \
            wg_commit();                                                                                   \
            GEMM_CODE;                                                                                     \
            wg_commit();                                                                                   \
            if (WAITPOS == 0) mbar_wait_unless(rdy, NB, NPH);                                              \
            if (WAITPOS == 2) rdy = mbar_test(NB, NPH);                                                    \
            wg_wait<1>();                                                                                  \
            fence_regs(at.s); fence_regs(at.p);                                                            \
            if (tid < 2) asm volatile("mbarrier.arrive.shared::cluster.b64 _, [%0];" ::"r"(REL) : "memory"); \
            if (WAITPOS == 1) rdy = mbar_test(NB, NPH);                                                    \
            EXPS();                                                                                        \
            if (WAITPOS != 0) mbar_wait_unless(rdy, NB, NPH);                                              \
        } while (0)
#define FUSED_PAIR(HIA, LOA, LOB, GEMM) do {                                                               \
            const uint64_t dv0 = mkdesc<HI_V>(pd + dlo(OFF_KV + 256, 640));                                \
            const uint64_t dv1 = mkdesc<HI_V>(sd + dlo(OFF_KV + 256, 640));                                \
            const uint64_t dk = mkdesc<HI_K>(sd + dlo(OFF_KV, 0));                                         \
            const uint64_t da = mkdesc<HIA>(sd + (LOA)), db = mkdesc<HI_W>(sd + (LOB));                    \
            FUSED_STEP(dv0, dk, fb + 8, ph, rel, GEMM(da, db, first));                                     \
            const uint32_t r1 = fb + rel_off;                                                              \
            rel = r1 + 8;                                                                                  \
            pd = sd + (SLOT >> 4); pb = fb + 8;                                                            \
            if (fb == bar_full + (NSTAGE - 2) * 8) { fb = bar_full; ph ^= 1; } else fb += 16;              \
            sd = (sd == sbd + (NSTAGE - 2) * (SLOT >> 4)) ? sbd : sd + 2 * (SLOT >> 4);                    \
            FUSED_STEP(dv1, dk + (SLOT >> 4), fb, ph, r1, GEMM(da + (SLOT >> 4), db + (SLOT >> 4), 1));    \
            first = 1;                                                                                     \
            TRACE();                                                                                       \
        } while (0)
#define GEMM_256(A, B, SC) do { wgmma6_ss_n256_t1(acc, A, B, SC); wgmma6_ss_n256_t1(acc, (A) + 2, (B) + 128, 1); } while (0)
#define GEMM_144(A, B, SC) do { wgmma6_ss_n144_t1(ah, A, B, SC); wgmma6_ss_n144_t1(ah, (A) + 256, (B) + 128, 1); wgmma6_ss_n144_t1(ah, (A) + 512, (B) + 256, 1); } while (0)
#define FINISH_ITEM(item) do {                                                                             \
            wg_fence();                                                                                    \
            ISSUE_PV();                                                                                    \
            wg_commit();                                                                                   \
            wg_wait<0>();                                                                                  \
            fence_regs(at.o); fence_regs(at.p); fence_regs(at.q);                                          \
            if (store_o(at.o, O_PTR(item), nt & 1, lane, gaddr)) {                                         \
                attn_true_max(at.o, at.q, g_kv + (size_t)(j * 4 + (item)) * HEAD_BYTES + lane * 4);        \
                store_o(at.o, O_PTR(item), nt & 1, lane, gaddr);                                           \
            }                                                                                              \
            if ((item) < 3) {                                                                              \
                load_q(at.q, qa + ((item) + 1) * 4608, lane);                                              \
                _Pragma("unroll") for (int i = 0; i < 16; i++) at.p[i] = 0u;                               \
                _Pragma("unroll") for (int i = 0; i < 12; i++) at.o[i] = 0.f;                              \
                fence_regs(at.o); fence_regs(at.p); fence_regs(at.q);                                      \
            }                                                                                              \
        } while (0)
#define C ,

        {
            float acc[128];
            int first = 0;
#pragma unroll 1
            for (int seg = 0; seg < 6; seg++) {
                int n = 0x459279 >> (seg * 4) & 15;
#pragma unroll 1
                do { FUSED_PAIR(HI_X, wg * 256 + dlo(OFF_AX, 16), dlo(0, 4096), GEMM_256); } while (--n);
                if (seg == 1 || seg == 4) {
                    mbar_wait(bar_gate, 0);
                    FINISH_ITEM(seg >> 2);
                } else {
                    const int t = (seg * 3) >> 2;
                    wg_wait<0>();
                    fence_regs(acc);
                    PROF(4 + 2 * t);
                    uint8_t* hp = a2w + (j * 36 + t * 8) * 4096;
#pragma unroll
                    for (int i = 0; i < 16; i++) {
                        stg32(hp + (i >> 1) * 4096 + (i & 1) * 128, pack(geglu2(acc[4 * i], acc[64 + 4 * i]), geglu2(acc[4 * i + 1], acc[64 + 4 * i + 1])));
                        stg32(hp + (i >> 1) * 4096 + (i & 1) * 128 + 256, pack(geglu2(acc[4 * i + 2], acc[64 + 4 * i + 2]), geglu2(acc[4 * i + 3], acc[64 + 4 * i + 3])));
                    }
                    undef_regs(acc);
                    first = 0;
                    signal(t);
                    PROF(5 + 2 * t);
                }
            }
        }
        float keep[36];
        {
            float ah[72];
            int first = 0;
#pragma unroll 1
            for (int seg = 0; seg < 3; seg++) {
                int n = seg == 2 ? 3 : 12;
#pragma unroll 1
                do { FUSED_PAIR(HI_A2, wg * 128 + dlo(OFF_A2, 128), dlo(0, 6144), GEMM_144); } while (--n);
                if (seg == 0) {
                    FINISH_ITEM(2);
                    signal(5);
                } else {
                    wg_wait<0>();
                    fence_regs(ah);
                    if (seg == 1) {
                        PROF(12);
                        const float w0 = 0.5f - 0.5f * __uint_as_float(lds32(gaddr)), w1 = 0.5f - 0.5f * __uint_as_float(lds32(gaddr + 32));
#pragma unroll
                        for (int i = 0; i < 72; i++) ah[i] *= (i & 2) ? w1 : w0;
                        fence_regs(ah);
                    }
                }
            }
            PROF(13);
            wg_fence();
            ISSUE_PV();
            ISSUE_QK();
            wg_commit();
            float4* mine = g_part + (size_t)(cta * 2 + wg) * 9 * 128 + tid;
#pragma unroll
            for (int i = 0; i < 9; i++) {
                const int bl = i < 8 ? 4 * i : 64, bh = i < 8 ? 32 + 4 * i : 68;
                const float4 lo = make_float4(ah[bl], ah[bl + 1], ah[bl + 2], ah[bl + 3]);
                const float4 hi = make_float4(ah[bh], ah[bh + 1], ah[bh + 2], ah[bh + 3]);
                const float4 snd = hf ? lo : hi, kp = hf ? hi : lo;
                __stcg(mine + i * 128, snd);
                keep[4 * i] = kp.x; keep[4 * i + 1] = kp.y; keep[4 * i + 2] = kp.z; keep[4 * i + 3] = kp.w;
            }
            signal(6);
        }
        STAGE_NEXT;
        mbar_wait(fb, ph);
        wg_wait<0>();
        fence_regs(at.s); fence_regs(at.p);
        RELEASE_PREV();
        EXPS();
        wg_fence();
        ISSUE_PV();
        ISSUE_QK();
        wg_commit();
        STAGE_NEXT;
        wg_wait<0>();
        fence_regs(at.s); fence_regs(at.p);
        EXPS();
        FINISH_ITEM(3);
        signal(7);
        PROF(14);
        {
            mbar_wait(bar_rdy + 6 * 8, 0);
            const float4* theirs = g_part + (size_t)((cta ^ 8) * 2 + wg) * 9 * 128 + tid;
            float4 v[9];
#pragma unroll
            for (int i = 0; i < 9; i++) v[i] = __ldcg(theirs + i * 128);
#pragma unroll
            for (int i = 0; i < 9; i++) { keep[4 * i] += v[i].x; keep[4 * i + 1] += v[i].y; keep[4 * i + 2] += v[i].z; keep[4 * i + 3] += v[i].w; }
            fence_regs(keep);
        }
        PROF(15);
#pragma unroll 1
        for (int kk = 0; kk < 4; kk++) {
            mbar_wait(fb, ph);
            const uint32_t da = sd + wg * 128 + dlo(OFF_A2, 128);
            const uint32_t db = sd + dlo(0, 6144);
            wg_fence();
            wgmma_ss_n72_t1<HI_A2, HI_W>(keep, da, db, 1);
            wgmma_ss_n72_t1<HI_A2, HI_W>(keep, da + 256, db + 128, 1);
            wgmma_ss_n72_t1<HI_A2, HI_W>(keep, da + 512, db + 256, 1);
            wg_commit();
            STAGE_NEXT;
        }
        asm volatile("barrier.cluster.arrive.relaxed.aligned;" ::: "memory");
        wg_wait<0>();
        fence_regs(keep);
        PROF(16);
        uint8_t* op = (uint8_t*)(out + (size_t)(m * 128 + grp * 8 + (lane >> 2)) * DM);
        uint32_t v[2][8];
#pragma unroll
        for (int r = 0; r < 2; r++)
#pragma unroll
            for (int b = 0; b < 8; b++) v[r][b] = pack(keep[4 * b + 2 * r], keep[4 * b + 2 * r + 1]);
#pragma unroll
        for (int r = 0; r < 2; r++)
#pragma unroll
            for (int g = 0; g < 8; g += 4) {
                uint32_t* u = &v[r][g];
#pragma unroll
                for (int s = 1; s <= 2; s <<= 1)
#pragma unroll
                    for (int i = 0; i < 2; i++) {
                        const int lo = s == 1 ? 2 * i : i, hi = lo + s;
                        const uint32_t t = __shfl_xor_sync(0xffffffffu, (c & s) ? u[lo] : u[hi], s);
                        if (c & s) u[lo] = t; else u[hi] = t;
                    }
            }
#pragma unroll
        for (int r = 0; r < 2; r++) {
            uint8_t* p = op + r * 8 * DM * 2;
            *(uint4*)(p + nt * 256 + hf * 128 + c * 16) = make_uint4(v[r][0], v[r][1], v[r][2], v[r][3]);
            *(uint4*)(p + nt * 256 + hf * 128 + 64 + c * 16) = make_uint4(v[r][4], v[r][5], v[r][6], v[r][7]);
            *(uint32_t*)(p + 1024 + nt * 32 + hf * 16 + c * 4) = pack(keep[32 + 2 * r], keep[33 + 2 * r]);
        }
        PROF(20);
        asm volatile("barrier.cluster.wait.aligned;" ::: "memory");
    }
}

typedef CUresult (*EncodeFn)(CUtensorMap*, CUtensorMapDataType, cuuint32_t, void*, const cuuint64_t*, const cuuint64_t*,
                             const cuuint32_t*, const cuuint32_t*, CUtensorMapInterleave, CUtensorMapSwizzle,
                             CUtensorMapL2promotion, CUtensorMapFloatOOBfill);

CUtensorMap make_map(EncodeFn enc, const void* ptr, uint64_t inner, uint64_t outer, uint32_t box_inner, uint32_t box_outer, CUtensorMapSwizzle swz) {
    CUtensorMap t;
    cuuint64_t dims[2] = {inner, outer};
    cuuint64_t strides[1] = {inner * 2};
    cuuint32_t box[2] = {box_inner, box_outer};
    cuuint32_t es[2] = {1, 1};
    enc(&t, CU_TENSOR_MAP_DATA_TYPE_BFLOAT16, 2, const_cast<void*>(ptr), dims, strides, box, es, CU_TENSOR_MAP_INTERLEAVE_NONE, swz,
        CU_TENSOR_MAP_L2_PROMOTION_L2_256B, CU_TENSOR_MAP_FLOAT_OOB_FILL_NONE);
    return t;
}

CUtensorMap make_strip_map(EncodeFn enc, const void* ptr, uint64_t rows) {
    CUtensorMap t;
    cuuint64_t dims[3] = {16, rows, DM / 8 - 1};
    cuuint64_t strides[2] = {DM * 2, 16};
    cuuint32_t box[3] = {64, 24, 1};
    cuuint32_t es[3] = {1, 1, 1};
    enc(&t, CU_TENSOR_MAP_DATA_TYPE_BFLOAT16, 3, const_cast<void*>(ptr), dims, strides, box, es, CU_TENSOR_MAP_INTERLEAVE_NONE,
        CU_TENSOR_MAP_SWIZZLE_128B, CU_TENSOR_MAP_L2_PROMOTION_L2_128B, CU_TENSOR_MAP_FLOAT_OOB_FILL_NONE);
    return t;
}

}

extern "C" void kernel_launch(void* const* d_in, const int* in_sizes, int n_in, void* d_out, int out_size) {
    (void)in_sizes; (void)n_in; (void)out_size;
    void* fn = nullptr;
    cudaDriverEntryPointQueryResult qr;
    cudaGetDriverEntryPoint("cuTensorMapEncodeTiled", &fn, cudaEnableDefault, &qr);
    EncodeFn enc = (EncodeFn)fn;
    const CUtensorMap tm_x = make_map(enc, d_in[0], DM, SEQ, 32, 128, CU_TENSOR_MAP_SWIZZLE_64B);
    const CUtensorMap tm_qkv = make_map(enc, d_in[1], 3 * DM, DM, 64, 16, CU_TENSOR_MAP_SWIZZLE_128B);
    const CUtensorMap tm_qkv8 = make_map(enc, d_in[1], 3 * DM, DM, 8, 16, CU_TENSOR_MAP_SWIZZLE_NONE);
    const CUtensorMap tm_wo = make_map(enc, d_in[2], DM, DM, 64, 24, CU_TENSOR_MAP_SWIZZLE_128B);
    const CUtensorMap tm_wg = make_map(enc, d_in[4], FF, DM, 64, 32, CU_TENSOR_MAP_SWIZZLE_128B);
    const CUtensorMap tm_wu = make_map(enc, d_in[5], FF, DM, 64, 32, CU_TENSOR_MAP_SWIZZLE_128B);
    const CUtensorMap tm_wd = make_map(enc, d_in[6], DM, FF, 64, 24, CU_TENSOR_MAP_SWIZZLE_128B);
    const CUtensorMap tm_wd16 = make_strip_map(enc, d_in[6], FF), tm_wo16 = make_strip_map(enc, d_in[2], DM);
    cudaFuncSetAttribute(fused_kernel, cudaFuncAttributeMaxDynamicSharedMemorySize, SMEM_BYTES);
    fused_kernel<<<NCTA, 384, SMEM_BYTES>>>(tm_x, tm_qkv, tm_qkv8, tm_wg, tm_wu, tm_wd, tm_wo, tm_wd16, tm_wo16, (const __nv_bfloat16*)d_in[0],
                                           (const __nv_bfloat16*)d_in[7], (const uint8_t*)d_in[1], (const uint8_t*)d_in[4], (const uint8_t*)d_in[5], (__nv_bfloat16*)d_out);
}
```

```cpp
#include <cuda_runtime.h>
#include <cuda.h>
#include <cuda_bf16.h>
#include <stdint.h>

#define PROFILE 0
#define WAITPOS 1
#define DOTRACE 0
#define DEFER 2
#define PACE 500
#define SLEEPNS "1000"

namespace {

constexpr int SEQ = 2048, DM = 576, FF = 4608;
constexpr int NCTA = 128;
constexpr int NSTAGE = 6;
constexpr int SLOT = 35 * 1024;
constexpr int OFF_AX = 22528;
constexpr int OFF_A2 = 18432;
constexpr int OFF_TL = 20480;
constexpr int OFF_GAP = 16384;
constexpr int OFF_KV = 30720;
constexpr int OFF_Q = NSTAGE * SLOT - 4608;
constexpr int OFF_BAR = NSTAGE * SLOT + 3 * 4608;
constexpr int SMEM_BYTES = OFF_BAR + 1024 + 1024;

constexpr int HEAD_BYTES = 256 * 640;
constexpr int A2_TILE = 336 * 4096;

constexpr int FL_KV = 0;
constexpr int FL_M = FL_KV + 8 * 32;
constexpr int FM_H = 0;
constexpr int FM_LATE = 7;
constexpr int FM_R = 16;
constexpr int FL_G = FL_M + 16 * 64;
constexpr int FL_E = FL_G + 4 * 32;
constexpr int FL_N = FL_E + (NCTA + 4) * 32;

__device__ __align__(1024) uint8_t g_kv[32 * HEAD_BYTES];
__device__ __align__(1024) uint8_t g_a2[16 * A2_TILE];
__device__ __align__(1024) uint4 g_part[NCTA * 2 * 5 * 128];
__device__ __align__(1024) uint8_t g_q3[NCTA * 4608];
__device__ __align__(1024) float4 g_px[NCTA * 2 * 3 * 128];
__device__ float g_gate[SEQ];
__device__ __align__(256) uint32_t g_flags[FL_N];

template <uint32_t BHI>
__device__ __forceinline__ void wgmma_rs_n24_t1(float (&d)[12], uint32_t a0, uint32_t a1, uint32_t a2, uint32_t a3, uint32_t db, int scale_d) {
  asm volatile("{\n.reg .pred p;\n.reg .b64 da, db;\n"
    "mov.b64 db, {%16, %18};\n"
    "setp.ne.b32 p, %17, 0;\n"
    "wgmma.mma_async.sync.aligned.m64n24k16.f32.bf16.bf16 "
    "{%0, %1, %2, %3, %4, %5, %6, %7, %8, %9, %10, %11}, "
    "{%12, %13, %14, %15}, db, p, 1, 1, 1;\n}\n"
    : "+f"(d[0]), "+f"(d[1]), "+f"(d[2]), "+f"(d[3]), "+f"(d[4]), "+f"(d[5]), "+f"(d[6]), "+f"(d[7]),
      "+f"(d[8]), "+f"(d[9]), "+f"(d[10]), "+f"(d[11])
    : "r"(a0), "r"(a1), "r"(a2), "r"(a3), "r"(db), "r"(scale_d), "n"(BHI));
}
template <uint32_t BHI>
__device__ __forceinline__ void wgmma_rs_n128_t0(float (&d)[64], uint32_t a0, uint32_t a1, uint32_t a2, uint32_t a3, uint32_t db, int scale_d) {
  asm volatile("{\n.reg .pred p;\n.reg .b64 da, db;\n"
    "mov.b64 db, {%68, %70};\n"
    "setp.ne.b32 p, %69, 0;\n"
    "wgmma.mma_async.sync.aligned.m64n128k16.f32.bf16.bf16 "
    "{%0, %1, %2, %3, %4, %5, %6, %7, %8, %9, %10, %11, %12, %13, %14, %15, "
    "%16, %17, %18, %19, %20, %21, %22, %23, %24, %25, %26, %27, %28, %29, %30, %31, "
    "%32, %33, %34, %35, %36, %37, %38, %39, %40, %41, %42, %43, %44, %45, %46, %47, "
    "%48, %49, %50, %51, %52, %53, %54, %55, %56, %57, %58, %59, %60, %61, %62, %63}, "
    "{%64, %65, %66, %67}, db, p, 1, 1, 0;\n}\n"
    : "+f"(d[0]), "+f"(d[1]), "+f"(d[2]), "+f"(d[3]), "+f"(d[4]), "+f"(d[5]), "+f"(d[6]), "+f"(d[7]),
      "+f"(d[8]), "+f"(d[9]), "+f"(d[10]), "+f"(d[11]), "+f"(d[12]), "+f"(d[13]), "+f"(d[14]), "+f"(d[15]),
      "+f"(d[16]), "+f"(d[17]), "+f"(d[18]), "+f"(d[19]), "+f"(d[20]), "+f"(d[21]), "+f"(d[22]), "+f"(d[23]),
      "+f"(d[24]), "+f"(d[25]), "+f"(d[26]), "+f"(d[27]), "+f"(d[28]), "+f"(d[29]), "+f"(d[30]), "+f"(d[31]),
      "+f"(d[32]), "+f"(d[33]), "+f"(d[34]), "+f"(d[35]), "+f"(d[36]), "+f"(d[37]), "+f"(d[38]), "+f"(d[39]),
      "+f"(d[40]), "+f"(d[41]), "+f"(d[42]), "+f"(d[43]), "+f"(d[44]), "+f"(d[45]), "+f"(d[46]), "+f"(d[47]),
      "+f"(d[48]), "+f"(d[49]), "+f"(d[50]), "+f"(d[51]), "+f"(d[52]), "+f"(d[53]), "+f"(d[54]), "+f"(d[55]),
      "+f"(d[56]), "+f"(d[57]), "+f"(d[58]), "+f"(d[59]), "+f"(d[60]), "+f"(d[61]), "+f"(d[62]), "+f"(d[63])
    : "r"(a0), "r"(a1), "r"(a2), "r"(a3), "r"(db), "r"(scale_d), "n"(BHI));
}
template <uint32_t AHI, uint32_t BHI>
__device__ __forceinline__ void wgmma_ss_n24_t1(float (&d)[12], uint32_t da, uint32_t db, int scale_d) {
  asm volatile("{\n.reg .pred p;\n.reg .b64 da, db;\n"
    "mov.b64 da, {%12, %15};\nmov.b64 db, {%13, %16};\n"
    "setp.ne.b32 p, %14, 0;\n"
    "wgmma.mma_async.sync.aligned.m64n24k16.f32.bf16.bf16 "
    "{%0, %1, %2, %3, %4, %5, %6, %7, %8, %9, %10, %11}, "
    "da, db, p, 1, 1, 0, 1;\n}\n"
    : "+f"(d[0]), "+f"(d[1]), "+f"(d[2]), "+f"(d[3]), "+f"(d[4]), "+f"(d[5]), "+f"(d[6]), "+f"(d[7]),
      "+f"(d[8]), "+f"(d[9]), "+f"(d[10]), "+f"(d[11])
    : "r"(da), "r"(db), "r"(scale_d), "n"(AHI), "n"(BHI));
}
template <uint32_t AHI, uint32_t BHI>
__device__ __forceinline__ void wgmma_ss_n128_t1(float (&d)[64], uint32_t da, uint32_t db, int scale_d) {
  asm volatile("{\n.reg .pred p;\n.reg .b64 da, db;\n"
    "mov.b64 da, {%64, %67};\nmov.b64 db, {%65, %68};\n"
    "setp.ne.b32 p, %66, 0;\n"
    "wgmma.mma_async.sync.aligned.m64n128k16.f32.bf16.bf16 "
    "{%0, %1, %2, %3, %4, %5, %6, %7, %8, %9, %10, %11, %12, %13, %14, %15, "
    "%16, %17, %18, %19, %20, %21, %22, %23, %24, %25, %26, %27, %28, %29, %30, %31, "
    "%32, %33, %34, %35, %36, %37, %38, %39, %40, %41, %42, %43, %44, %45, %46, %47, "
    "%48, %49, %50, %51, %52, %53, %54, %55, %56, %57, %58, %59, %60, %61, %62, %63}, "
    "da, db, p, 1, 1, 0, 1;\n}\n"
    : "+f"(d[0]), "+f"(d[1]), "+f"(d[2]), "+f"(d[3]), "+f"(d[4]), "+f"(d[5]), "+f"(d[6]), "+f"(d[7]),
      "+f"(d[8]), "+f"(d[9]), "+f"(d[10]), "+f"(d[11]), "+f"(d[12]), "+f"(d[13]), "+f"(d[14]), "+f"(d[15]),
      "+f"(d[16]), "+f"(d[17]), "+f"(d[18]), "+f"(d[19]), "+f"(d[20]), "+f"(d[21]), "+f"(d[22]), "+f"(d[23]),
      "+f"(d[24]), "+f"(d[25]), "+f"(d[26]), "+f"(d[27]), "+f"(d[28]), "+f"(d[29]), "+f"(d[30]), "+f"(d[31]),
      "+f"(d[32]), "+f"(d[33]), "+f"(d[34]), "+f"(d[35]), "+f"(d[36]), "+f"(d[37]), "+f"(d[38]), "+f"(d[39]),
      "+f"(d[40]), "+f"(d[41]), "+f"(d[42]), "+f"(d[43]), "+f"(d[44]), "+f"(d[45]), "+f"(d[46]), "+f"(d[47]),
      "+f"(d[48]), "+f"(d[49]), "+f"(d[50]), "+f"(d[51]), "+f"(d[52]), "+f"(d[53]), "+f"(d[54]), "+f"(d[55]),
      "+f"(d[56]), "+f"(d[57]), "+f"(d[58]), "+f"(d[59]), "+f"(d[60]), "+f"(d[61]), "+f"(d[62]), "+f"(d[63])
    : "r"(da), "r"(db), "r"(scale_d), "n"(AHI), "n"(BHI));
}
template <uint32_t AHI, uint32_t BHI>
__device__ __forceinline__ void wgmma_ss_n192_t1(float (&d)[96], uint32_t da, uint32_t db, int scale_d) {
  asm volatile("{\n.reg .pred p;\n.reg .b64 da, db;\n"
    "mov.b64 da, {%96, %99};\nmov.b64 db, {%97, %100};\n"
    "setp.ne.b32 p, %98, 0;\n"
    "wgmma.mma_async.sync.aligned.m64n192k16.f32.bf16.bf16 "
    "{%0, %1, %2, %3, %4, %5, %6, %7, %8, %9, %10, %11, %12, %13, %14, %15, "
    "%16, %17, %18, %19, %20, %21, %22, %23, %24, %25, %26, %27, %28, %29, %30, %31, "
    "%32, %33, %34, %35, %36, %37, %38, %39, %40, %41, %42, %43, %44, %45, %46, %47, "
    "%48, %49, %50, %51, %52, %53, %54, %55, %56, %57, %58, %59, %60, %61, %62, %63, "
    "%64, %65, %66, %67, %68, %69, %70, %71, %72, %73, %74, %75, %76, %77, %78, %79, "
    "%80, %81, %82, %83, %84, %85, %86, %87, %88, %89, %90, %91, %92, %93, %94, %95}, "
    "da, db, p, 1, 1, 0, 1;\n}\n"
    : "+f"(d[0]), "+f"(d[1]), "+f"(d[2]), "+f"(d[3]), "+f"(d[4]), "+f"(d[5]), "+f"(d[6]), "+f"(d[7]),
      "+f"(d[8]), "+f"(d[9]), "+f"(d[10]), "+f"(d[11]), "+f"(d[12]), "+f"(d[13]), "+f"(d[14]), "+f"(d[15]),
      "+f"(d[16]), "+f"(d[17]), "+f"(d[18]), "+f"(d[19]), "+f"(d[20]), "+f"(d[21]), "+f"(d[22]), "+f"(d[23]),
      "+f"(d[24]), "+f"(d[25]), "+f"(d[26]), "+f"(d[27]), "+f"(d[28]), "+f"(d[29]), "+f"(d[30]), "+f"(d[31]),
      "+f"(d[32]), "+f"(d[33]), "+f"(d[34]), "+f"(d[35]), "+f"(d[36]), "+f"(d[37]), "+f"(d[38]), "+f"(d[39]),
      "+f"(d[40]), "+f"(d[41]), "+f"(d[42]), "+f"(d[43]), "+f"(d[44]), "+f"(d[45]), "+f"(d[46]), "+f"(d[47]),
      "+f"(d[48]), "+f"(d[49]), "+f"(d[50]), "+f"(d[51]), "+f"(d[52]), "+f"(d[53]), "+f"(d[54]), "+f"(d[55]),
      "+f"(d[56]), "+f"(d[57]), "+f"(d[58]), "+f"(d[59]), "+f"(d[60]), "+f"(d[61]), "+f"(d[62]), "+f"(d[63]),
      "+f"(d[64]), "+f"(d[65]), "+f"(d[66]), "+f"(d[67]), "+f"(d[68]), "+f"(d[69]), "+f"(d[70]), "+f"(d[71]),
      "+f"(d[72]), "+f"(d[73]), "+f"(d[74]), "+f"(d[75]), "+f"(d[76]), "+f"(d[77]), "+f"(d[78]), "+f"(d[79]),
      "+f"(d[80]), "+f"(d[81]), "+f"(d[82]), "+f"(d[83]), "+f"(d[84]), "+f"(d[85]), "+f"(d[86]), "+f"(d[87]),
      "+f"(d[88]), "+f"(d[89]), "+f"(d[90]), "+f"(d[91]), "+f"(d[92]), "+f"(d[93]), "+f"(d[94]), "+f"(d[95])
    : "r"(da), "r"(db), "r"(scale_d), "n"(AHI), "n"(BHI));
}
template <uint32_t AHI, uint32_t BHI>
__device__ __forceinline__ void wgmma_ss_n256_t1(float (&d)[128], uint32_t da, uint32_t db, int scale_d) {
  asm volatile("{\n.reg .pred p;\n.reg .b64 da, db;\n"
    "mov.b64 da, {%128, %131};\nmov.b64 db, {%129, %132};\n"
    "setp.ne.b32 p, %130, 0;\n"
    "wgmma.mma_async.sync.aligned.m64n256k16.f32.bf16.bf16 "
    "{%0, %1, %2, %3, %4, %5, %6, %7, %8, %9, %10, %11, %12, %13, %14, %15, "
    "%16, %17, %18, %19, %20, %21, %22, %23, %24, %25, %26, %27, %28, %29, %30, %31, "
    "%32, %33, %34, %35, %36, %37, %38, %39, %40, %41, %42, %43, %44, %45, %46, %47, "
    "%48, %49, %50, %51, %52, %53, %54, %55, %56, %57, %58, %59, %60, %61, %62, %63, "
    "%64, %65, %66, %67, %68, %69, %70, %71, %72, %73, %74, %75, %76, %77, %78, %79, "
    "%80, %81, %82, %83, %84, %85, %86, %87, %88, %89, %90, %91, %92, %93, %94, %95, "
    "%96, %97, %98, %99, %100, %101, %102, %103, %104, %105, %106, %107, %108, %109, %110, %111, "
    "%112, %113, %114, %115, %116, %117, %118, %119, %120, %121, %122, %123, %124, %125, %126, %127}, "
    "da, db, p, 1, 1, 0, 1;\n}\n"
    : "+f"(d[0]), "+f"(d[1]), "+f"(d[2]), "+f"(d[3]), "+f"(d[4]), "+f"(d[5]), "+f"(d[6]), "+f"(d[7]),
      "+f"(d[8]), "+f"(d[9]), "+f"(d[10]), "+f"(d[11]), "+f"(d[12]), "+f"(d[13]), "+f"(d[14]), "+f"(d[15]),
      "+f"(d[16]), "+f"(d[17]), "+f"(d[18]), "+f"(d[19]), "+f"(d[20]), "+f"(d[21]), "+f"(d[22]), "+f"(d[23]),
      "+f"(d[24]), "+f"(d[25]), "+f"(d[26]), "+f"(d[27]), "+f"(d[28]), "+f"(d[29]), "+f"(d[30]), "+f"(d[31]),
      "+f"(d[32]), "+f"(d[33]), "+f"(d[34]), "+f"(d[35]), "+f"(d[36]), "+f"(d[37]), "+f"(d[38]), "+f"(d[39]),
      "+f"(d[40]), "+f"(d[41]), "+f"(d[42]), "+f"(d[43]), "+f"(d[44]), "+f"(d[45]), "+f"(d[46]), "+f"(d[47]),
      "+f"(d[48]), "+f"(d[49]), "+f"(d[50]), "+f"(d[51]), "+f"(d[52]), "+f"(d[53]), "+f"(d[54]), "+f"(d[55]),
      "+f"(d[56]), "+f"(d[57]), "+f"(d[58]), "+f"(d[59]), "+f"(d[60]), "+f"(d[61]), "+f"(d[62]), "+f"(d[63]),
      "+f"(d[64]), "+f"(d[65]), "+f"(d[66]), "+f"(d[67]), "+f"(d[68]), "+f"(d[69]), "+f"(d[70]), "+f"(d[71]),
      "+f"(d[72]), "+f"(d[73]), "+f"(d[74]), "+f"(d[75]), "+f"(d[76]), "+f"(d[77]), "+f"(d[78]), "+f"(d[79]),
      "+f"(d[80]), "+f"(d[81]), "+f"(d[82]), "+f"(d[83]), "+f"(d[84]), "+f"(d[85]), "+f"(d[86]), "+f"(d[87]),
      "+f"(d[88]), "+f"(d[89]), "+f"(d[90]), "+f"(d[91]), "+f"(d[92]), "+f"(d[93]), "+f"(d[94]), "+f"(d[95]),
      "+f"(d[96]), "+f"(d[97]), "+f"(d[98]), "+f"(d[99]), "+f"(d[100]), "+f"(d[101]), "+f"(d[102]), "+f"(d[103]),
      "+f"(d[104]), "+f"(d[105]), "+f"(d[106]), "+f"(d[107]), "+f"(d[108]), "+f"(d[109]), "+f"(d[110]), "+f"(d[111]),
      "+f"(d[112]), "+f"(d[113]), "+f"(d[114]), "+f"(d[115]), "+f"(d[116]), "+f"(d[117]), "+f"(d[118]), "+f"(d[119]),
      "+f"(d[120]), "+f"(d[121]), "+f"(d[122]), "+f"(d[123]), "+f"(d[124]), "+f"(d[125]), "+f"(d[126]), "+f"(d[127])
    : "r"(da), "r"(db), "r"(scale_d), "n"(AHI), "n"(BHI));
}
__device__ __forceinline__ void wgmma6_rs_n24_t1(float (&d)[12], uint32_t a0, uint32_t a1, uint32_t a2, uint32_t a3, uint64_t db, int scale_d) {
  asm volatile("{\n.reg .pred p;\n"
    "setp.ne.b32 p, %17, 0;\n"
    "wgmma.mma_async.sync.aligned.m64n24k16.f32.bf16.bf16 "
    "{%0, %1, %2, %3, %4, %5, %6, %7, %8, %9, %10, %11}, "
    "{%12, %13, %14, %15}, %16, p, 1, 1, 1;\n}\n"
    : "+f"(d[0]), "+f"(d[1]), "+f"(d[2]), "+f"(d[3]), "+f"(d[4]), "+f"(d[5]), "+f"(d[6]), "+f"(d[7]),
      "+f"(d[8]), "+f"(d[9]), "+f"(d[10]), "+f"(d[11])
    : "r"(a0), "r"(a1), "r"(a2), "r"(a3), "l"(db), "r"(scale_d));
}
__device__ __forceinline__ void wgmma6_rs_n64_t0(float (&d)[32], uint32_t a0, uint32_t a1, uint32_t a2, uint32_t a3, uint64_t db, int scale_d) {
  asm volatile("{\n.reg .pred p;\n"
    "setp.ne.b32 p, %37, 0;\n"
    "wgmma.mma_async.sync.aligned.m64n64k16.f32.bf16.bf16 "
    "{%0, %1, %2, %3, %4, %5, %6, %7, %8, %9, %10, %11, %12, %13, %14, %15, "
    "%16, %17, %18, %19, %20, %21, %22, %23, %24, %25, %26, %27, %28, %29, %30, %31}, "
    "{%32, %33, %34, %35}, %36, p, 1, 1, 0;\n}\n"
    : "+f"(d[0]), "+f"(d[1]), "+f"(d[2]), "+f"(d[3]), "+f"(d[4]), "+f"(d[5]), "+f"(d[6]), "+f"(d[7]),
      "+f"(d[8]), "+f"(d[9]), "+f"(d[10]), "+f"(d[11]), "+f"(d[12]), "+f"(d[13]), "+f"(d[14]), "+f"(d[15]),
      "+f"(d[16]), "+f"(d[17]), "+f"(d[18]), "+f"(d[19]), "+f"(d[20]), "+f"(d[21]), "+f"(d[22]), "+f"(d[23]),
      "+f"(d[24]), "+f"(d[25]), "+f"(d[26]), "+f"(d[27]), "+f"(d[28]), "+f"(d[29]), "+f"(d[30]), "+f"(d[31])
    : "r"(a0), "r"(a1), "r"(a2), "r"(a3), "l"(db), "r"(scale_d));
}
__device__ __forceinline__ void wgmma6_ss_n80_t1(float (&d)[40], uint64_t da, uint64_t db, int scale_d) {
  asm volatile("{\n.reg .pred p;\n"
    "setp.ne.b32 p, %42, 0;\n"
    "wgmma.mma_async.sync.aligned.m64n80k16.f32.bf16.bf16 "
    "{%0, %1, %2, %3, %4, %5, %6, %7, %8, %9, %10, %11, %12, %13, %14, %15, "
    "%16, %17, %18, %19, %20, %21, %22, %23, %24, %25, %26, %27, %28, %29, %30, %31, "
    "%32, %33, %34, %35, %36, %37, %38, %39}, "
    "%40, %41, p, 1, 1, 0, 1;\n}\n"
    : "+f"(d[0]), "+f"(d[1]), "+f"(d[2]), "+f"(d[3]), "+f"(d[4]), "+f"(d[5]), "+f"(d[6]), "+f"(d[7]),
      "+f"(d[8]), "+f"(d[9]), "+f"(d[10]), "+f"(d[11]), "+f"(d[12]), "+f"(d[13]), "+f"(d[14]), "+f"(d[15]),
      "+f"(d[16]), "+f"(d[17]), "+f"(d[18]), "+f"(d[19]), "+f"(d[20]), "+f"(d[21]), "+f"(d[22]), "+f"(d[23]),
      "+f"(d[24]), "+f"(d[25]), "+f"(d[26]), "+f"(d[27]), "+f"(d[28]), "+f"(d[29]), "+f"(d[30]), "+f"(d[31]),
      "+f"(d[32]), "+f"(d[33]), "+f"(d[34]), "+f"(d[35]), "+f"(d[36]), "+f"(d[37]), "+f"(d[38]), "+f"(d[39])
    : "l"(da), "l"(db), "r"(scale_d));
}
__device__ __forceinline__ void wgmma6_ss_n144_t1(float (&d)[72], uint64_t da, uint64_t db, int scale_d) {
  asm volatile("{\n.reg .pred p;\n"
    "setp.ne.b32 p, %74, 0;\n"
    "wgmma.mma_async.sync.aligned.m64n144k16.f32.bf16.bf16 "
    "{%0, %1, %2, %3, %4, %5, %6, %7, %8, %9, %10, %11, %12, %13, %14, %15, "
    "%16, %17, %18, %19, %20, %21, %22, %23, %24, %25, %26, %27, %28, %29, %30, %31, "
    "%32, %33, %34, %35, %36, %37, %38, %39, %40, %41, %42, %43, %44, %45, %46, %47, "
    "%48, %49, %50, %51, %52, %53, %54, %55, %56, %57, %58, %59, %60, %61, %62, %63, "
    "%64, %65, %66, %67, %68, %69, %70, %71}, "
    "%72, %73, p, 1, 1, 0, 1;\n}\n"
    : "+f"(d[0]), "+f"(d[1]), "+f"(d[2]), "+f"(d[3]), "+f"(d[4]), "+f"(d[5]), "+f"(d[6]), "+f"(d[7]),
      "+f"(d[8]), "+f"(d[9]), "+f"(d[10]), "+f"(d[11]), "+f"(d[12]), "+f"(d[13]), "+f"(d[14]), "+f"(d[15]),
      "+f"(d[16]), "+f"(d[17]), "+f"(d[18]), "+f"(d[19]), "+f"(d[20]), "+f"(d[21]), "+f"(d[22]), "+f"(d[23]),
      "+f"(d[24]), "+f"(d[25]), "+f"(d[26]), "+f"(d[27]), "+f"(d[28]), "+f"(d[29]), "+f"(d[30]), "+f"(d[31]),
      "+f"(d[32]), "+f"(d[33]), "+f"(d[34]), "+f"(d[35]), "+f"(d[36]), "+f"(d[37]), "+f"(d[38]), "+f"(d[39]),
      "+f"(d[40]), "+f"(d[41]), "+f"(d[42]), "+f"(d[43]), "+f"(d[44]), "+f"(d[45]), "+f"(d[46]), "+f"(d[47]),
      "+f"(d[48]), "+f"(d[49]), "+f"(d[50]), "+f"(d[51]), "+f"(d[52]), "+f"(d[53]), "+f"(d[54]), "+f"(d[55]),
      "+f"(d[56]), "+f"(d[57]), "+f"(d[58]), "+f"(d[59]), "+f"(d[60]), "+f"(d[61]), "+f"(d[62]), "+f"(d[63]),
      "+f"(d[64]), "+f"(d[65]), "+f"(d[66]), "+f"(d[67]), "+f"(d[68]), "+f"(d[69]), "+f"(d[70]), "+f"(d[71])
    : "l"(da), "l"(db), "r"(scale_d));
}
__device__ __forceinline__ void wgmma6_ss_n256_t1(float (&d)[128], uint64_t da, uint64_t db, int scale_d) {
  asm volatile("{\n.reg .pred p;\n"
    "setp.ne.b32 p, %130, 0;\n"
    "wgmma.mma_async.sync.aligned.m64n256k16.f32.bf16.bf16 "
    "{%0, %1, %2, %3, %4, %5, %6, %7, %8, %9, %10, %11, %12, %13, %14, %15, "
    "%16, %17, %18, %19, %20, %21, %22, %23, %24, %25, %26, %27, %28, %29, %30, %31, "
    "%32, %33, %34, %35, %36, %37, %38, %39, %40, %41, %42, %43, %44, %45, %46, %47, "
    "%48, %49, %50, %51, %52, %53, %54, %55, %56, %57, %58, %59, %60, %61, %62, %63, "
    "%64, %65, %66, %67, %68, %69, %70, %71, %72, %73, %74, %75, %76, %77, %78, %79, "
    "%80, %81, %82, %83, %84, %85, %86, %87, %88, %89, %90, %91, %92, %93, %94, %95, "
    "%96, %97, %98, %99, %100, %101, %102, %103, %104, %105, %106, %107, %108, %109, %110, %111, "
    "%112, %113, %114, %115, %116, %117, %118, %119, %120, %121, %122, %123, %124, %125, %126, %127}, "
    "%128, %129, p, 1, 1, 0, 1;\n}\n"
    : "+f"(d[0]), "+f"(d[1]), "+f"(d[2]), "+f"(d[3]), "+f"(d[4]), "+f"(d[5]), "+f"(d[6]), "+f"(d[7]),
      "+f"(d[8]), "+f"(d[9]), "+f"(d[10]), "+f"(d[11]), "+f"(d[12]), "+f"(d[13]), "+f"(d[14]), "+f"(d[15]),
      "+f"(d[16]), "+f"(d[17]), "+f"(d[18]), "+f"(d[19]), "+f"(d[20]), "+f"(d[21]), "+f"(d[22]), "+f"(d[23]),
      "+f"(d[24]), "+f"(d[25]), "+f"(d[26]), "+f"(d[27]), "+f"(d[28]), "+f"(d[29]), "+f"(d[30]), "+f"(d[31]),
      "+f"(d[32]), "+f"(d[33]), "+f"(d[34]), "+f"(d[35]), "+f"(d[36]), "+f"(d[37]), "+f"(d[38]), "+f"(d[39]),
      "+f"(d[40]), "+f"(d[41]), "+f"(d[42]), "+f"(d[43]), "+f"(d[44]), "+f"(d[45]), "+f"(d[46]), "+f"(d[47]),
      "+f"(d[48]), "+f"(d[49]), "+f"(d[50]), "+f"(d[51]), "+f"(d[52]), "+f"(d[53]), "+f"(d[54]), "+f"(d[55]),
      "+f"(d[56]), "+f"(d[57]), "+f"(d[58]), "+f"(d[59]), "+f"(d[60]), "+f"(d[61]), "+f"(d[62]), "+f"(d[63]),
      "+f"(d[64]), "+f"(d[65]), "+f"(d[66]), "+f"(d[67]), "+f"(d[68]), "+f"(d[69]), "+f"(d[70]), "+f"(d[71]),
      "+f"(d[72]), "+f"(d[73]), "+f"(d[74]), "+f"(d[75]), "+f"(d[76]), "+f"(d[77]), "+f"(d[78]), "+f"(d[79]),
      "+f"(d[80]), "+f"(d[81]), "+f"(d[82]), "+f"(d[83]), "+f"(d[84]), "+f"(d[85]), "+f"(d[86]), "+f"(d[87]),
      "+f"(d[88]), "+f"(d[89]), "+f"(d[90]), "+f"(d[91]), "+f"(d[92]), "+f"(d[93]), "+f"(d[94]), "+f"(d[95]),
      "+f"(d[96]), "+f"(d[97]), "+f"(d[98]), "+f"(d[99]), "+f"(d[100]), "+f"(d[101]), "+f"(d[102]), "+f"(d[103]),
      "+f"(d[104]), "+f"(d[105]), "+f"(d[106]), "+f"(d[107]), "+f"(d[108]), "+f"(d[109]), "+f"(d[110]), "+f"(d[111]),
      "+f"(d[112]), "+f"(d[113]), "+f"(d[114]), "+f"(d[115]), "+f"(d[116]), "+f"(d[117]), "+f"(d[118]), "+f"(d[119]),
      "+f"(d[120]), "+f"(d[121]), "+f"(d[122]), "+f"(d[123]), "+f"(d[124]), "+f"(d[125]), "+f"(d[126]), "+f"(d[127])
    : "l"(da), "l"(db), "r"(scale_d));
}

__device__ __forceinline__ void wg_fence() { asm volatile("wgmma.fence.sync.aligned;" ::: "memory"); }
__device__ __forceinline__ void wg_commit() { asm volatile("wgmma.commit_group.sync.aligned;" ::: "memory"); }
template <int N> __device__ __forceinline__ void wg_wait() { asm volatile("wgmma.wait_group.sync.aligned %0;" ::"n"(N) : "memory"); }
__host__ __device__ constexpr uint32_t dlo(uint32_t off, uint32_t lbo) { return (off >> 4) | ((lbo >> 4) << 16); }
__host__ __device__ constexpr uint32_t dhi(uint32_t sbo, uint32_t swz) { return (sbo >> 4) | (swz << 30); }
constexpr uint32_t HI_X = dhi(512, 2), HI_W = dhi(1024, 1), HI_A2 = dhi(256, 0), HI_K = dhi(640, 0), HI_V = dhi(128, 0), HI_T = dhi(512, 0);
__device__ __forceinline__ float ex2(float x) { float y; asm volatile("ex2.approx.ftz.f32 %0, %1;" : "=f"(y) : "f"(x)); return y; }
template <uint32_t HI> __device__ __forceinline__ uint64_t mkdesc(uint32_t lo) {
    uint64_t d;
    asm("mov.b64 %0, {%1, %2};" : "=l"(d) : "r"(lo), "n"(HI));
    return d;
}
__device__ __forceinline__ float sel(int p, float a, float b) {
    float y;
    asm("{\n.reg .pred q;\nsetp.ne.s32 q, %3, 0;\nselp.f32 %0, %1, %2, q;\n}" : "=f"(y) : "f"(a), "f"(b), "r"(p));
    return y;
}
__device__ __forceinline__ float rcp_fast(float x) { float y; asm("rcp.approx.ftz.f32 %0, %1;" : "=f"(y) : "f"(x)); return y; }
__device__ __forceinline__ float tanh_fast(float x) { float y; asm("tanh.approx.f32 %0, %1;" : "=f"(y) : "f"(x)); return y; }
__device__ __forceinline__ uint32_t pack(float lo, float hi) { uint32_t y; asm("cvt.rn.bf16x2.f32 %0, %1, %2;" : "=r"(y) : "f"(hi), "f"(lo)); return y; }
template <int N> __device__ __forceinline__ void fence_regs(float (&d)[N]) {
#pragma unroll
    for (int i = 0; i < N; i++) asm volatile("" : "+f"(d[i])::"memory");
}
template <int N> __device__ __forceinline__ void fence_regs(uint32_t (&d)[N]) {
#pragma unroll
    for (int i = 0; i < N; i++) asm volatile("" : "+r"(d[i])::"memory");
}
template <int N> __device__ __forceinline__ void undef_regs(float (&d)[N]) {
#pragma unroll
    for (int i = 0; i < N; i++) asm volatile("" : "=f"(d[i]));
}
__device__ __forceinline__ void mbar_init(uint32_t bar, uint32_t cnt) { asm volatile("mbarrier.init.shared::cta.b64 [%0], %1;" ::"r"(bar), "r"(cnt) : "memory"); }
__device__ __forceinline__ void mbar_expect_tx(uint32_t bar, uint32_t bytes) { asm volatile("mbarrier.arrive.expect_tx.shared::cta.b64 _, [%0], %1;" ::"r"(bar), "r"(bytes) : "memory"); }
__device__ __forceinline__ void mbar_arrive(uint32_t bar) { asm volatile("mbarrier.arrive.shared::cta.b64 _, [%0];" ::"r"(bar) : "memory"); }
__device__ __forceinline__ void mbar_arrive_cluster(uint32_t bar, uint32_t cta) {
    asm volatile("{\n.reg .b32 ra;\nmapa.shared::cluster.u32 ra, %0, %1;\nmbarrier.arrive.shared::cluster.b64 _, [ra];\n}" ::"r"(bar), "r"(cta) : "memory");
}
__device__ __forceinline__ void mbar_wait(uint32_t bar, uint32_t parity) {
    asm volatile(
        "{\n.reg .pred p;\n.reg .u32 n;\n"
        "mbarrier.try_wait.parity.shared::cta.b64 p, [%0], %1;\n"
        "@p bra.uni LAB_DONE;\n"
        "mov.u32 n, 0;\n"
        "LAB_WAIT:\n"
        "mbarrier.try_wait.parity.shared::cta.b64 p, [%0], %1, " SLEEPNS ";\n"
        "@p bra.uni LAB_DONE;\n"
        "add.u32 n, n, 1;\n"
        "setp.ge.u32 p, n, 0x400000;\n"
        "@p trap;\n"
        "bra.uni LAB_WAIT;\n"
        "LAB_DONE:\n}" ::"r"(bar), "r"(parity) : "memory");
}
__device__ __forceinline__ void flag_wait(const uint32_t* p, uint32_t target) {
    asm volatile(
        "{\n.reg .pred p;\n.reg .u32 n;\n.reg .s32 v;\n"
        "mov.u32 n, 0;\n"
        "LAB_WAIT:\n"
        "ld.acquire.gpu.global.s32 v, [%0];\n"
        "sub.s32 v, v, %1;\n"
        "setp.ge.s32 p, v, 0;\n"
        "@p bra.uni LAB_DONE;\n"
        "add.u32 n, n, 1;\n"
        "setp.ge.u32 p, n, 0x800000;\n"
        "@p trap;\n"
        "bra.uni LAB_WAIT;\n"
        "LAB_DONE:\n}" ::"l"(p), "r"(target) : "memory");
}
__device__ __forceinline__ void flag_add(uint32_t* p) { asm volatile("red.release.gpu.global.add.u32 [%0], 1;" ::"l"(p) : "memory"); }
__device__ __forceinline__ void flag_addv(uint32_t* p, uint32_t v) { asm volatile("red.release.gpu.global.add.u32 [%0], %1;" ::"l"(p), "r"(v) : "memory"); }
__device__ __forceinline__ uint32_t flag_ld(const uint32_t* p) { uint32_t v; asm volatile("ld.acquire.gpu.global.u32 %0, [%1];" : "=r"(v) : "l"(p) : "memory"); return v; }
__device__ __forceinline__ void fence_async_global() { asm volatile("fence.proxy.async.global;" ::: "memory"); }
__device__ __forceinline__ void fence_async_shared() { asm volatile("fence.proxy.async.shared::cta;" ::: "memory"); }
__device__ __forceinline__ bool elect_one() {
    uint32_t p;
    asm volatile("{\n.reg .pred p;\nelect.sync _|p, 0xffffffff;\nselp.u32 %0, 1, 0, p;\n}" : "=r"(p));
    return p != 0;
}
__device__ __forceinline__ uint32_t mbar_test(uint32_t bar, uint32_t parity) {
    uint32_t p;
    asm volatile("{\n.reg .pred p;\nmbarrier.test_wait.parity.shared::cta.b64 p, [%1], %2;\nselp.u32 %0, 1, 0, p;\n}" : "=r"(p) : "r"(bar), "r"(parity) : "memory");
    return p;
}
__device__ __forceinline__ void mbar_wait_unless(uint32_t done, uint32_t bar, uint32_t parity) {
    asm volatile(
        "{\n.reg .pred p;\n.reg .u32 n;\n"
        "setp.ne.u32 p, %2, 0;\n"
        "@p bra.uni LAB_DONE;\n"
        "mov.u32 n, 0;\n"
        "LAB_WAIT:\n"
        "mbarrier.try_wait.parity.shared::cta.b64 p, [%0], %1, 1000;\n"
        "@p bra.uni LAB_DONE;\n"
        "add.u32 n, n, 1;\n"
        "setp.ge.u32 p, n, 0x400000;\n"
        "@p trap;\n"
        "bra.uni LAB_WAIT;\n"
        "LAB_DONE:\n}" ::"r"(bar), "r"(parity), "r"(done) : "memory");
}
__device__ __forceinline__ void bulk_s2g(void* dst, uint32_t src, uint32_t bytes) {
    asm volatile("cp.async.bulk.global.shared::cta.bulk_group [%0], [%1], %2;" ::"l"(dst), "r"(src), "r"(bytes) : "memory");
}
__device__ __forceinline__ void bulk_s2c(uint32_t addr, uint32_t bytes, uint32_t bar, uint32_t cta) {
    asm volatile("{\n.reg .b32 d, b;\nmapa.shared::cluster.u32 d, %0, %3;\nmapa.shared::cluster.u32 b, %2, %3;\n"
                 "cp.async.bulk.shared::cluster.shared::cta.mbarrier::complete_tx::bytes [d], [%0], %1, [b];\n}"
                 ::"r"(addr), "r"(bytes), "r"(bar), "r"(cta) : "memory");
}
__device__ __forceinline__ void sts32(uint32_t a, uint32_t v) { asm volatile("st.shared.u32 [%0], %1;" ::"r"(a), "r"(v) : "memory"); }
__device__ __forceinline__ void sts128(uint32_t a, uint32_t x, uint32_t y, uint32_t z, uint32_t w) { asm volatile("st.shared.v4.u32 [%0], {%1, %2, %3, %4};" ::"r"(a), "r"(x), "r"(y), "r"(z), "r"(w) : "memory"); }
__device__ __forceinline__ void stsm4(uint32_t a, uint32_t r0, uint32_t r1, uint32_t r2, uint32_t r3) {
    asm volatile("stmatrix.sync.aligned.m8n8.x4.shared.b16 [%0], {%1, %2, %3, %4};" ::"r"(a), "r"(r0), "r"(r1), "r"(r2), "r"(r3) : "memory");
}
__device__ __forceinline__ uint32_t lds32(uint32_t a) { uint32_t v; asm volatile("ld.shared.u32 %0, [%1];" : "=r"(v) : "r"(a) : "memory"); return v; }
__device__ __forceinline__ void tma_2d(uint32_t dst, const CUtensorMap* tm, int c0, int c1, uint32_t bar) {
    asm volatile("cp.async.bulk.tensor.2d.shared::cluster.global.mbarrier::complete_tx::bytes [%0], [%1, {%3, %4}], [%2];"
                 ::"r"(dst), "l"(tm), "r"(bar), "r"(c0), "r"(c1) : "memory");
}
__device__ __forceinline__ void tma_2d_mc(uint32_t dst, const CUtensorMap* tm, int c0, int c1, uint32_t bar) {
    asm volatile("cp.async.bulk.tensor.2d.shared::cluster.global.mbarrier::complete_tx::bytes.multicast::cluster [%0], [%1, {%3, %4}], [%2], %5;"
                 ::"r"(dst), "l"(tm), "r"(bar), "r"(c0), "r"(c1), "h"((uint16_t)3) : "memory");
}
__device__ __forceinline__ void tma_3d_mc(uint32_t dst, const CUtensorMap* tm, int c1, int c2, uint32_t bar) {
    asm volatile("cp.async.bulk.tensor.3d.shared::cluster.global.mbarrier::complete_tx::bytes.multicast::cluster [%0], [%1, {0, %3, %4}], [%2], %5;"
                 ::"r"(dst), "l"(tm), "r"(bar), "r"(c1), "r"(c2), "h"((uint16_t)3) : "memory");
}
__device__ __forceinline__ void bulk_g2s(uint32_t dst, const void* src, uint32_t bytes, uint32_t bar) {
    asm volatile("cp.async.bulk.shared::cluster.global.mbarrier::complete_tx::bytes [%0], [%1], %2, [%3];"
                 ::"r"(dst), "l"(src), "r"(bytes), "r"(bar) : "memory");
}
__device__ __forceinline__ void bulk_g2s_mc(uint32_t dst, const void* src, uint32_t bytes, uint32_t bar) {
    asm volatile("cp.async.bulk.shared::cluster.global.mbarrier::complete_tx::bytes.multicast::cluster [%0], [%1], %2, [%3], %4;"
                 ::"r"(dst), "l"(src), "r"(bytes), "r"(bar), "h"((uint16_t)3) : "memory");
}
__device__ __forceinline__ void mma_16816(float* d, uint32_t a0, uint32_t a1, uint32_t a2, uint32_t a3, uint32_t b0, uint32_t b1) {
    asm volatile("mma.sync.aligned.m16n8k16.row.col.f32.bf16.bf16.f32 {%0,%1,%2,%3}, {%4,%5,%6,%7}, {%8,%9}, {%0,%1,%2,%3};"
                 : "+f"(d[0]), "+f"(d[1]), "+f"(d[2]), "+f"(d[3]) : "r"(a0), "r"(a1), "r"(a2), "r"(a3), "r"(b0), "r"(b1));
}
__device__ __forceinline__ uint32_t movm_t(uint32_t a) { uint32_t d; asm volatile("movmatrix.sync.aligned.m8n8.trans.b16 %0, %1;" : "=r"(d) : "r"(a)); return d; }
__device__ __forceinline__ uint32_t ldg32(const uint8_t* p) { uint32_t v; asm volatile("ld.global.u32 %0, [%1];" : "=r"(v) : "l"(p) : "memory"); return v; }
__device__ __forceinline__ void stg32(uint8_t* p, uint32_t v) { asm volatile("st.global.u32 [%0], %1;" ::"l"(p), "r"(v) : "memory"); }
#define PROF(i) do {} while (0)
#define TRACE() do {} while (0)
#define PROFX(w, i) do {} while (0)

struct Ring {
    uint32_t slot;
    uint32_t phase;
    __device__ __forceinline__ void next() { if (++slot == NSTAGE) { slot = 0; phase ^= 1; } }
};

__device__ __forceinline__ void load_q(uint32_t (&q)[8], uint32_t qa, int lane) {
    q[0] = lds32(qa + lane * 4);       q[1] = lds32(qa + lane * 4 + 256);
    q[2] = lds32(qa + lane * 4 + 128); q[3] = lds32(qa + lane * 4 + 384);
    const uint32_t t0 = lds32(qa + 512 + (lane & ~3)), t1 = lds32(qa + 544 + (lane & ~3));
    q[4] = (lane & 3) == 2 ? t0 : 0u;  q[5] = (lane & 3) == 2 ? t1 : 0u;
}

__device__ __forceinline__ bool norm_o(uint32_t (&w)[6], const float (&o)[12], int lane, uint32_t gaddr) {
    const float l0 = __shfl_sync(0xffffffffu, o[8], (lane & ~3) | 1);
    const float l1 = __shfl_sync(0xffffffffu, o[10], (lane & ~3) | 1);
    const float i0 = rcp_fast(l0) * __uint_as_float(lds32(gaddr)), i1 = rcp_fast(l1) * __uint_as_float(lds32(gaddr + 32));
    uint32_t big = 0;
#pragma unroll
    for (int b = 0; b < 3; b++) {
        w[2 * b] = pack(o[4 * b] * i0, o[4 * b + 1] * i0);
        w[2 * b + 1] = pack(o[4 * b + 2] * i1, o[4 * b + 3] * i1);
        if (b == 2 && (lane & 3) != 0) w[4] = w[5] = 0u;
        big |= ((w[2 * b] & 0x7F807F80u) + 0x00800080u) | ((w[2 * b + 1] & 0x7F807F80u) + 0x00800080u);
    }
    const bool ok = fminf(l0, l1) >= 0x1p-30f && l0 <= 0x1p60f && l1 <= 0x1p60f && (big & 0x80008000u) == 0;
    return !__all_sync(0xffffffffu, ok);
}

__device__ __forceinline__ void attn_true_max(float (&o)[12], const uint32_t (&q)[8], const uint8_t* kv) {
    float m0 = -INFINITY, m1 = -INFINITY;
#pragma unroll
    for (int i = 0; i < 12; i++) o[i] = 0.f;
#pragma unroll 1
    for (int kb = 0; kb < SEQ / 16; kb++) {
        uint32_t t[2][5];
#pragma unroll
        for (int g = 0; g < 2; g++)
#pragma unroll
            for (int ch = 0; ch < 5; ch++) t[g][ch] = ldg32(kv + (kb * 2 + g) * 640 + ch * 128);
        float s[2][4];
#pragma unroll
        for (int g = 0; g < 2; g++) {
            s[g][0] = s[g][1] = s[g][2] = s[g][3] = 0.f;
            mma_16816(s[g], q[0], q[1], q[2], q[3], t[g][0], t[g][1]);
            mma_16816(s[g], q[4], q[5], 0u, 0u, t[g][4], 0u);
        }
        float x0 = fmaxf(fmaxf(s[0][0], s[0][1]), fmaxf(s[1][0], s[1][1]));
        float x1 = fmaxf(fmaxf(s[0][2], s[0][3]), fmaxf(s[1][2], s[1][3]));
        x0 = fmaxf(x0, __shfl_xor_sync(0xffffffffu, x0, 1)); x0 = fmaxf(x0, __shfl_xor_sync(0xffffffffu, x0, 2));
        x1 = fmaxf(x1, __shfl_xor_sync(0xffffffffu, x1, 1)); x1 = fmaxf(x1, __shfl_xor_sync(0xffffffffu, x1, 2));
        const float n0 = fmaxf(m0, x0), n1 = fmaxf(m1, x1);
        const float u0 = (n0 == -INFINITY) ? 0.f : n0, u1 = (n1 == -INFINITY) ? 0.f : n1;
        const float c0 = ex2(m0 - u0), c1 = ex2(m1 - u1);
        m0 = n0; m1 = n1;
#pragma unroll
        for (int b = 0; b < 3; b++) { o[4 * b] *= c0; o[4 * b + 1] *= c0; o[4 * b + 2] *= c1; o[4 * b + 3] *= c1; }
        const uint32_t a0 = pack(ex2(s[0][0] - u0), ex2(s[0][1] - u0)), a1 = pack(ex2(s[0][2] - u1), ex2(s[0][3] - u1));
        const uint32_t a2 = pack(ex2(s[1][0] - u0), ex2(s[1][1] - u0)), a3 = pack(ex2(s[1][2] - u1), ex2(s[1][3] - u1));
#pragma unroll
        for (int b = 0; b < 3; b++) mma_16816(&o[4 * b], a0, a1, a2, a3, movm_t(t[0][2 + b]), movm_t(t[1][2 + b]));
    }
}

__device__ __forceinline__ float geglu2(float g, float u) {
    const float p = fmaf(g * g, 0.044715f * 0.7978845608028654f, 0.7978845608028654f);
    const float th = tanh_fast(g * p);
    const float y = g * u;
    return fmaf(y, th, y);
}

struct Attn {
    float s[32];
    float o[12];
    uint32_t p[16];
    uint32_t q[8];
};

__global__ void __cluster_dims__(2, 1, 1) __launch_bounds__(384, 1)
fused_kernel(__nv_bfloat16* __restrict__ out, const __nv_bfloat16* __restrict__ x, const __nv_bfloat16* __restrict__ gate_w,
             const __grid_constant__ CUtensorMap tm_x, const __grid_constant__ CUtensorMap tm_qkv,
             const __grid_constant__ CUtensorMap tm_qkv8,
             const __grid_constant__ CUtensorMap tm_wg, const __grid_constant__ CUtensorMap tm_wu,
             const __grid_constant__ CUtensorMap tm_wd, const __grid_constant__ CUtensorMap tm_wo,
             const __grid_constant__ CUtensorMap tm_wd16, const __grid_constant__ CUtensorMap tm_wo16) {
    extern __shared__ uint8_t smem_raw[];
    const uint32_t sb = __shfl_sync(0xffffffffu, ((uint32_t)__cvta_generic_to_shared(smem_raw) + 1023) & ~1023u, 0);
    const uint32_t bars = sb + OFF_BAR;
    const uint32_t bar_full = bars, bar_empty = bars + 64;
    const uint32_t bar_ev = bars + 128;
    const uint32_t bar_rdy = bars + 256;
    const uint32_t bar_ep = bars + 320, bar_gate = bars + 328;
    const uint32_t bar_st = bars + 336;
    const uint32_t bar_late = bars + 384;
    const uint32_t bar_px = bars + 416;
    const uint32_t bar_free = bars + 424;
    const uint32_t s_epoch = bars + 448, s_zero = bars + 452, s_gate = bars + 512;

    const int cta = blockIdx.x;
    const int rank = cta & 1;
    const int j = (cta >> 1) & 7;
    const int m = (cta >> 4) * 2 + rank;
    const int hf = j >> 2, nt = j & 3;
    const int warp = __shfl_sync(0xffffffffu, threadIdx.x >> 5, 0);
    const int lane = threadIdx.x & 31;
    const int wg = warp >> 2;

    if (elect_one()) {
        const uint32_t lo = warp < 2 ? 2 : (warp >= 8 && warp <= 10) ? 1 : 4, hi = warp == 10 ? 4 : lo;
        mbar_init(bars + warp * 32, lo); mbar_init(bars + warp * 32 + 8, lo);
        mbar_init(bars + warp * 32 + 16, hi); mbar_init(bars + warp * 32 + 24, hi);
        if (warp < 7) mbar_init(bar_late + warp * 8, 1);
        sts32(s_zero, 0u);
        asm volatile("fence.mbarrier_init.release.cluster;" ::: "memory");
    }
    asm volatile("barrier.cluster.arrive.relaxed.aligned;" ::: "memory");
    asm volatile("barrier.cluster.wait.acquire.aligned;" ::: "memory");

    if (wg == 2) {
        asm volatile("setmaxnreg.dec.sync.aligned.u32 24;");
        if (cta >= NCTA) {
            if (warp == 8 && elect_one()) {
                const uint32_t ep = g_flags[FL_E + cta * 32] + 1;
                g_flags[FL_E + cta * 32] = ep;
                mbar_wait(bar_ev + 2 * 8, 0);
                mbar_wait(bar_ev + 10 * 8, 0);
                flag_add(&g_flags[FL_G + (cta - NCTA) * 32]);
#pragma unroll 1
                for (int i = 0; i < 2; i++) {
                    const int jx = (cta - NCTA) * 2 + i;
                    flag_wait(&g_flags[FL_KV + jx * 32 + 1], ep * 32);
                    fence_async_global();
                    mbar_expect_tx(bar_rdy + i * 8, 20480 + 16 * 4608);
#pragma unroll 1
                    for (int p = 0; p < 8; p++) bulk_g2s(sb + 40960 + (i * 8 + p) * 9216, g_q3 + (p * 16 + jx * 2) * 4608, 9216, bar_rdy + i * 8);
                    bulk_g2s(sb + i * 20480, g_kv + (size_t)(jx * 4 + 3) * HEAD_BYTES + 28 * 5120, 20480, bar_rdy + i * 8);
                }
#pragma unroll 1
                for (int i = 0; i < 2; i++) {
                    mbar_wait(bar_ev + i * 8, 0);
                    mbar_wait(bar_ev + (8 + i) * 8, 0);
                    flag_add(&g_flags[FL_KV + ((cta - NCTA) * 2 + i) * 32 + 2]);
                }
            }
        } else if (warp == 8) {
            if (elect_one()) {
                Ring r{0, 1};
                const int row0 = m * 128;
                const CUtensorMap* tw = rank ? &tm_wu : &tm_wg;
                PROFX(0, 40); PROFX(1, 40);
#pragma unroll 1
                for (int kk = 0; kk < 18; kk++) {
                    if (kk == 1) { PROFX(0, 41); PROFX(1, 41); }
                    if (kk == 6) { PROFX(0, 42); PROFX(1, 42); }
                    const uint32_t st = sb + r.slot * SLOT, fb = bar_full + r.slot * 8;
                    mbar_wait(bar_empty + r.slot * 8, r.phase);
                    mbar_arrive(fb);
                    mbar_expect_tx(fb, 8192 + 12288 + 8192 + 1536);
                    tma_2d(st + OFF_AX, &tm_x, kk * 32, row0, fb);
#pragma unroll
                    for (int b = 0; b < 3; b++) tma_2d_mc(st + 8192 + b * 4096 + rank * 2048, &tm_qkv, b * 576 + j * 72, kk * 32 + rank * 16, fb);
                    tma_2d_mc(st + rank * 4096, tw, j * 576 + 512, kk * 32, fb);
#pragma unroll
                    for (int b = 0; b < 3; b++) tma_2d_mc(st + OFF_TL + b * 512 + rank * 256, &tm_qkv8, b * 576 + j * 72 + 64, kk * 32 + rank * 16, fb);
                    r.next();
                }
#pragma unroll 1
                for (int t = 0; t < 4; t++)
#pragma unroll 1
                    for (int kk = 0; kk < 18; kk++) {
                        const uint32_t st = sb + r.slot * SLOT, fb = bar_full + r.slot * 8;
                        mbar_wait(bar_empty + r.slot * 8, r.phase);
                        if (t == 0 && kk < 2) mbar_arrive(fb);
                        mbar_expect_tx(fb, 8192 + 16384);
                        tma_2d_mc(st + rank * 8192, tw, j * 576 + t * 128, kk * 32, fb);
                        tma_2d_mc(st + rank * 8192 + 4096, tw, j * 576 + t * 128 + 64, kk * 32, fb);
                        tma_2d(st + OFF_AX, &tm_x, kk * 32, row0, fb);
                        r.next();
                    }
                const uint8_t* a2 = g_a2 + (size_t)m * A2_TILE;
                mbar_wait(bar_rdy + 4 * 8, 0);
#pragma unroll 1
                for (int n = 0; n < 48; n++) {
                    const int u = n >> 2, jj = n & 3;
                    const uint32_t st = sb + r.slot * SLOT, fb = bar_full + r.slot * 8;
                    mbar_wait(bar_empty + r.slot * 8, r.phase);
                    mbar_expect_tx(fb, 12288 + 18432);
                    const int ks = (hf * 4 + jj) * 36 + u * 3;
#pragma unroll
                    for (int b = 0; b < 2; b++) tma_2d_mc(st + b * 6144 + rank * 3072, &tm_wd, nt * 128 + b * 64, ks * 16 + rank * 24, fb);
                    tma_3d_mc(st + 12288 + rank * 3072, &tm_wd16, ks * 16 + rank * 24, 64 + nt * 2, fb);
                    if (jj == 0) { mbar_wait(bar_rdy + ((3 * u + 2) >> 3) * 8, 0); fence_async_global(); }
                    bulk_g2s(st + OFF_A2, a2 + ks * 4096, 12288, fb);
                    r.next();
                }
#pragma unroll 1
                for (int n = 0; n < 4; n++) {
                    const uint32_t st = sb + r.slot * SLOT, fb = bar_full + r.slot * 8;
                    mbar_wait(bar_empty + r.slot * 8, r.phase);
                    mbar_expect_tx(fb, 12288 + 18432);
                    const int pr = hf * 2 + (n & 1), head = (pr * 2 + rank) * 4 + (n >> 1);
#pragma unroll
                    for (int b = 0; b < 2; b++) tma_2d_mc(st + b * 6144 + rank * 3072, &tm_wo, nt * 128 + b * 64, head * 18, fb);
                    tma_3d_mc(st + 12288 + rank * 3072, &tm_wo16, head * 18, 64 + nt * 2, fb);
                    if (n == 0) { mbar_wait(bar_rdy + 5 * 8, 0); fence_async_global(); }
                    bulk_g2s(st + OFF_A2, a2 + (288 + ((n >> 1) * 4 + pr) * 3) * 4096, 12288, fb);
                    r.next();
                }
#pragma unroll 1
                for (int n = 0; n < 8; n++) {
                    const uint32_t st = sb + r.slot * SLOT, fb = bar_full + r.slot * 8;
                    mbar_wait(bar_empty + r.slot * 8, r.phase);
                    if (n >= 2) mbar_arrive(fb);
                    mbar_expect_tx(fb, 12288 + 12288);
                    const int pr = (n < 4 ? n : (j >> 1) + n) & 3;
                    const int head = (pr * 2 + rank) * 4 + 2 + (n >> 2);
                    tma_2d_mc(st + rank * 3072, &tm_wo, nt * 128 + hf * 64, head * 18, fb);
                    tma_3d_mc(st + 6144 + rank * 3072, &tm_wo16, head * 18, 64 + nt * 2, fb);
                    if (n < 4) bulk_g2s(st + OFF_A2, a2 + (288 + (8 + n) * 3) * 4096, 12288, fb);
                    else mbar_arrive(bar_late + (n - 4) * 8);
                    r.next();
                }
            }
        } else if (warp == 9) {
            if (elect_one()) {
                const uint32_t ep = g_flags[FL_E + cta * 32] + 1;
                g_flags[FL_E + cta * 32] = ep;
                sts32(s_epoch, ep);
                mbar_arrive(bar_ep);
                Ring r{0, 1};
                const uint8_t* kv = g_kv + (size_t)(j * 4) * HEAD_BYTES + rank * 2560;
                const int rot = (cta >> 4) * 4;
                flag_wait(&g_flags[FL_KV + j * 32], ep * 32);
                fence_async_global();
                PROFX(0, 37); PROFX(1, 37);
#pragma unroll 1
                for (int it = 4; it < 124; it++) {
                    const uint32_t fb = bar_full + r.slot * 8;
                    if (it == 24) { flag_wait(&g_flags[FL_KV + j * 32 + 1], ep * 32); fence_async_global(); }
                    mbar_wait(bar_empty + r.slot * 8, r.phase);
                    mbar_expect_tx(fb, 5120);
                    bulk_g2s_mc(sb + r.slot * SLOT + OFF_KV + rank * 2560, kv + (it < 32 ? (it + rot) & 31 : it) * 5120, 2560, fb);
                    r.next();
                }
                flag_wait(&g_flags[FL_KV + j * 32 + 2], ep);
                mbar_arrive(bar_px);
                uint32_t* fr = &g_flags[FL_M + m * 64 + FM_R];
                mbar_wait(bar_ev + 6 * 8, 0);
                mbar_wait(bar_ev + 14 * 8, 0);
                PROFX(0, 51); PROFX(1, 51);
                flag_add(fr + j);
                PROFX(0, 52); PROFX(1, 52);
                flag_wait(fr + (j ^ 4), ep);
                PROFX(0, 53); PROFX(1, 53);
                mbar_arrive(bar_rdy + 6 * 8);
            }
        } else {
            const int w = warp - 10;
            if (elect_one()) {
                const uint32_t mine = 2 + rank * 2 + w, other = 2 + (rank ^ 1) * 2 + w;
                mbar_wait(bar_st + w * 8, 0);
                PROFX(w, 32);
                bulk_s2g(g_kv + (size_t)(j * 4) * HEAD_BYTES + (m * 16 + w * 8) * 640, sb + mine * SLOT + OFF_KV, 5120);
                asm volatile("cp.async.bulk.commit_group;" ::: "memory");
                mbar_arrive(bar_full + mine * 8);
                mbar_expect_tx(bar_full + other * 8, 5120);
#pragma unroll 1
                for (int i = 0; i < 2; i++) {
                    if (i == rank) {
                        mbar_wait(bar_empty + mine * 8, 0);
                        bulk_s2c(sb + mine * SLOT + OFF_KV, 5120, bar_full + mine * 8, rank ^ 1);
                    } else {
                        asm volatile("cp.async.bulk.wait_group 0;" ::: "memory");
                        flag_add(&g_flags[FL_KV + j * 32]);
                    }
                }
                PROFX(w, 34);
                mbar_wait(bar_st + (2 + w) * 8, 0);
                bulk_s2g(g_q3 + cta * 4608 + w * 2304, sb + OFF_Q + 3 * 4608 + w * 2304, 2304);
#pragma unroll 1
                for (int h = 1; h < 4; h++) {
                    __nanosleep(PACE);
                    bulk_s2g(g_kv + (size_t)(j * 4 + h) * HEAD_BYTES + (m * 16 + w * 8) * 640, sb + (w * 3 + h - 1) * SLOT + OFF_GAP, 5120);
                    asm volatile("cp.async.bulk.commit_group;\ncp.async.bulk.wait_group 0;" ::: "memory");
                }
                mbar_arrive(bar_free + w * 8);
                flag_add(&g_flags[FL_KV + j * 32 + 1]);
                PROFX(w, 35);
            }
            __syncwarp();
            uint32_t* fm = &g_flags[FL_M + m * 64];
            mbar_wait(bar_ep, 0);
            const uint32_t ep = lds32(s_epoch);
            if (w == 1) {
                flag_wait(&g_flags[FL_G + (m >> 2) * 32], ep);
                const uint4 gv = __ldcg((const uint4*)(g_gate + m * 128) + lane);
                sts128(s_gate + lane * 16, gv.x, gv.y, gv.z, gv.w);
                __syncwarp();
                if (lane == 0) mbar_arrive(bar_gate);
            }
            if (elect_one()) {
#pragma unroll 1
                for (int i = 0; i < 6; i++) {
                    const int e = i == 0 ? 4 : i == 5 ? 5 : i - 1;
                    mbar_wait(bar_ev + (w * 8 + e) * 8, 0);
                    if (e < 3) {
                        uint8_t* hp = g_a2 + (size_t)m * A2_TILE + (j * 36 + e * 8) * 4096 + w * 2048;
#pragma unroll 1
                        for (int k = 0; k < 8; k++) {
                            const int g = (k * 11) >> 5;
                            bulk_s2g(hp + k * 4096, sb + (w * 3 + g) * SLOT + OFF_GAP + (k - g * 3) * 2048, 2048);
                        }
                        asm volatile("cp.async.bulk.commit_group;\ncp.async.bulk.wait_group 0;" ::: "memory");
                    }
                    uint32_t* fl = fm + FM_H + (e == 5 ? 5 : hf * 8 + e);
                    flag_add(fl);
                    if (w == 0) { flag_wait(fl, ep * (e == 5 ? 16 : 8)); mbar_arrive(bar_rdy + e * 8); }
                }
                mbar_wait(bar_ev + (w * 8 + 7) * 8, 0);
                PROFX(w, 48);
                flag_addv(fm + FM_LATE, 1u << ((j >> 1) * 8));
                PROFX(w, 49);
                const uint32_t base = (ep - 1) * 0x04040404u;
                uint32_t todo = 5u << w, tries = 0;
#pragma unroll 1
                while (todo) {
                    const uint32_t got = flag_ld(fm + FM_LATE) - base;
                    fence_async_global();
#pragma unroll 1
                    for (int n = w; n < 4; n += 2) {
                        const int pr = ((j >> 1) + n) & 3;
                        if (((todo >> n) & 1) && ((got >> (pr * 8)) & 4)) {
                            mbar_wait(bar_late + n * 8, 0);
                            bulk_g2s(sb + (2 + n) * SLOT + OFF_A2, g_a2 + (size_t)m * A2_TILE + (288 + (12 + pr) * 3) * 4096, 12288, bar_full + (2 + n) * 8);
                            todo &= ~(1u << n);
                        }
                    }
                    asm volatile("{\n.reg .pred p;\nsetp.gt.u32 p, %0, 0x800000;\n@p trap;\n}" ::"r"(++tries));
                }
                PROFX(w, 50);
            }
        }
    } else {
        asm volatile("setmaxnreg.inc.sync.aligned.u32 240;");
        const int wq = warp & 3;
        const int c = lane & 3;
        const int tid = threadIdx.x & 127;
        const int grp = wg * 8 + wq * 2;
        const uint32_t sbd = (sb & 0x3FFFF) >> 4;
        uint32_t sd = sbd, pd = sbd, fb = bar_full, pb = bar_full, ph = 0;
#define STAGE_NEXT do { pd = sd; sd = (sd == sbd + (NSTAGE - 1) * (SLOT >> 4)) ? sbd : sd + (SLOT >> 4);   \
                        pb = fb; fb += 8; if (fb == bar_full + NSTAGE * 8) { fb = bar_full; ph ^= 1; } } while (0)
        auto release = [&]() { if (tid < 2) mbar_arrive_cluster(pb + 64, tid); };
        auto signal = [&](int e) { __syncwarp(); if (lane == 0) mbar_arrive(bar_ev + (wg * 8 + e) * 8); };
        if (cta >= NCTA) {
            PROF(0);
            {
                float wv[72];
#pragma unroll
                for (int i = 0; i < 9; i++) {
                    const uint4 t = __ldg((const uint4*)gate_w + (lane & 7) + i * 8);
                    const uint32_t u[4] = {t.x, t.y, t.z, t.w};
#pragma unroll
                    for (int e = 0; e < 4; e++) { wv[8 * i + 2 * e] = __uint_as_float(u[e] << 16); wv[8 * i + 2 * e + 1] = __uint_as_float(u[e] & 0xffff0000u); }
                }
                __nanosleep(1500);
#pragma unroll 1
                for (int b = 0; b < 8; b++) {
                    const int row = (cta - NCTA) * 512 + warp * 64 + b * 8 + (lane >> 3);
                    uint4 xa[2][9];
#pragma unroll
                    for (int r = 0; r < 2; r++)
#pragma unroll
                        for (int i = 0; i < 9; i++) xa[r][i] = __ldg((const uint4*)(x + (size_t)(row + r * 4) * DM) + (lane & 7) + i * 8);
#pragma unroll
                    for (int r = 0; r < 2; r++) {
                        float z = 0.f, y = 0.f;
#pragma unroll
                        for (int i = 0; i < 9; i++) {
                            const uint32_t u[4] = {xa[r][i].x, xa[r][i].y, xa[r][i].z, xa[r][i].w};
#pragma unroll
                            for (int e = 0; e < 4; e++) {
                                z = fmaf(__uint_as_float(u[e] << 16), wv[8 * i + 2 * e], z);
                                y = fmaf(__uint_as_float(u[e] & 0xffff0000u), wv[8 * i + 2 * e + 1], y);
                            }
                        }
                        z += y;
#pragma unroll
                        for (int d = 1; d < 8; d <<= 1) z += __shfl_xor_sync(0xffffffffu, z, d);
                        if ((lane & 7) == 0) g_gate[row + r * 4] = rcp_fast(1.f + ex2(-1.4426950408889634f * z));
                    }
                }
                signal(2);
                PROF(2);
            }
            float s0[64], s1[64], o[12];
            uint32_t p0[32], p1[32], q[8];
            q[6] = lds32(s_zero); q[7] = lds32(s_zero);
#pragma unroll
            for (int i = 0; i < 12; i++) o[i] = 0.f;
            auto store_px = [&](int u) {
                const int src = ((u & 15) >> 1) * 16 + ((cta - NCTA) * 2 + (u >> 4)) * 2 + (u & 1);
                float4* dst = g_px + (size_t)(src * 2 + wg) * 3 * 128 + tid;
#pragma unroll
                for (int i = 0; i < 3; i++) __stcg(dst + i * 128, make_float4(o[4 * i], o[4 * i + 1], o[4 * i + 2], o[4 * i + 3]));
            };
            mbar_wait(bar_rdy, 0);
            PROF(1);
            load_q(q, sb + 40960 + warp * 576, lane);
            fence_regs(q); fence_regs(o);
            wg_fence();
            wgmma_rs_n128_t0<HI_K>(s0, q[0], q[1], q[2], q[3], sbd + dlo(0, 128), 0);
            wgmma_rs_n128_t0<HI_K>(s0, q[4], q[5], q[6], q[7], sbd + dlo(512, 0), 1);
            wg_commit();
            wg_wait<0>();
            fence_regs(s0);
#pragma unroll 1
            for (int u = 0; u < 32; u++) {
                const uint32_t kb = sbd + (u >> 4) * 1280;
                wg_fence();
                wgmma_rs_n128_t0<HI_K>(s1, q[0], q[1], q[2], q[3], kb + dlo(10240, 128), 0);
                wgmma_rs_n128_t0<HI_K>(s1, q[4], q[5], q[6], q[7], kb + dlo(10240 + 512, 0), 1);
                wg_commit();
#pragma unroll
                for (int i = 0; i < 32; i++) p0[i] = pack(ex2(s0[2 * i]), ex2(s0[2 * i + 1]));
                fence_regs(p0);
                wg_wait<0>();
                fence_regs(o); fence_regs(s1); fence_regs(q);
                store_px(u > 0 ? u - 1 : 0);
                if (u == 16) signal(0);
                if (u == 15) mbar_wait(bar_rdy + 8, 0);
                const int un = u < 31 ? u + 1 : u;
                load_q(q, sb + 40960 + un * 4608 + warp * 576, lane);
                fence_regs(q);
                const uint32_t kn = sbd + (un >> 4) * 1280;
                wg_fence();
#pragma unroll
                for (int i = 0; i < 8; i++) wgmma_rs_n24_t1<HI_V>(o, p0[4 * i], p0[4 * i + 1], p0[4 * i + 2], p0[4 * i + 3], kb + dlo(256, 640) + 80 * i, i != 0);
                wgmma_rs_n128_t0<HI_K>(s0, q[0], q[1], q[2], q[3], kn + dlo(0, 128), 0);
                wgmma_rs_n128_t0<HI_K>(s0, q[4], q[5], q[6], q[7], kn + dlo(512, 0), 1);
                wg_commit();
#pragma unroll
                for (int i = 0; i < 32; i++) p1[i] = pack(ex2(s1[2 * i]), ex2(s1[2 * i + 1]));
                fence_regs(p1);
                wg_fence();
#pragma unroll
                for (int i = 0; i < 8; i++) wgmma_rs_n24_t1<HI_V>(o, p1[4 * i], p1[4 * i + 1], p1[4 * i + 2], p1[4 * i + 3], kb + dlo(10240 + 256, 640) + 80 * i, 1);
                wg_commit();
                wg_wait<1>();
                fence_regs(s0); fence_regs(p0);
            }
            wg_wait<0>();
            fence_regs(o);
            store_px(31);
            signal(1);
            PROF(20);
            return;
        }
        Attn at;
        PROF(0);

        uint8_t* a2w = g_a2 + (size_t)m * A2_TILE + grp * 256 + lane * 4;
        const uint32_t qa = sb + OFF_Q + warp * 576;
        float acc[128];
        {
            float qkv[96], tl[12], gu[64];
#pragma unroll 1
            for (int kk = 0; kk < 18 - DEFER; kk++) {
                mbar_wait(fb, ph);
                if (kk == 0) PROF(21);
                if (kk == 6) PROF(22);
                if (kk == 12) PROF(23);
                const uint32_t da = sd + wg * 256 + dlo(OFF_AX, 16), db = sd + dlo(0, 4096), dt = sd + dlo(OFF_TL, 128);
                wg_fence();
                wgmma_ss_n192_t1<HI_X, HI_W>(qkv, da, db + 512, kk != 0);
                wgmma_ss_n24_t1<HI_X, HI_T>(tl, da, dt, kk != 0);
                wgmma_ss_n128_t1<HI_X, HI_W>(gu, da, db, kk != 0);
                wgmma_ss_n192_t1<HI_X, HI_W>(qkv, da + 2, db + 512 + 128, 1);
                wgmma_ss_n24_t1<HI_X, HI_T>(tl, da + 2, dt + 16, 1);
                wgmma_ss_n128_t1<HI_X, HI_W>(gu, da + 2, db + 128, 1);
                wg_commit();
                wg_wait<1>();
                if (kk > 0) release();
                STAGE_NEXT;
            }
#pragma unroll
            for (int kk = 0; kk < DEFER; kk++) {
                mbar_wait(fb + kk * 8, ph);
                const uint32_t st = sd + kk * (SLOT >> 4);
                const uint32_t da = st + wg * 256 + dlo(OFF_AX, 16), db = st + dlo(0, 4096), dt = st + dlo(OFF_TL, 128);
                wg_fence();
                wgmma_ss_n192_t1<HI_X, HI_W>(qkv, da, db + 512, 1);
                wgmma_ss_n24_t1<HI_X, HI_T>(tl, da, dt, 1);
                wgmma_ss_n192_t1<HI_X, HI_W>(qkv, da + 2, db + 512 + 128, 1);
                wgmma_ss_n24_t1<HI_X, HI_T>(tl, da + 2, dt + 16, 1);
                wg_commit();
                if (kk == 0) { wg_wait<1>(); release(); }
            }
#pragma unroll
            for (int kk = 0; kk < DEFER; kk++) {
                const uint32_t st = sd + kk * (SLOT >> 4);
                const uint32_t da = st + wg * 256 + dlo(OFF_AX, 16), db = st + dlo(0, 4096);
                wgmma_ss_n128_t1<HI_X, HI_W>(gu, da, db, 1);
                wgmma_ss_n128_t1<HI_X, HI_W>(gu, da + 2, db + 128, 1);
            }
            wg_commit();
            wg_wait<1>();
            fence_regs(qkv); fence_regs(tl);
            PROF(1);
            constexpr float QS = 0.23570226039551584f * 1.4426950408889634f;
            uint32_t kp[9][2], vp[9][2];
#pragma unroll
            for (int i = 0; i < 9; i++) {
                const float* k4 = i < 8 ? &qkv[32 + 4 * i] : &tl[4];
                const float* v4 = i < 8 ? &qkv[64 + 4 * i] : &tl[8];
                kp[i][0] = pack(k4[0], k4[1]); kp[i][1] = pack(k4[2], k4[3]);
                vp[i][0] = pack(v4[0], v4[1]); vp[i][1] = pack(v4[2], v4[3]);
            }
            const int quad = lane & ~3;
            const uint32_t cst = c == 1 ? 0x3F80u : 0u;
            {
                const uint32_t a = sb + (2 + rank * 2 + wg) * SLOT + OFF_KV + wq * 1280 + lane * 4;
#pragma unroll
                for (int r = 0; r < 2; r++) {
                    const uint32_t kt = __shfl_sync(0xffffffffu, kp[2][r], quad);
                    sts32(a + r * 640, kp[0][r]);       sts32(a + r * 640 + 128, kp[1][r]);
                    sts32(a + r * 640 + 256, vp[0][r]); sts32(a + r * 640 + 384, vp[1][r]);
                    sts32(a + r * 640 + 512, c == 0 ? vp[2][r] : c == 2 ? kt : cst);
                }
                fence_async_shared();
                __syncwarp();
                if (lane == 0) mbar_arrive(bar_st + wg * 8);
            }
            PROF(2);
#pragma unroll
            for (int i = 0; i < 9; i++) {
                const float* q4 = i < 8 ? &qkv[4 * i] : &tl[0];
                const uint32_t q0 = pack(q4[0] * QS, q4[1] * QS), q1 = pack(q4[2] * QS, q4[3] * QS);
                if (i < 2) { at.q[2 * i] = q0; at.q[2 * i + 1] = q1; }
                else {
                    if (i == 2) {
                        const uint32_t t0 = __shfl_sync(0xffffffffu, q0, quad), t1 = __shfl_sync(0xffffffffu, q1, quad);
                        at.q[4] = c == 2 ? t0 : 0u; at.q[5] = c == 2 ? t1 : 0u;
                    }
                    const int lc = 8 * i + 2 * c;
                    const int hd = (lc * 3641) >> 16;
                    const int d = lc - hd * 18;
                    const bool last = (i & 1) == 0 && c == i / 2 - 1;
                    const uint32_t aq = qa + hd * 4608 + (last ? 512 + (lane >> 2) * 4 : (d >> 3) * 128 + (d & 7) * 2 + (lane >> 2) * 16);
                    if (i > 2 || c > 0) { sts32(aq, q0); sts32(aq + (last ? 32 : 256), q1); }
                }
            }
            mbar_wait(bar_st + (wg ^ 1) * 8, 0);
#pragma unroll
            for (int i = 2; i < 9; i++) {
                const int lc = 8 * i + 2 * c;
                const int hd = (lc * 3641) >> 16;
                const int d = lc - hd * 18;
                const uint32_t ak = sb + (wg * 3 - 1 + hd) * SLOT + OFF_GAP + wq * 1280 + (lane >> 2) * 16;
                const uint32_t off = (d >> 3) * 128 + (d & 7) * 2;
                if ((i & 1) == 0 && c == i / 2 - 1) {
                    if (i > 2) { sts128(ak + 512, vp[i][0], 0x3F80u, kp[i][0], 0u); sts128(ak + 512 + 640, vp[i][1], 0x3F80u, kp[i][1], 0u); }
                } else {
                    sts32(ak + off, kp[i][0]); sts32(ak + off + 640, kp[i][1]); sts32(ak + off + 256, vp[i][0]); sts32(ak + off + 256 + 640, vp[i][1]);
                }
            }
            fence_async_shared();
            __syncwarp();
            if (lane == 0) mbar_arrive(bar_st + (2 + wg) * 8);
            PROF(39);
            wg_wait<0>();
            fence_regs(gu);
            if (tid < 2 * DEFER) mbar_arrive_cluster(fb + 64 + (tid >> 1) * 8, tid & 1);
#pragma unroll
            for (int kk = 0; kk < 2; kk++) {
                mbar_wait(bar_full + kk * 8, 1);
                const uint32_t st = sbd + kk * (SLOT >> 4);
                const uint32_t da = st + wg * 256 + dlo(OFF_AX, 16), db = st + dlo(0, 4096);
                wg_fence();
                wgmma_ss_n256_t1<HI_X, HI_W>(acc, da, db, kk);
                wgmma_ss_n256_t1<HI_X, HI_W>(acc, da + 2, db + 128, 1);
                wg_commit();
            }
            sd = sbd + 2 * (SLOT >> 4); fb = bar_full + 16; pb = bar_full; ph = 1;
            uint32_t hv[16];
#pragma unroll
            for (int i = 0; i < 16; i++) hv[i] = pack(geglu2(gu[2 * i], gu[32 + 2 * i]), geglu2(gu[2 * i + 1], gu[32 + 2 * i + 1]));
            uint8_t* hp = a2w + (j * 36 + 32) * 4096;
#pragma unroll
            for (int i = 0; i < 16; i++) stg32(hp + (i >> 2) * 4096 + ((i >> 1) & 1) * 128 + (i & 1) * 256, hv[i]);
            signal(4);
            PROF(3);
            wg_wait<1>();
            release();
            mbar_wait(fb, ph);
            PROF(38);
        }

        const uint32_t gaddr = s_gate + (grp * 8 + (lane >> 2)) * 4;
        at.q[6] = lds32(s_zero); at.q[7] = lds32(s_zero);
#pragma unroll
        for (int i = 0; i < 16; i++) at.p[i] = 0u;
#pragma unroll
        for (int i = 0; i < 12; i++) at.o[i] = 0.f;
        fence_regs(at.q); fence_regs(at.p); fence_regs(at.o);
        pd = sd;
        uint32_t rel = bar_empty + 8;
        asm volatile("mapa.shared::cluster.u32 %0, %0, %1;" : "+r"(rel) : "r"(tid & 1));
        const uint32_t rel_off = rel - (bar_full + 8);

#define ISSUE_PV() do {                                                                                    \
            const uint32_t dv = pd + dlo(OFF_KV + 256, 640);                                               \
            wgmma_rs_n24_t1<HI_V>(at.o, at.p[0], at.p[1], at.p[2], at.p[3], dv, 1);                        \
            wgmma_rs_n24_t1<HI_V>(at.o, at.p[4], at.p[5], at.p[6], at.p[7], dv + 80, 1);                   \
            wgmma_rs_n24_t1<HI_V>(at.o, at.p[8], at.p[9], at.p[10], at.p[11], dv + 160, 1);                \
            wgmma_rs_n24_t1<HI_V>(at.o, at.p[12], at.p[13], at.p[14], at.p[15], dv + 240, 1);              \
        } while (0)
#define EXPS() do {                                                                                        \
            _Pragma("unroll") for (int i = 0; i < 16; i++) at.p[i] = pack(ex2(at.s[2 * i]), ex2(at.s[2 * i + 1])); \
            fence_regs(at.p);                                                                              \
        } while (0)
#define FUSED_STEP(DV, DK, NB, NPH, REL, GEMM_CODE) do {                                                   \
            uint32_t rdy;                                                                                  \
            if (WAITPOS == 0) rdy = mbar_test(NB, NPH);                                                    \
            wg_fence();                                                                                    \
            wgmma6_rs_n24_t1(at.o, at.p[0], at.p[1], at.p[2], at.p[3], (DV), 1);                           \
            wgmma6_rs_n24_t1(at.o, at.p[4], at.p[5], at.p[6], at.p[7], (DV) + 80, 1);                      \
            wgmma6_rs_n24_t1(at.o, at.p[8], at.p[9], at.p[10], at.p[11], (DV) + 160, 1);                   \
            wgmma6_rs_n24_t1(at.o, at.p[12], at.p[13], at.p[14], at.p[15], (DV) + 240, 1);                 \
            wgmma6_rs_n64_t0(at.s, at.q[0], at.q[1], at.q[2], at.q[3], (DK) + dlo(0, 128), 0);             \
            wgmma6_rs_n64_t0(at.s, at.q[4], at.q[5], at.q[6], at.q[7], (DK) + 32, 1);                      \
            wg_commit();                                                                                   \
            GEMM_CODE;                                                                                     \
            wg_commit();                                                                                   \
            if (WAITPOS == 0) mbar_wait_unless(rdy, NB, NPH);                                              \
            if (WAITPOS == 2) rdy = mbar_test(NB, NPH);                                                    \
            wg_wait<1>();                                                                                  \
            fence_regs(at.s); fence_regs(at.p);                                                            \
            if (tid < 2) asm volatile("mbarrier.arrive.shared::cluster.b64 _, [%0];" ::"r"(REL) : "memory"); \
            if (WAITPOS == 1) rdy = mbar_test(NB, NPH);                                                    \
            EXPS();                                                                                        \
            if (WAITPOS != 0) mbar_wait_unless(rdy, NB, NPH);                                              \
        } while (0)
#define FUSED_PAIR(HIA, LOA, LOB, STEP0, GEMM) do {                                                             \
            const uint64_t dv0 = mkdesc<HI_V>(pd + dlo(OFF_KV + 256, 640));                                \
            const uint64_t dv1 = mkdesc<HI_V>(sd + dlo(OFF_KV + 256, 640));                                \
            const uint64_t dk = mkdesc<HI_K>(sd + dlo(OFF_KV, 0));                                         \
            const uint64_t da = mkdesc<HIA>(sd + (LOA)), db = mkdesc<HI_W>(sd + (LOB));                    \
            STEP0(dv0, dk, fb + 8, ph, rel, GEMM(da, db, first));                                               \
            const uint32_t r1 = fb + rel_off;                                                              \
            rel = r1 + 8;                                                                                  \
            pd = sd + (SLOT >> 4); pb = fb + 8;                                                            \
            if (fb == bar_full + (NSTAGE - 2) * 8) { fb = bar_full; ph ^= 1; } else fb += 16;              \
            sd = (sd == sbd + (NSTAGE - 2) * (SLOT >> 4)) ? sbd : sd + 2 * (SLOT >> 4);                    \
            FUSED_STEP(dv1, dk + (SLOT >> 4), fb, ph, r1, GEMM(da + (SLOT >> 4), db + (SLOT >> 4), 1));    \
            first = 1;                                                                                     \
            TRACE();                                                                                       \
        } while (0)
#define GEMM_256(A, B, SC) do { wgmma6_ss_n256_t1(acc, A, B, SC); wgmma6_ss_n256_t1(acc, (A) + 2, (B) + 128, 1); } while (0)
#define GEMM_80(A, B, SC) do { wgmma6_ss_n80_t1(keep, A, B, SC); wgmma6_ss_n80_t1(keep, (A) + 256, (B) + 128, 1); wgmma6_ss_n80_t1(keep, (A) + 512, (B) + 256, 1); } while (0)
#define GEMM_144(A, B, SC) do { wgmma6_ss_n144_t1(ah, A, B, SC); wgmma6_ss_n144_t1(ah, (A) + 256, (B) + 128, 1); wgmma6_ss_n144_t1(ah, (A) + 512, (B) + 256, 1); } while (0)
#define NORM_ITEM(item) do {                                                                               \
            if (norm_o(ow, at.o, lane, gaddr)) {                                                           \
                attn_true_max(at.o, at.q, g_kv + (size_t)(j * 4 + (item)) * HEAD_BYTES + lane * 4);        \
                norm_o(ow, at.o, lane, gaddr);                                                             \
            }                                                                                              \
        } while (0)
#define STORE_ITEM(item) do { uint32_t ow[6]; NORM_ITEM(item); PUT_ITEM(item); } while (0)
#define PUT_ITEM(item) do {                                                                                \
            uint8_t* op = a2w + (288 + ((item) * 4 + (j >> 1)) * 3) * 4096 + (j & 1) * 4224;            \
            const int step = (j & 1) ? 3968 : 128;                                                         \
            stg32(op, ow[0]);        stg32(op + 256, ow[1]);                                               \
            stg32(op + step, ow[2]); stg32(op + step + 256, ow[3]);                                        \
            stg32(op + 4096, ow[4]); stg32(op + 4096 + 256, ow[5]);                                        \
        } while (0)
#define ITEM_STEP(DV, DK, NB, NPH, REL, GEMM_CODE) do {                                                    \
            uint32_t qo[8];                                                                                \
            _Pragma("unroll") for (int i = 0; i < 6; i++) asm volatile("mov.b32 %0, %1;" : "=r"(qo[i]) : "r"(at.q[i])); \
            load_q(at.q, qa + (item + 1) * 4608, lane);                                                    \
            fence_regs(at.q);                                                                              \
            wg_fence();                                                                                    \
            wgmma6_rs_n24_t1(at.o, at.p[0], at.p[1], at.p[2], at.p[3], (DV), 1);                           \
            wgmma6_rs_n24_t1(at.o, at.p[4], at.p[5], at.p[6], at.p[7], (DV) + 80, 1);                      \
            wgmma6_rs_n24_t1(at.o, at.p[8], at.p[9], at.p[10], at.p[11], (DV) + 160, 1);                   \
            wgmma6_rs_n24_t1(at.o, at.p[12], at.p[13], at.p[14], at.p[15], (DV) + 240, 1);                 \
            wgmma6_rs_n64_t0(at.s, at.q[0], at.q[1], at.q[2], at.q[3], (DK) + dlo(0, 128), 0);             \
            wgmma6_rs_n64_t0(at.s, at.q[4], at.q[5], at.q[6], at.q[7], (DK) + 32, 1);                      \
            wg_commit();                                                                                   \
            GEMM_CODE;                                                                                     \
            wg_commit();                                                                                   \
            wg_wait<1>();                                                                                  \
            fence_regs(at.o); fence_regs(at.p); fence_regs(at.s);                                          \
            if (tid < 2) asm volatile("mbarrier.arrive.shared::cluster.b64 _, [%0];" ::"r"(REL) : "memory"); \
            uint32_t ow[6];                                                                                \
            const bool bad = norm_o(ow, at.o, lane, gaddr);                                                \
            EXPS();                                                                                        \
            if (bad) {                                                                                     \
                attn_true_max(at.o, qo, g_kv + (size_t)(j * 4 + (item)) * HEAD_BYTES + lane * 4);          \
                norm_o(ow, at.o, lane, gaddr);                                                             \
            }                                                                                              \
            PUT_ITEM(item);                                                                                \
            _Pragma("unroll") for (int i = 0; i < 12; i++) at.o[i] = 0.f;                                  \
            fence_regs(at.o);                                                                              \
            mbar_wait(NB, NPH);                                                                            \
        } while (0)
#define C ,

#define H2(i) pack(geglu2(acc[i], acc[64 + (i)]), geglu2(acc[(i) + 1], acc[65 + (i)]))
        float keep[40];
        float4 px[3];
        {
            float ah[72];
            int first = 1;
            {
#pragma unroll 1
                for (int t = 0; t < 5; t++) {
                    int n = 0x26988 >> (t * 4) & 15;
#pragma unroll 1
                    do { FUSED_PAIR(HI_X, wg * 256 + dlo(OFF_AX, 16), dlo(0, 4096), FUSED_STEP, GEMM_256); } while (--n);
                    if (t & 1) {
                        const int item = t >> 1;
                        mbar_wait(t == 1 ? bar_gate : bar_rdy + 2 * 8, 0);
                        FUSED_PAIR(HI_X, wg * 256 + dlo(OFF_AX, 16), dlo(0, 4096), ITEM_STEP, GEMM_256);
                    }
                    if (t < 3) {
                        mbar_wait(t > 0 ? bar_rdy + (t - 1) * 8 : bar_free + wg * 8, 0);
                        wg_wait<0>();
                        fence_regs(acc);
                        first = 0;
#define EPI_STAGED {                                                                                       \
                        PROF(4 + 2 * t);                                                                   \
                        const uint32_t ha = sb + wg * 3 * SLOT + OFF_GAP + wq * 512 + lane * 16;           \
                        _Pragma("unroll") for (int k = 0; k < 8; k++)                                      \
                            stsm4(ha + (k / 3) * SLOT + (k % 3) * 2048, H2(8 * k), H2(8 * k + 4), H2(8 * k + 2), H2(8 * k + 6)); \
                        fence_async_shared();                                                              \
                        undef_regs(acc);                                                                   \
                        signal(t);                                                                         \
                        PROF(5 + 2 * t); }
                        EPI_STAGED;
                    }
                }
                wg_wait<0>();
                fence_regs(acc);
                first = 0;
#define EPI_DIRECT {                                                                                       \
                PROF(10);                                                                                  \
                uint8_t* hp = a2w + (j * 36 + 24) * 4096;                                                  \
                _Pragma("unroll") for (int i = 0; i < 16; i++) {                                           \
                    stg32(hp + (i >> 1) * 4096 + (i & 1) * 128, H2(4 * i));                                \
                    stg32(hp + (i >> 1) * 4096 + (i & 1) * 128 + 256, H2(4 * i + 2));                      \
                }                                                                                          \
                signal(3);                                                                                 \
                PROF(11); }
                EPI_DIRECT;
            }
#pragma unroll 1
            for (int seg = 0; seg < 3; seg++) {
                int n = 0x2AD >> (seg * 4) & 15;
#pragma unroll 1
                do { FUSED_PAIR(HI_A2, wg * 128 + dlo(OFF_A2, 128), dlo(0, 6144), FUSED_STEP, GEMM_144); } while (--n);
                if (seg == 0) {
                    constexpr int item = 2;
                    FUSED_PAIR(HI_A2, wg * 128 + dlo(OFF_A2, 128), dlo(0, 6144), ITEM_STEP, GEMM_144);
                    signal(5);
                } else {
                    if (seg == 1) {
                        wg_wait<0>();
                        fence_regs(ah);
                        PROF(12);
                        const float w0 = 0.5f - 0.5f * __uint_as_float(lds32(gaddr)), w1 = 0.5f - 0.5f * __uint_as_float(lds32(gaddr + 32));
#pragma unroll
                        for (int i = 0; i < 72; i++) ah[i] *= (i & 2) ? w1 : w0;
                        fence_regs(ah);
                    }
                }
            }
            wg_wait<0>();
            fence_regs(ah);
            PROF(17);
            mbar_wait(bar_px, 0);
#pragma unroll
            for (int i = 0; i < 3; i++) px[i] = __ldcg(g_px + (size_t)(cta * 2 + wg) * 3 * 128 + tid + i * 128);
            uint4* mine = g_part + (size_t)(cta * 2 + wg) * 5 * 128 + tid;
#pragma unroll
            for (int i = 0; i < 5; i++) {
                uint32_t u[4];
#pragma unroll
                for (int e = 0; e < 4; e++) {
                    const int k = 8 * i + 2 * e;
                    if (i < 4) {
                        u[e] = pack(sel(hf, ah[k], ah[32 + k]), sel(hf, ah[k + 1], ah[33 + k]));
                        keep[k] = sel(hf, ah[32 + k], ah[k]); keep[k + 1] = sel(hf, ah[33 + k], ah[k + 1]);
                    } else {
                        u[e] = pack(ah[32 + k], ah[33 + k]);
                        keep[k] = sel(1, ah[32 + k], 0.f); keep[k + 1] = sel(1, ah[33 + k], 0.f);
                    }
                }
                __stcg(mine + i * 128, make_uint4(u[0], u[1], u[2], u[3]));
            }
            signal(6);
            fence_regs(keep);
        }
        {
            int first = 1;
            FUSED_PAIR(HI_A2, wg * 128 + dlo(OFF_A2, 128), dlo(0, 6144), FUSED_STEP, GEMM_80);
        }
        PROF(13);
        wg_fence();
        ISSUE_PV();
        wg_commit();
        wg_wait<0>();
        fence_regs(at.o); fence_regs(at.p); fence_regs(at.q);
#pragma unroll
        for (int i = 0; i < 3; i++) { at.o[4 * i] += px[i].x; at.o[4 * i + 1] += px[i].y; at.o[4 * i + 2] += px[i].z; at.o[4 * i + 3] += px[i].w; }
        STORE_ITEM(3);
        signal(7);
        fence_regs(keep);
        PROF(14);
#define WO_STAGES(FROM, TO) _Pragma("unroll 1") for (int kk = FROM; kk < TO; kk++) {                       \
            mbar_wait(fb, ph);                                                                             \
            if (kk == 2) PROF(15);                                                                         \
            const uint64_t da = mkdesc<HI_A2>(sd + wg * 128 + dlo(OFF_A2, 128)), db = mkdesc<HI_W>(sd + dlo(0, 6144)); \
            wg_fence();                                                                                    \
            GEMM_80(da, db, 1);                                                                            \
            wg_commit();                                                                                   \
            wg_wait<1>();                                                                                  \
            if (kk < 1) release();                                      \
            STAGE_NEXT;                                                                                    \
        }
        WO_STAGES(0, 2)
        {
            mbar_wait(bar_rdy + 6 * 8, 0);
            const uint4* theirs = g_part + (size_t)((cta ^ 8) * 2 + wg) * 5 * 128 + tid;
            uint4 pv[5];
#pragma unroll
            for (int i = 0; i < 5; i++) pv[i] = __ldcg(theirs + i * 128);
            wg_wait<0>();
            fence_regs(keep);
#pragma unroll
            for (int i = 0; i < 5; i++) {
                const uint32_t u[4] = {pv[i].x, pv[i].y, pv[i].z, pv[i].w};
#pragma unroll
                for (int e = 0; e < 4; e++) { keep[8 * i + 2 * e] += __uint_as_float(u[e] << 16); keep[8 * i + 2 * e + 1] += __uint_as_float(u[e] & 0xffff0000u); }
            }
            fence_regs(keep);
        }
        WO_STAGES(2, 6)
        asm volatile("barrier.cluster.arrive.relaxed.aligned;" ::: "memory");
        const uint32_t tb = sb + (warp >> 1) * SLOT + OFF_KV + (warp & 1) * 2560;
        const uint32_t trow = ((lane >> 3) & 1) * 8 + (lane & 7);
        uint8_t* op = (uint8_t*)(out + (size_t)(m * 128 + grp * 8) * DM);
        wg_wait<0>();
        fence_regs(keep);
        PROF(16);
#pragma unroll
        for (int i = 0; i < 5; i++) {
            const uint32_t a = i < 4 ? tb + trow * 128 + (((2 * i + (lane >> 4)) ^ (lane & 7)) << 4) : tb + 2048 + trow * 32 + (lane >> 4) * 16;
            stsm4(a, pack(keep[8 * i], keep[8 * i + 1]), pack(keep[8 * i + 2], keep[8 * i + 3]), pack(keep[8 * i + 4], keep[8 * i + 5]), pack(keep[8 * i + 6], keep[8 * i + 7]));
        }
        __syncwarp();
        uint4 v[5];
#pragma unroll
        for (int i = 0; i < 5; i++) {
            const uint32_t r = 4 * i + (lane >> 3);
            const uint32_t a = i < 4 ? tb + r * 128 + (((lane & 7) ^ (r & 7)) << 4) : tb + 2048 + lane * 16;
            asm volatile("ld.shared.v4.u32 {%0, %1, %2, %3}, [%4];" : "=r"(v[i].x), "=r"(v[i].y), "=r"(v[i].z), "=r"(v[i].w) : "r"(a) : "memory");
        }
#pragma unroll
        for (int i = 0; i < 4; i++) *(uint4*)(op + (4 * i + (lane >> 3)) * (DM * 2) + nt * 256 + hf * 128 + (lane & 7) * 16) = v[i];
        if (wg == hf) *(uint4*)(op + (lane >> 1) * (DM * 2) + 1024 + nt * 32 + (lane & 1) * 16) = v[4];
        PROF(20);
        asm volatile("barrier.cluster.wait.aligned;" ::: "memory");
    }
}

typedef CUresult (*EncodeFn)(CUtensorMap*, CUtensorMapDataType, cuuint32_t, void*, const cuuint64_t*, const cuuint64_t*,
                             const cuuint32_t*, const cuuint32_t*, CUtensorMapInterleave, CUtensorMapSwizzle,
                             CUtensorMapL2promotion, CUtensorMapFloatOOBfill);

CUtensorMap make_map(EncodeFn enc, const void* ptr, uint64_t inner, uint64_t outer, uint32_t box_inner, uint32_t box_outer, CUtensorMapSwizzle swz) {
    CUtensorMap t;
    cuuint64_t dims[2] = {inner, outer};
    cuuint64_t strides[1] = {inner * 2};
    cuuint32_t box[2] = {box_inner, box_outer};
    cuuint32_t es[2] = {1, 1};
    enc(&t, CU_TENSOR_MAP_DATA_TYPE_BFLOAT16, 2, const_cast<void*>(ptr), dims, strides, box, es, CU_TENSOR_MAP_INTERLEAVE_NONE, swz,
        CU_TENSOR_MAP_L2_PROMOTION_L2_256B, CU_TENSOR_MAP_FLOAT_OOB_FILL_NONE);
    return t;
}

CUtensorMap make_strip_map(EncodeFn enc, const void* ptr, uint64_t rows, uint64_t width) {
    CUtensorMap t;
    cuuint64_t dims[3] = {width, rows, (DM - width) / 8 + 1};
    cuuint64_t strides[2] = {DM * 2, 16};
    cuuint32_t box[3] = {64, 24, 1};
    cuuint32_t es[3] = {1, 1, 1};
    enc(&t, CU_TENSOR_MAP_DATA_TYPE_BFLOAT16, 3, const_cast<void*>(ptr), dims, strides, box, es, CU_TENSOR_MAP_INTERLEAVE_NONE,
        CU_TENSOR_MAP_SWIZZLE_128B, CU_TENSOR_MAP_L2_PROMOTION_L2_128B, CU_TENSOR_MAP_FLOAT_OOB_FILL_NONE);
    return t;
}

}

extern "C" void kernel_launch(void* const* d_in, const int* in_sizes, int n_in, void* d_out, int out_size) {
    (void)in_sizes; (void)n_in; (void)out_size;
    void* fn = nullptr;
    cudaDriverEntryPointQueryResult qr;
    cudaGetDriverEntryPoint("cuTensorMapEncodeTiled", &fn, cudaEnableDefault, &qr);
    EncodeFn enc = (EncodeFn)fn;
    const CUtensorMap tm_x = make_map(enc, d_in[0], DM, SEQ, 32, 128, CU_TENSOR_MAP_SWIZZLE_64B);
    const CUtensorMap tm_qkv = make_map(enc, d_in[1], 3 * DM, DM, 64, 16, CU_TENSOR_MAP_SWIZZLE_128B);
    const CUtensorMap tm_qkv8 = make_map(enc, d_in[1], 3 * DM, DM, 8, 16, CU_TENSOR_MAP_SWIZZLE_NONE);
    const CUtensorMap tm_wo = make_map(enc, d_in[2], DM, DM, 64, 24, CU_TENSOR_MAP_SWIZZLE_128B);
    const CUtensorMap tm_wg = make_map(enc, d_in[4], FF, DM, 64, 32, CU_TENSOR_MAP_SWIZZLE_128B);
    const CUtensorMap tm_wu = make_map(enc, d_in[5], FF, DM, 64, 32, CU_TENSOR_MAP_SWIZZLE_128B);
    const CUtensorMap tm_wd = make_map(enc, d_in[6], DM, FF, 64, 24, CU_TENSOR_MAP_SWIZZLE_128B);
    const CUtensorMap tm_wd16 = make_strip_map(enc, d_in[6], FF, 16), tm_wo16 = make_strip_map(enc, d_in[2], DM, 16);
    cudaFuncSetAttribute(fused_kernel, cudaFuncAttributeMaxDynamicSharedMemorySize, SMEM_BYTES);
    fused_kernel<<<NCTA + 4, 384, SMEM_BYTES>>>((__nv_bfloat16*)d_out, (const __nv_bfloat16*)d_in[0], (const __nv_bfloat16*)d_in[7],
                                               tm_x, tm_qkv, tm_qkv8, tm_wg, tm_wu, tm_wd, tm_wo, tm_wd16, tm_wo16);
}
```

```cpp
#include <cuda_runtime.h>
#include <cuda.h>
#include <cuda_bf16.h>
#include <stdint.h>

#define PROFILE 0
#define DOTRACE 0

namespace {

constexpr int SEQ = 2048, DM = 576, FF = 4608;
constexpr int NCTA = 128;
constexpr int NSTAGE = 6;
constexpr int DEFER = 2;
constexpr int SLOT = 35 * 1024;
constexpr int OFF_AX = 22528;
constexpr int OFF_A2 = 18432;
constexpr int OFF_TL = 20480;
constexpr int OFF_GAP = 16384;
constexpr int OFF_KV = 30720;
constexpr int OFF_Q = NSTAGE * SLOT - 4608;
constexpr int OFF_BAR = NSTAGE * SLOT + 3 * 4608;
constexpr int SMEM_BYTES = OFF_BAR + 1024 + 1024;

constexpr int HEAD_BYTES = 256 * 640;
constexpr int A2_TILE = 336 * 4096;

constexpr int FL_KV = 0;
constexpr int FL_M = FL_KV + 8 * 32;
constexpr int FM_H = 0;
constexpr int FM_LATE = 7;
constexpr int FM_R = 16;
constexpr int FL_G = FL_M + 16 * 64;
constexpr int FL_E = FL_G + 4 * 32;
constexpr int FL_N = FL_E + (NCTA + 4) * 32;

__device__ __align__(1024) uint8_t g_kv[32 * HEAD_BYTES];
__device__ __align__(1024) uint8_t g_a2[16 * A2_TILE];
__device__ __align__(1024) uint4 g_part[NCTA * 2 * 5 * 128];
__device__ __align__(1024) uint8_t g_q3[NCTA * 4608];
__device__ __align__(1024) float4 g_px[NCTA * 2 * 3 * 128];
__device__ float g_gate[SEQ];
__device__ __align__(256) uint32_t g_flags[FL_N];

template <uint32_t BHI>
__device__ __forceinline__ void wgmma_rs_n24_t1(float (&d)[12], uint32_t a0, uint32_t a1, uint32_t a2, uint32_t a3, uint32_t db, int scale_d) {
  asm volatile("{\n.reg .pred p;\n.reg .b64 da, db;\n"
    "mov.b64 db, {%16, %18};\n"
    "setp.ne.b32 p, %17, 0;\n"
    "wgmma.mma_async.sync.aligned.m64n24k16.f32.bf16.bf16 "
    "{%0, %1, %2, %3, %4, %5, %6, %7, %8, %9, %10, %11}, "
    "{%12, %13, %14, %15}, db, p, 1, 1, 1;\n}\n"
    : "+f"(d[0]), "+f"(d[1]), "+f"(d[2]), "+f"(d[3]), "+f"(d[4]), "+f"(d[5]), "+f"(d[6]), "+f"(d[7]),
      "+f"(d[8]), "+f"(d[9]), "+f"(d[10]), "+f"(d[11])
    : "r"(a0), "r"(a1), "r"(a2), "r"(a3), "r"(db), "r"(scale_d), "n"(BHI));
}
template <uint32_t BHI>
__device__ __forceinline__ void wgmma_rs_n128_t0(float (&d)[64], uint32_t a0, uint32_t a1, uint32_t a2, uint32_t a3, uint32_t db, int scale_d) {
  asm volatile("{\n.reg .pred p;\n.reg .b64 da, db;\n"
    "mov.b64 db, {%68, %70};\n"
    "setp.ne.b32 p, %69, 0;\n"
    "wgmma.mma_async.sync.aligned.m64n128k16.f32.bf16.bf16 "
    "{%0, %1, %2, %3, %4, %5, %6, %7, %8, %9, %10, %11, %12, %13, %14, %15, "
    "%16, %17, %18, %19, %20, %21, %22, %23, %24, %25, %26, %27, %28, %29, %30, %31, "
    "%32, %33, %34, %35, %36, %37, %38, %39, %40, %41, %42, %43, %44, %45, %46, %47, "
    "%48, %49, %50, %51, %52, %53, %54, %55, %56, %57, %58, %59, %60, %61, %62, %63}, "
    "{%64, %65, %66, %67}, db, p, 1, 1, 0;\n}\n"
    : "+f"(d[0]), "+f"(d[1]), "+f"(d[2]), "+f"(d[3]), "+f"(d[4]), "+f"(d[5]), "+f"(d[6]), "+f"(d[7]),
      "+f"(d[8]), "+f"(d[9]), "+f"(d[10]), "+f"(d[11]), "+f"(d[12]), "+f"(d[13]), "+f"(d[14]), "+f"(d[15]),
      "+f"(d[16]), "+f"(d[17]), "+f"(d[18]), "+f"(d[19]), "+f"(d[20]), "+f"(d[21]), "+f"(d[22]), "+f"(d[23]),
      "+f"(d[24]), "+f"(d[25]), "+f"(d[26]), "+f"(d[27]), "+f"(d[28]), "+f"(d[29]), "+f"(d[30]), "+f"(d[31]),
      "+f"(d[32]), "+f"(d[33]), "+f"(d[34]), "+f"(d[35]), "+f"(d[36]), "+f"(d[37]), "+f"(d[38]), "+f"(d[39]),
      "+f"(d[40]), "+f"(d[41]), "+f"(d[42]), "+f"(d[43]), "+f"(d[44]), "+f"(d[45]), "+f"(d[46]), "+f"(d[47]),
      "+f"(d[48]), "+f"(d[49]), "+f"(d[50]), "+f"(d[51]), "+f"(d[52]), "+f"(d[53]), "+f"(d[54]), "+f"(d[55]),
      "+f"(d[56]), "+f"(d[57]), "+f"(d[58]), "+f"(d[59]), "+f"(d[60]), "+f"(d[61]), "+f"(d[62]), "+f"(d[63])
    : "r"(a0), "r"(a1), "r"(a2), "r"(a3), "r"(db), "r"(scale_d), "n"(BHI));
}
template <uint32_t AHI, uint32_t BHI>
__device__ __forceinline__ void wgmma_ss_n24_t1(float (&d)[12], uint32_t da, uint32_t db, int scale_d) {
  asm volatile("{\n.reg .pred p;\n.reg .b64 da, db;\n"
    "mov.b64 da, {%12, %15};\nmov.b64 db, {%13, %16};\n"
    "setp.ne.b32 p, %14, 0;\n"
    "wgmma.mma_async.sync.aligned.m64n24k16.f32.bf16.bf16 "
    "{%0, %1, %2, %3, %4, %5, %6, %7, %8, %9, %10, %11}, "
    "da, db, p, 1, 1, 0, 1;\n}\n"
    : "+f"(d[0]), "+f"(d[1]), "+f"(d[2]), "+f"(d[3]), "+f"(d[4]), "+f"(d[5]), "+f"(d[6]), "+f"(d[7]),
      "+f"(d[8]), "+f"(d[9]), "+f"(d[10]), "+f"(d[11])
    : "r"(da), "r"(db), "r"(scale_d), "n"(AHI), "n"(BHI));
}
template <uint32_t AHI, uint32_t BHI>
__device__ __forceinline__ void wgmma_ss_n128_t1(float (&d)[64], uint32_t da, uint32_t db, int scale_d) {
  asm volatile("{\n.reg .pred p;\n.reg .b64 da, db;\n"
    "mov.b64 da, {%64, %67};\nmov.b64 db, {%65, %68};\n"
    "setp.ne.b32 p, %66, 0;\n"
    "wgmma.mma_async.sync.aligned.m64n128k16.f32.bf16.bf16 "
    "{%0, %1, %2, %3, %4, %5, %6, %7, %8, %9, %10, %11, %12, %13, %14, %15, "
    "%16, %17, %18, %19, %20, %21, %22, %23, %24, %25, %26, %27, %28, %29, %30, %31, "
    "%32, %33, %34, %35, %36, %37, %38, %39, %40, %41, %42, %43, %44, %45, %46, %47, "
    "%48, %49, %50, %51, %52, %53, %54, %55, %56, %57, %58, %59, %60, %61, %62, %63}, "
    "da, db, p, 1, 1, 0, 1;\n}\n"
    : "+f"(d[0]), "+f"(d[1]), "+f"(d[2]), "+f"(d[3]), "+f"(d[4]), "+f"(d[5]), "+f"(d[6]), "+f"(d[7]),
      "+f"(d[8]), "+f"(d[9]), "+f"(d[10]), "+f"(d[11]), "+f"(d[12]), "+f"(d[13]), "+f"(d[14]), "+f"(d[15]),
      "+f"(d[16]), "+f"(d[17]), "+f"(d[18]), "+f"(d[19]), "+f"(d[20]), "+f"(d[21]), "+f"(d[22]), "+f"(d[23]),
      "+f"(d[24]), "+f"(d[25]), "+f"(d[26]), "+f"(d[27]), "+f"(d[28]), "+f"(d[29]), "+f"(d[30]), "+f"(d[31]),
      "+f"(d[32]), "+f"(d[33]), "+f"(d[34]), "+f"(d[35]), "+f"(d[36]), "+f"(d[37]), "+f"(d[38]), "+f"(d[39]),
      "+f"(d[40]), "+f"(d[41]), "+f"(d[42]), "+f"(d[43]), "+f"(d[44]), "+f"(d[45]), "+f"(d[46]), "+f"(d[47]),
      "+f"(d[48]), "+f"(d[49]), "+f"(d[50]), "+f"(d[51]), "+f"(d[52]), "+f"(d[53]), "+f"(d[54]), "+f"(d[55]),
      "+f"(d[56]), "+f"(d[57]), "+f"(d[58]), "+f"(d[59]), "+f"(d[60]), "+f"(d[61]), "+f"(d[62]), "+f"(d[63])
    : "r"(da), "r"(db), "r"(scale_d), "n"(AHI), "n"(BHI));
}
template <uint32_t AHI, uint32_t BHI>
__device__ __forceinline__ void wgmma_ss_n192_t1(float (&d)[96], uint32_t da, uint32_t db, int scale_d) {
  asm volatile("{\n.reg .pred p;\n.reg .b64 da, db;\n"
    "mov.b64 da, {%96, %99};\nmov.b64 db, {%97, %100};\n"
    "setp.ne.b32 p, %98, 0;\n"
    "wgmma.mma_async.sync.aligned.m64n192k16.f32.bf16.bf16 "
    "{%0, %1, %2, %3, %4, %5, %6, %7, %8, %9, %10, %11, %12, %13, %14, %15, "
    "%16, %17, %18, %19, %20, %21, %22, %23, %24, %25, %26, %27, %28, %29, %30, %31, "
    "%32, %33, %34, %35, %36, %37, %38, %39, %40, %41, %42, %43, %44, %45, %46, %47, "
    "%48, %49, %50, %51, %52, %53, %54, %55, %56, %57, %58, %59, %60, %61, %62, %63, "
    "%64, %65, %66, %67, %68, %69, %70, %71, %72, %73, %74, %75, %76, %77, %78, %79, "
    "%80, %81, %82, %83, %84, %85, %86, %87, %88, %89, %90, %91, %92, %93, %94, %95}, "
    "da, db, p, 1, 1, 0, 1;\n}\n"
    : "+f"(d[0]), "+f"(d[1]), "+f"(d[2]), "+f"(d[3]), "+f"(d[4]), "+f"(d[5]), "+f"(d[6]), "+f"(d[7]),
      "+f"(d[8]), "+f"(d[9]), "+f"(d[10]), "+f"(d[11]), "+f"(d[12]), "+f"(d[13]), "+f"(d[14]), "+f"(d[15]),
      "+f"(d[16]), "+f"(d[17]), "+f"(d[18]), "+f"(d[19]), "+f"(d[20]), "+f"(d[21]), "+f"(d[22]), "+f"(d[23]),
      "+f"(d[24]), "+f"(d[25]), "+f"(d[26]), "+f"(d[27]), "+f"(d[28]), "+f"(d[29]), "+f"(d[30]), "+f"(d[31]),
      "+f"(d[32]), "+f"(d[33]), "+f"(d[34]), "+f"(d[35]), "+f"(d[36]), "+f"(d[37]), "+f"(d[38]), "+f"(d[39]),
      "+f"(d[40]), "+f"(d[41]), "+f"(d[42]), "+f"(d[43]), "+f"(d[44]), "+f"(d[45]), "+f"(d[46]), "+f"(d[47]),
      "+f"(d[48]), "+f"(d[49]), "+f"(d[50]), "+f"(d[51]), "+f"(d[52]), "+f"(d[53]), "+f"(d[54]), "+f"(d[55]),
      "+f"(d[56]), "+f"(d[57]), "+f"(d[58]), "+f"(d[59]), "+f"(d[60]), "+f"(d[61]), "+f"(d[62]), "+f"(d[63]),
      "+f"(d[64]), "+f"(d[65]), "+f"(d[66]), "+f"(d[67]), "+f"(d[68]), "+f"(d[69]), "+f"(d[70]), "+f"(d[71]),
      "+f"(d[72]), "+f"(d[73]), "+f"(d[74]), "+f"(d[75]), "+f"(d[76]), "+f"(d[77]), "+f"(d[78]), "+f"(d[79]),
      "+f"(d[80]), "+f"(d[81]), "+f"(d[82]), "+f"(d[83]), "+f"(d[84]), "+f"(d[85]), "+f"(d[86]), "+f"(d[87]),
      "+f"(d[88]), "+f"(d[89]), "+f"(d[90]), "+f"(d[91]), "+f"(d[92]), "+f"(d[93]), "+f"(d[94]), "+f"(d[95])
    : "r"(da), "r"(db), "r"(scale_d), "n"(AHI), "n"(BHI));
}
template <uint32_t AHI, uint32_t BHI>
__device__ __forceinline__ void wgmma_ss_n256_t1(float (&d)[128], uint32_t da, uint32_t db, int scale_d) {
  asm volatile("{\n.reg .pred p;\n.reg .b64 da, db;\n"
    "mov.b64 da, {%128, %131};\nmov.b64 db, {%129, %132};\n"
    "setp.ne.b32 p, %130, 0;\n"
    "wgmma.mma_async.sync.aligned.m64n256k16.f32.bf16.bf16 "
    "{%0, %1, %2, %3, %4, %5, %6, %7, %8, %9, %10, %11, %12, %13, %14, %15, "
    "%16, %17, %18, %19, %20, %21, %22, %23, %24, %25, %26, %27, %28, %29, %30, %31, "
    "%32, %33, %34, %35, %36, %37, %38, %39, %40, %41, %42, %43, %44, %45, %46, %47, "
    "%48, %49, %50, %51, %52, %53, %54, %55, %56, %57, %58, %59, %60, %61, %62, %63, "
    "%64, %65, %66, %67, %68, %69, %70, %71, %72, %73, %74, %75, %76, %77, %78, %79, "
    "%80, %81, %82, %83, %84, %85, %86, %87, %88, %89, %90, %91, %92, %93, %94, %95, "
    "%96, %97, %98, %99, %100, %101, %102, %103, %104, %105, %106, %107, %108, %109, %110, %111, "
    "%112, %113, %114, %115, %116, %117, %118, %119, %120, %121, %122, %123, %124, %125, %126, %127}, "
    "da, db, p, 1, 1, 0, 1;\n}\n"
    : "+f"(d[0]), "+f"(d[1]), "+f"(d[2]), "+f"(d[3]), "+f"(d[4]), "+f"(d[5]), "+f"(d[6]), "+f"(d[7]),
      "+f"(d[8]), "+f"(d[9]), "+f"(d[10]), "+f"(d[11]), "+f"(d[12]), "+f"(d[13]), "+f"(d[14]), "+f"(d[15]),
      "+f"(d[16]), "+f"(d[17]), "+f"(d[18]), "+f"(d[19]), "+f"(d[20]), "+f"(d[21]), "+f"(d[22]), "+f"(d[23]),
      "+f"(d[24]), "+f"(d[25]), "+f"(d[26]), "+f"(d[27]), "+f"(d[28]), "+f"(d[29]), "+f"(d[30]), "+f"(d[31]),
      "+f"(d[32]), "+f"(d[33]), "+f"(d[34]), "+f"(d[35]), "+f"(d[36]), "+f"(d[37]), "+f"(d[38]), "+f"(d[39]),
      "+f"(d[40]), "+f"(d[41]), "+f"(d[42]), "+f"(d[43]), "+f"(d[44]), "+f"(d[45]), "+f"(d[46]), "+f"(d[47]),
      "+f"(d[48]), "+f"(d[49]), "+f"(d[50]), "+f"(d[51]), "+f"(d[52]), "+f"(d[53]), "+f"(d[54]), "+f"(d[55]),
      "+f"(d[56]), "+f"(d[57]), "+f"(d[58]), "+f"(d[59]), "+f"(d[60]), "+f"(d[61]), "+f"(d[62]), "+f"(d[63]),
      "+f"(d[64]), "+f"(d[65]), "+f"(d[66]), "+f"(d[67]), "+f"(d[68]), "+f"(d[69]), "+f"(d[70]), "+f"(d[71]),
      "+f"(d[72]), "+f"(d[73]), "+f"(d[74]), "+f"(d[75]), "+f"(d[76]), "+f"(d[77]), "+f"(d[78]), "+f"(d[79]),
      "+f"(d[80]), "+f"(d[81]), "+f"(d[82]), "+f"(d[83]), "+f"(d[84]), "+f"(d[85]), "+f"(d[86]), "+f"(d[87]),
      "+f"(d[88]), "+f"(d[89]), "+f"(d[90]), "+f"(d[91]), "+f"(d[92]), "+f"(d[93]), "+f"(d[94]), "+f"(d[95]),
      "+f"(d[96]), "+f"(d[97]), "+f"(d[98]), "+f"(d[99]), "+f"(d[100]), "+f"(d[101]), "+f"(d[102]), "+f"(d[103]),
      "+f"(d[104]), "+f"(d[105]), "+f"(d[106]), "+f"(d[107]), "+f"(d[108]), "+f"(d[109]), "+f"(d[110]), "+f"(d[111]),
      "+f"(d[112]), "+f"(d[113]), "+f"(d[114]), "+f"(d[115]), "+f"(d[116]), "+f"(d[117]), "+f"(d[118]), "+f"(d[119]),
      "+f"(d[120]), "+f"(d[121]), "+f"(d[122]), "+f"(d[123]), "+f"(d[124]), "+f"(d[125]), "+f"(d[126]), "+f"(d[127])
    : "r"(da), "r"(db), "r"(scale_d), "n"(AHI), "n"(BHI));
}
__device__ __forceinline__ void wgmma6_rs_n24_t1(float (&d)[12], uint32_t a0, uint32_t a1, uint32_t a2, uint32_t a3, uint64_t db, int scale_d) {
  asm volatile("{\n.reg .pred p;\n"
    "setp.ne.b32 p, %17, 0;\n"
    "wgmma.mma_async.sync.aligned.m64n24k16.f32.bf16.bf16 "
    "{%0, %1, %2, %3, %4, %5, %6, %7, %8, %9, %10, %11}, "
    "{%12, %13, %14, %15}, %16, p, 1, 1, 1;\n}\n"
    : "+f"(d[0]), "+f"(d[1]), "+f"(d[2]), "+f"(d[3]), "+f"(d[4]), "+f"(d[5]), "+f"(d[6]), "+f"(d[7]),
      "+f"(d[8]), "+f"(d[9]), "+f"(d[10]), "+f"(d[11])
    : "r"(a0), "r"(a1), "r"(a2), "r"(a3), "l"(db), "r"(scale_d));
}
__device__ __forceinline__ void wgmma6_rs_n64_t0(float (&d)[32], uint32_t a0, uint32_t a1, uint32_t a2, uint32_t a3, uint64_t db, int scale_d) {
  asm volatile("{\n.reg .pred p;\n"
    "setp.ne.b32 p, %37, 0;\n"
    "wgmma.mma_async.sync.aligned.m64n64k16.f32.bf16.bf16 "
    "{%0, %1, %2, %3, %4, %5, %6, %7, %8, %9, %10, %11, %12, %13, %14, %15, "
    "%16, %17, %18, %19, %20, %21, %22, %23, %24, %25, %26, %27, %28, %29, %30, %31}, "
    "{%32, %33, %34, %35}, %36, p, 1, 1, 0;\n}\n"
    : "+f"(d[0]), "+f"(d[1]), "+f"(d[2]), "+f"(d[3]), "+f"(d[4]), "+f"(d[5]), "+f"(d[6]), "+f"(d[7]),
      "+f"(d[8]), "+f"(d[9]), "+f"(d[10]), "+f"(d[11]), "+f"(d[12]), "+f"(d[13]), "+f"(d[14]), "+f"(d[15]),
      "+f"(d[16]), "+f"(d[17]), "+f"(d[18]), "+f"(d[19]), "+f"(d[20]), "+f"(d[21]), "+f"(d[22]), "+f"(d[23]),
      "+f"(d[24]), "+f"(d[25]), "+f"(d[26]), "+f"(d[27]), "+f"(d[28]), "+f"(d[29]), "+f"(d[30]), "+f"(d[31])
    : "r"(a0), "r"(a1), "r"(a2), "r"(a3), "l"(db), "r"(scale_d));
}
__device__ __forceinline__ void wgmma6_ss_n80_t1(float (&d)[40], uint64_t da, uint64_t db, int scale_d) {
  asm volatile("{\n.reg .pred p;\n"
    "setp.ne.b32 p, %42, 0;\n"
    "wgmma.mma_async.sync.aligned.m64n80k16.f32.bf16.bf16 "
    "{%0, %1, %2, %3, %4, %5, %6, %7, %8, %9, %10, %11, %12, %13, %14, %15, "
    "%16, %17, %18, %19, %20, %21, %22, %23, %24, %25, %26, %27, %28, %29, %30, %31, "
    "%32, %33, %34, %35, %36, %37, %38, %39}, "
    "%40, %41, p, 1, 1, 0, 1;\n}\n"
    : "+f"(d[0]), "+f"(d[1]), "+f"(d[2]), "+f"(d[3]), "+f"(d[4]), "+f"(d[5]), "+f"(d[6]), "+f"(d[7]),
      "+f"(d[8]), "+f"(d[9]), "+f"(d[10]), "+f"(d[11]), "+f"(d[12]), "+f"(d[13]), "+f"(d[14]), "+f"(d[15]),
      "+f"(d[16]), "+f"(d[17]), "+f"(d[18]), "+f"(d[19]), "+f"(d[20]), "+f"(d[21]), "+f"(d[22]), "+f"(d[23]),
      "+f"(d[24]), "+f"(d[25]), "+f"(d[26]), "+f"(d[27]), "+f"(d[28]), "+f"(d[29]), "+f"(d[30]), "+f"(d[31]),
      "+f"(d[32]), "+f"(d[33]), "+f"(d[34]), "+f"(d[35]), "+f"(d[36]), "+f"(d[37]), "+f"(d[38]), "+f"(d[39])
    : "l"(da), "l"(db), "r"(scale_d));
}
__device__ __forceinline__ void wgmma6_ss_n144_t1(float (&d)[72], uint64_t da, uint64_t db, int scale_d) {
  asm volatile("{\n.reg .pred p;\n"
    "setp.ne.b32 p, %74, 0;\n"
    "wgmma.mma_async.sync.aligned.m64n144k16.f32.bf16.bf16 "
    "{%0, %1, %2, %3, %4, %5, %6, %7, %8, %9, %10, %11, %12, %13, %14, %15, "
    "%16, %17, %18, %19, %20, %21, %22, %23, %24, %25, %26, %27, %28, %29, %30, %31, "
    "%32, %33, %34, %35, %36, %37, %38, %39, %40, %41, %42, %43, %44, %45, %46, %47, "
    "%48, %49, %50, %51, %52, %53, %54, %55, %56, %57, %58, %59, %60, %61, %62, %63, "
    "%64, %65, %66, %67, %68, %69, %70, %71}, "
    "%72, %73, p, 1, 1, 0, 1;\n}\n"
    : "+f"(d[0]), "+f"(d[1]), "+f"(d[2]), "+f"(d[3]), "+f"(d[4]), "+f"(d[5]), "+f"(d[6]), "+f"(d[7]),
      "+f"(d[8]), "+f"(d[9]), "+f"(d[10]), "+f"(d[11]), "+f"(d[12]), "+f"(d[13]), "+f"(d[14]), "+f"(d[15]),
      "+f"(d[16]), "+f"(d[17]), "+f"(d[18]), "+f"(d[19]), "+f"(d[20]), "+f"(d[21]), "+f"(d[22]), "+f"(d[23]),
      "+f"(d[24]), "+f"(d[25]), "+f"(d[26]), "+f"(d[27]), "+f"(d[28]), "+f"(d[29]), "+f"(d[30]), "+f"(d[31]),
      "+f"(d[32]), "+f"(d[33]), "+f"(d[34]), "+f"(d[35]), "+f"(d[36]), "+f"(d[37]), "+f"(d[38]), "+f"(d[39]),
      "+f"(d[40]), "+f"(d[41]), "+f"(d[42]), "+f"(d[43]), "+f"(d[44]), "+f"(d[45]), "+f"(d[46]), "+f"(d[47]),
      "+f"(d[48]), "+f"(d[49]), "+f"(d[50]), "+f"(d[51]), "+f"(d[52]), "+f"(d[53]), "+f"(d[54]), "+f"(d[55]),
      "+f"(d[56]), "+f"(d[57]), "+f"(d[58]), "+f"(d[59]), "+f"(d[60]), "+f"(d[61]), "+f"(d[62]), "+f"(d[63]),
      "+f"(d[64]), "+f"(d[65]), "+f"(d[66]), "+f"(d[67]), "+f"(d[68]), "+f"(d[69]), "+f"(d[70]), "+f"(d[71])
    : "l"(da), "l"(db), "r"(scale_d));
}
__device__ __forceinline__ void wgmma6_ss_n256_t1(float (&d)[128], uint64_t da, uint64_t db, int scale_d) {
  asm volatile("{\n.reg .pred p;\n"
    "setp.ne.b32 p, %130, 0;\n"
    "wgmma.mma_async.sync.aligned.m64n256k16.f32.bf16.bf16 "
    "{%0, %1, %2, %3, %4, %5, %6, %7, %8, %9, %10, %11, %12, %13, %14, %15, "
    "%16, %17, %18, %19, %20, %21, %22, %23, %24, %25, %26, %27, %28, %29, %30, %31, "
    "%32, %33, %34, %35, %36, %37, %38, %39, %40, %41, %42, %43, %44, %45, %46, %47, "
    "%48, %49, %50, %51, %52, %53, %54, %55, %56, %57, %58, %59, %60, %61, %62, %63, "
    "%64, %65, %66, %67, %68, %69, %70, %71, %72, %73, %74, %75, %76, %77, %78, %79, "
    "%80, %81, %82, %83, %84, %85, %86, %87, %88, %89, %90, %91, %92, %93, %94, %95, "
    "%96, %97, %98, %99, %100, %101, %102, %103, %104, %105, %106, %107, %108, %109, %110, %111, "
    "%112, %113, %114, %115, %116, %117, %118, %119, %120, %121, %122, %123, %124, %125, %126, %127}, "
    "%128, %129, p, 1, 1, 0, 1;\n}\n"
    : "+f"(d[0]), "+f"(d[1]), "+f"(d[2]), "+f"(d[3]), "+f"(d[4]), "+f"(d[5]), "+f"(d[6]), "+f"(d[7]),
      "+f"(d[8]), "+f"(d[9]), "+f"(d[10]), "+f"(d[11]), "+f"(d[12]), "+f"(d[13]), "+f"(d[14]), "+f"(d[15]),
      "+f"(d[16]), "+f"(d[17]), "+f"(d[18]), "+f"(d[19]), "+f"(d[20]), "+f"(d[21]), "+f"(d[22]), "+f"(d[23]),
      "+f"(d[24]), "+f"(d[25]), "+f"(d[26]), "+f"(d[27]), "+f"(d[28]), "+f"(d[29]), "+f"(d[30]), "+f"(d[31]),
      "+f"(d[32]), "+f"(d[33]), "+f"(d[34]), "+f"(d[35]), "+f"(d[36]), "+f"(d[37]), "+f"(d[38]), "+f"(d[39]),
      "+f"(d[40]), "+f"(d[41]), "+f"(d[42]), "+f"(d[43]), "+f"(d[44]), "+f"(d[45]), "+f"(d[46]), "+f"(d[47]),
      "+f"(d[48]), "+f"(d[49]), "+f"(d[50]), "+f"(d[51]), "+f"(d[52]), "+f"(d[53]), "+f"(d[54]), "+f"(d[55]),
      "+f"(d[56]), "+f"(d[57]), "+f"(d[58]), "+f"(d[59]), "+f"(d[60]), "+f"(d[61]), "+f"(d[62]), "+f"(d[63]),
      "+f"(d[64]), "+f"(d[65]), "+f"(d[66]), "+f"(d[67]), "+f"(d[68]), "+f"(d[69]), "+f"(d[70]), "+f"(d[71]),
      "+f"(d[72]), "+f"(d[73]), "+f"(d[74]), "+f"(d[75]), "+f"(d[76]), "+f"(d[77]), "+f"(d[78]), "+f"(d[79]),
      "+f"(d[80]), "+f"(d[81]), "+f"(d[82]), "+f"(d[83]), "+f"(d[84]), "+f"(d[85]), "+f"(d[86]), "+f"(d[87]),
      "+f"(d[88]), "+f"(d[89]), "+f"(d[90]), "+f"(d[91]), "+f"(d[92]), "+f"(d[93]), "+f"(d[94]), "+f"(d[95]),
      "+f"(d[96]), "+f"(d[97]), "+f"(d[98]), "+f"(d[99]), "+f"(d[100]), "+f"(d[101]), "+f"(d[102]), "+f"(d[103]),
      "+f"(d[104]), "+f"(d[105]), "+f"(d[106]), "+f"(d[107]), "+f"(d[108]), "+f"(d[109]), "+f"(d[110]), "+f"(d[111]),
      "+f"(d[112]), "+f"(d[113]), "+f"(d[114]), "+f"(d[115]), "+f"(d[116]), "+f"(d[117]), "+f"(d[118]), "+f"(d[119]),
      "+f"(d[120]), "+f"(d[121]), "+f"(d[122]), "+f"(d[123]), "+f"(d[124]), "+f"(d[125]), "+f"(d[126]), "+f"(d[127])
    : "l"(da), "l"(db), "r"(scale_d));
}

__device__ __forceinline__ void wg_fence() { asm volatile("wgmma.fence.sync.aligned;" ::: "memory"); }
__device__ __forceinline__ void wg_commit() { asm volatile("wgmma.commit_group.sync.aligned;" ::: "memory"); }
template <int N> __device__ __forceinline__ void wg_wait() { asm volatile("wgmma.wait_group.sync.aligned %0;" ::"n"(N) : "memory"); }
__host__ __device__ constexpr uint32_t dlo(uint32_t off, uint32_t lbo) { return (off >> 4) | ((lbo >> 4) << 16); }
__host__ __device__ constexpr uint32_t dhi(uint32_t sbo, uint32_t swz) { return (sbo >> 4) | (swz << 30); }
constexpr uint32_t HI_X = dhi(512, 2), HI_W = dhi(1024, 1), HI_A2 = dhi(256, 0), HI_K = dhi(640, 0), HI_V = dhi(128, 0), HI_T = dhi(512, 0);
__device__ __forceinline__ float ex2(float x) { float y; asm volatile("ex2.approx.ftz.f32 %0, %1;" : "=f"(y) : "f"(x)); return y; }
template <uint32_t HI> __device__ __forceinline__ uint64_t mkdesc(uint32_t lo) {
    uint64_t d;
    asm("mov.b64 %0, {%1, %2};" : "=l"(d) : "r"(lo), "n"(HI));
    return d;
}
__device__ __forceinline__ float sel(int p, float a, float b) {
    float y;
    asm("{\n.reg .pred q;\nsetp.ne.s32 q, %3, 0;\nselp.f32 %0, %1, %2, q;\n}" : "=f"(y) : "f"(a), "f"(b), "r"(p));
    return y;
}
__device__ __forceinline__ float rcp_fast(float x) { float y; asm("rcp.approx.ftz.f32 %0, %1;" : "=f"(y) : "f"(x)); return y; }
__device__ __forceinline__ float tanh_fast(float x) { float y; asm("tanh.approx.f32 %0, %1;" : "=f"(y) : "f"(x)); return y; }
__device__ __forceinline__ uint32_t pack(float lo, float hi) { uint32_t y; asm("cvt.rn.bf16x2.f32 %0, %1, %2;" : "=r"(y) : "f"(hi), "f"(lo)); return y; }
template <int N> __device__ __forceinline__ void fence_regs(float (&d)[N]) {
#pragma unroll
    for (int i = 0; i < N; i++) asm volatile("" : "+f"(d[i])::"memory");
}
template <int N> __device__ __forceinline__ void fence_regs(uint32_t (&d)[N]) {
#pragma unroll
    for (int i = 0; i < N; i++) asm volatile("" : "+r"(d[i])::"memory");
}
template <int N> __device__ __forceinline__ void undef_regs(float (&d)[N]) {
#pragma unroll
    for (int i = 0; i < N; i++) asm volatile("" : "=f"(d[i]));
}
__device__ __forceinline__ void mbar_init(uint32_t bar, uint32_t cnt) { asm volatile("mbarrier.init.shared::cta.b64 [%0], %1;" ::"r"(bar), "r"(cnt) : "memory"); }
__device__ __forceinline__ void mbar_expect_tx(uint32_t bar, uint32_t bytes) { asm volatile("mbarrier.arrive.expect_tx.shared::cta.b64 _, [%0], %1;" ::"r"(bar), "r"(bytes) : "memory"); }
__device__ __forceinline__ void mbar_arrive(uint32_t bar) { asm volatile("mbarrier.arrive.shared::cta.b64 _, [%0];" ::"r"(bar) : "memory"); }
__device__ __forceinline__ void mbar_arrive_cluster(uint32_t bar, uint32_t cta) {
    asm volatile("{\n.reg .b32 ra;\nmapa.shared::cluster.u32 ra, %0, %1;\nmbarrier.arrive.shared::cluster.b64 _, [ra];\n}" ::"r"(bar), "r"(cta) : "memory");
}
__device__ __forceinline__ void mbar_wait(uint32_t bar, uint32_t parity) {
    asm volatile(
        "{\n.reg .pred p;\n.reg .u32 n;\n"
        "mbarrier.try_wait.parity.shared::cta.b64 p, [%0], %1;\n"
        "@p bra.uni LAB_DONE;\n"
        "mov.u32 n, 0;\n"
        "LAB_WAIT:\n"
        "mbarrier.try_wait.parity.shared::cta.b64 p, [%0], %1, 1000;\n"
        "@p bra.uni LAB_DONE;\n"
        "add.u32 n, n, 1;\n"
        "setp.ge.u32 p, n, 0x400000;\n"
        "@p trap;\n"
        "bra.uni LAB_WAIT;\n"
        "LAB_DONE:\n}" ::"r"(bar), "r"(parity) : "memory");
}
__device__ __forceinline__ void flag_wait(const uint32_t* p, uint32_t target) {
    asm volatile(
        "{\n.reg .pred p;\n.reg .u32 n;\n.reg .s32 v;\n"
        "mov.u32 n, 0;\n"
        "LAB_WAIT:\n"
        "ld.acquire.gpu.global.s32 v, [%0];\n"
        "sub.s32 v, v, %1;\n"
        "setp.ge.s32 p, v, 0;\n"
        "@p bra.uni LAB_DONE;\n"
        "add.u32 n, n, 1;\n"
        "setp.ge.u32 p, n, 0x800000;\n"
        "@p trap;\n"
        "bra.uni LAB_WAIT;\n"
        "LAB_DONE:\n}" ::"l"(p), "r"(target) : "memory");
}
__device__ __forceinline__ uint32_t flag_wait_bits(const uint32_t* p, uint32_t base, uint32_t mask) {
    uint32_t v;
    asm volatile(
        "{\n.reg .pred p;\n.reg .u32 n, t;\n"
        "mov.u32 n, 0;\n"
        "LAB_WAIT:\n"
        "ld.acquire.gpu.global.u32 %0, [%1];\n"
        "sub.u32 %0, %0, %2;\n"
        "and.b32 t, %0, %3;\n"
        "setp.ne.u32 p, t, 0;\n"
        "@p bra.uni LAB_DONE;\n"
        "add.u32 n, n, 1;\n"
        "setp.ge.u32 p, n, 0x800000;\n"
        "@p trap;\n"
        "bra.uni LAB_WAIT;\n"
        "LAB_DONE:\n}" : "=&r"(v) : "l"(p), "r"(base), "r"(mask) : "memory");
    return v;
}
__device__ __forceinline__ void flag_add(uint32_t* p) { asm volatile("red.release.gpu.global.add.u32 [%0], 1;" ::"l"(p) : "memory"); }
__device__ __forceinline__ void flag_addv(uint32_t* p, uint32_t v) { asm volatile("red.release.gpu.global.add.u32 [%0], %1;" ::"l"(p), "r"(v) : "memory"); }
__device__ __forceinline__ void fence_async_global() { asm volatile("fence.proxy.async.global;" ::: "memory"); }
__device__ __forceinline__ void fence_async_shared() { asm volatile("fence.proxy.async.shared::cta;" ::: "memory"); }
__device__ __forceinline__ bool elect_one() {
    uint32_t p;
    asm volatile("{\n.reg .pred p;\nelect.sync _|p, 0xffffffff;\nselp.u32 %0, 1, 0, p;\n}" : "=r"(p));
    return p != 0;
}
__device__ __forceinline__ uint32_t mbar_test(uint32_t bar, uint32_t parity) {
    uint32_t p;
    asm volatile("{\n.reg .pred p;\nmbarrier.test_wait.parity.shared::cta.b64 p, [%1], %2;\nselp.u32 %0, 1, 0, p;\n}" : "=r"(p) : "r"(bar), "r"(parity) : "memory");
    return p;
}
__device__ __forceinline__ void mbar_wait_unless(uint32_t done, uint32_t bar, uint32_t parity) {
    asm volatile(
        "{\n.reg .pred p;\n.reg .u32 n;\n"
        "setp.ne.u32 p, %2, 0;\n"
        "@p bra.uni LAB_DONE;\n"
        "mov.u32 n, 0;\n"
        "LAB_WAIT:\n"
        "mbarrier.try_wait.parity.shared::cta.b64 p, [%0], %1, 1000;\n"
        "@p bra.uni LAB_DONE;\n"
        "add.u32 n, n, 1;\n"
        "setp.ge.u32 p, n, 0x400000;\n"
        "@p trap;\n"
        "bra.uni LAB_WAIT;\n"
        "LAB_DONE:\n}" ::"r"(bar), "r"(parity), "r"(done) : "memory");
}
__device__ __forceinline__ void bulk_s2g(void* dst, uint32_t src, uint32_t bytes) {
    asm volatile("cp.async.bulk.global.shared::cta.bulk_group [%0], [%1], %2;" ::"l"(dst), "r"(src), "r"(bytes) : "memory");
}
__device__ __forceinline__ void bulk_s2c(uint32_t addr, uint32_t bytes, uint32_t bar, uint32_t cta) {
    asm volatile("{\n.reg .b32 d, b;\nmapa.shared::cluster.u32 d, %0, %3;\nmapa.shared::cluster.u32 b, %2, %3;\n"
                 "cp.async.bulk.shared::cluster.shared::cta.mbarrier::complete_tx::bytes [d], [%0], %1, [b];\n}"
                 ::"r"(addr), "r"(bytes), "r"(bar), "r"(cta) : "memory");
}
__device__ __forceinline__ void sts32(uint32_t a, uint32_t v) { asm volatile("st.shared.u32 [%0], %1;" ::"r"(a), "r"(v) : "memory"); }
__device__ __forceinline__ void sts128(uint32_t a, uint32_t x, uint32_t y, uint32_t z, uint32_t w) { asm volatile("st.shared.v4.u32 [%0], {%1, %2, %3, %4};" ::"r"(a), "r"(x), "r"(y), "r"(z), "r"(w) : "memory"); }
__device__ __forceinline__ void stsm4(uint32_t a, uint32_t r0, uint32_t r1, uint32_t r2, uint32_t r3) {
    asm volatile("stmatrix.sync.aligned.m8n8.x4.shared.b16 [%0], {%1, %2, %3, %4};" ::"r"(a), "r"(r0), "r"(r1), "r"(r2), "r"(r3) : "memory");
}
__device__ __forceinline__ uint32_t lds32(uint32_t a) { uint32_t v; asm volatile("ld.shared.u32 %0, [%1];" : "=r"(v) : "r"(a) : "memory"); return v; }
__device__ __forceinline__ void tma_2d(uint32_t dst, const CUtensorMap* tm, int c0, int c1, uint32_t bar) {
    asm volatile("cp.async.bulk.tensor.2d.shared::cluster.global.mbarrier::complete_tx::bytes [%0], [%1, {%3, %4}], [%2];"
                 ::"r"(dst), "l"(tm), "r"(bar), "r"(c0), "r"(c1) : "memory");
}
__device__ __forceinline__ void tma_2d_mc(uint32_t dst, const CUtensorMap* tm, int c0, int c1, uint32_t bar) {
    asm volatile("cp.async.bulk.tensor.2d.shared::cluster.global.mbarrier::complete_tx::bytes.multicast::cluster [%0], [%1, {%3, %4}], [%2], %5;"
                 ::"r"(dst), "l"(tm), "r"(bar), "r"(c0), "r"(c1), "h"((uint16_t)3) : "memory");
}
__device__ __forceinline__ void tma_3d_mc(uint32_t dst, const CUtensorMap* tm, int c1, int c2, uint32_t bar) {
    asm volatile("cp.async.bulk.tensor.3d.shared::cluster.global.mbarrier::complete_tx::bytes.multicast::cluster [%0], [%1, {0, %3, %4}], [%2], %5;"
                 ::"r"(dst), "l"(tm), "r"(bar), "r"(c1), "r"(c2), "h"((uint16_t)3) : "memory");
}
__device__ __forceinline__ void bulk_g2s(uint32_t dst, const void* src, uint32_t bytes, uint32_t bar) {
    asm volatile("cp.async.bulk.shared::cluster.global.mbarrier::complete_tx::bytes [%0], [%1], %2, [%3];"
                 ::"r"(dst), "l"(src), "r"(bytes), "r"(bar) : "memory");
}
__device__ __forceinline__ void bulk_g2s_mc(uint32_t dst, const void* src, uint32_t bytes, uint32_t bar) {
    asm volatile("cp.async.bulk.shared::cluster.global.mbarrier::complete_tx::bytes.multicast::cluster [%0], [%1], %2, [%3], %4;"
                 ::"r"(dst), "l"(src), "r"(bytes), "r"(bar), "h"((uint16_t)3) : "memory");
}
__device__ __forceinline__ void mma_16816(float* d, uint32_t a0, uint32_t a1, uint32_t a2, uint32_t a3, uint32_t b0, uint32_t b1) {
    asm volatile("mma.sync.aligned.m16n8k16.row.col.f32.bf16.bf16.f32 {%0,%1,%2,%3}, {%4,%5,%6,%7}, {%8,%9}, {%0,%1,%2,%3};"
                 : "+f"(d[0]), "+f"(d[1]), "+f"(d[2]), "+f"(d[3]) : "r"(a0), "r"(a1), "r"(a2), "r"(a3), "r"(b0), "r"(b1));
}
__device__ __forceinline__ uint32_t movm_t(uint32_t a) { uint32_t d; asm volatile("movmatrix.sync.aligned.m8n8.trans.b16 %0, %1;" : "=r"(d) : "r"(a)); return d; }
__device__ __forceinline__ uint32_t ldg32(const uint8_t* p) { uint32_t v; asm volatile("ld.global.u32 %0, [%1];" : "=r"(v) : "l"(p) : "memory"); return v; }
__device__ __forceinline__ void stg32(uint8_t* p, uint32_t v) { asm volatile("st.global.u32 [%0], %1;" ::"l"(p), "r"(v) : "memory"); }
#define PROF(i) do {} while (0)
#define TRACE() do {} while (0)
#define PROFX(w, i) do {} while (0)

struct Ring {
    uint32_t slot;
    uint32_t phase;
    __device__ __forceinline__ void next() { if (++slot == NSTAGE) { slot = 0; phase ^= 1; } }
};

__device__ __forceinline__ void load_q(uint32_t (&q)[8], uint32_t qa, int lane) {
    q[0] = lds32(qa + lane * 4);       q[1] = lds32(qa + lane * 4 + 256);
    q[2] = lds32(qa + lane * 4 + 128); q[3] = lds32(qa + lane * 4 + 384);
    const uint32_t t0 = lds32(qa + 512 + (lane & ~3)), t1 = lds32(qa + 544 + (lane & ~3));
    q[4] = (lane & 3) == 2 ? t0 : 0u;  q[5] = (lane & 3) == 2 ? t1 : 0u;
}

__device__ __forceinline__ bool norm_o(uint32_t (&w)[6], const float (&o)[12], int lane, uint32_t gaddr) {
    const float l0 = __shfl_sync(0xffffffffu, o[8], (lane & ~3) | 1);
    const float l1 = __shfl_sync(0xffffffffu, o[10], (lane & ~3) | 1);
    const float i0 = rcp_fast(l0) * __uint_as_float(lds32(gaddr)), i1 = rcp_fast(l1) * __uint_as_float(lds32(gaddr + 32));
    uint32_t big = 0;
#pragma unroll
    for (int b = 0; b < 3; b++) {
        w[2 * b] = pack(o[4 * b] * i0, o[4 * b + 1] * i0);
        w[2 * b + 1] = pack(o[4 * b + 2] * i1, o[4 * b + 3] * i1);
        if (b == 2 && (lane & 3) != 0) w[4] = w[5] = 0u;
        big |= ((w[2 * b] & 0x7F807F80u) + 0x00800080u) | ((w[2 * b + 1] & 0x7F807F80u) + 0x00800080u);
    }
    const bool ok = fminf(l0, l1) >= 0x1p-30f && l0 <= 0x1p60f && l1 <= 0x1p60f && (big & 0x80008000u) == 0;
    return !__all_sync(0xffffffffu, ok);
}

__device__ __forceinline__ void attn_true_max(float (&o)[12], const uint32_t (&q)[8], const uint8_t* kv) {
    float m0 = -INFINITY, m1 = -INFINITY;
#pragma unroll
    for (int i = 0; i < 12; i++) o[i] = 0.f;
#pragma unroll 1
    for (int kb = 0; kb < SEQ / 16; kb++) {
        uint32_t t[2][5];
#pragma unroll
        for (int g = 0; g < 2; g++)
#pragma unroll
            for (int ch = 0; ch < 5; ch++) t[g][ch] = ldg32(kv + (kb * 2 + g) * 640 + ch * 128);
        float s[2][4];
#pragma unroll
        for (int g = 0; g < 2; g++) {
            s[g][0] = s[g][1] = s[g][2] = s[g][3] = 0.f;
            mma_16816(s[g], q[0], q[1], q[2], q[3], t[g][0], t[g][1]);
            mma_16816(s[g], q[4], q[5], 0u, 0u, t[g][4], 0u);
        }
        float x0 = fmaxf(fmaxf(s[0][0], s[0][1]), fmaxf(s[1][0], s[1][1]));
        float x1 = fmaxf(fmaxf(s[0][2], s[0][3]), fmaxf(s[1][2], s[1][3]));
        x0 = fmaxf(x0, __shfl_xor_sync(0xffffffffu, x0, 1)); x0 = fmaxf(x0, __shfl_xor_sync(0xffffffffu, x0, 2));
        x1 = fmaxf(x1, __shfl_xor_sync(0xffffffffu, x1, 1)); x1 = fmaxf(x1, __shfl_xor_sync(0xffffffffu, x1, 2));
        const float n0 = fmaxf(m0, x0), n1 = fmaxf(m1, x1);
        const float u0 = (n0 == -INFINITY) ? 0.f : n0, u1 = (n1 == -INFINITY) ? 0.f : n1;
        const float c0 = ex2(m0 - u0), c1 = ex2(m1 - u1);
        m0 = n0; m1 = n1;
#pragma unroll
        for (int b = 0; b < 3; b++) { o[4 * b] *= c0; o[4 * b + 1] *= c0; o[4 * b + 2] *= c1; o[4 * b + 3] *= c1; }
        const uint32_t a0 = pack(ex2(s[0][0] - u0), ex2(s[0][1] - u0)), a1 = pack(ex2(s[0][2] - u1), ex2(s[0][3] - u1));
        const uint32_t a2 = pack(ex2(s[1][0] - u0), ex2(s[1][1] - u0)), a3 = pack(ex2(s[1][2] - u1), ex2(s[1][3] - u1));
#pragma unroll
        for (int b = 0; b < 3; b++) mma_16816(&o[4 * b], a0, a1, a2, a3, movm_t(t[0][2 + b]), movm_t(t[1][2 + b]));
    }
}

__device__ __forceinline__ float geglu2(float g, float u) {
    const float p = fmaf(g * g, 0.044715f * 0.7978845608028654f, 0.7978845608028654f);
    const float th = tanh_fast(g * p);
    const float y = g * u;
    return fmaf(y, th, y);
}

struct Attn {
    float s[32];
    float o[12];
    uint32_t p[16];
    uint32_t q[8];
};

__global__ void __cluster_dims__(2, 1, 1) __launch_bounds__(384, 1)
fused_kernel(__nv_bfloat16* __restrict__ out, const __nv_bfloat16* __restrict__ x, const __nv_bfloat16* __restrict__ gate_w,
             const uint8_t* __restrict__ wqkv, const uint8_t* __restrict__ wgt, const uint8_t* __restrict__ wu,
             const __grid_constant__ CUtensorMap tm_x, const __grid_constant__ CUtensorMap tm_qkv,
             const __grid_constant__ CUtensorMap tm_qkv8,
             const __grid_constant__ CUtensorMap tm_wg, const __grid_constant__ CUtensorMap tm_wu,
             const __grid_constant__ CUtensorMap tm_wd, const __grid_constant__ CUtensorMap tm_wo,
             const __grid_constant__ CUtensorMap tm_wd16, const __grid_constant__ CUtensorMap tm_wo16) {
    extern __shared__ uint8_t smem_raw[];
    const uint32_t sb = __shfl_sync(0xffffffffu, ((uint32_t)__cvta_generic_to_shared(smem_raw) + 1023) & ~1023u, 0);
    const uint32_t bars = sb + OFF_BAR;
    const uint32_t bar_full = bars, bar_empty = bars + 64;
    const uint32_t bar_ev = bars + 128;
    const uint32_t bar_rdy = bars + 256;
    const uint32_t bar_ep = bars + 320, bar_gate = bars + 328;
    const uint32_t bar_st = bars + 336;
    const uint32_t bar_late = bars + 408;
    const uint32_t bar_px = bars + 416;
    const uint32_t bar_free = bars + 424;
    const uint32_t s_epoch = bars + 448, s_zero = bars + 452, s_order = bars + 464, s_gate = bars + 512;

    const int cta = blockIdx.x;
    const int rank = cta & 1;
    const int j = (cta >> 1) & 7;
    const int m = (cta >> 4) * 2 + rank;
    const int hf = j >> 2, nt = j & 3;
    const int warp = __shfl_sync(0xffffffffu, threadIdx.x >> 5, 0);
    const int lane = threadIdx.x & 31;
    const int wg = warp >> 2;

    auto prefetch_stages = [&](int n) {
        const int t = threadIdx.x;
        const int row = (t >> 3) * 16 + m, sel = t & 7;
        const uint8_t* p = sel < 6 ? wqkv + (size_t)row * (3 * DM * 2) + (sel >> 1) * (DM * 2) + j * 128 + (sel & 1) * 128
                                   : (sel == 7 ? wu : wgt) + (size_t)row * (FF * 2) + (j * 576 + 512) * 2;
        if (t < n * 16) asm volatile("prefetch.global.L2 [%0];" ::"l"(p));
        p = (const uint8_t*)x + (size_t)(m * 128 + j * 16 + (t & 15)) * (DM * 2) + (t >> 4) * 128;
        if (t < n * 8) asm volatile("prefetch.global.L2 [%0];" ::"l"(p));
    };
    if (elect_one()) {
        const uint32_t lo = warp < 2 ? 2 : (warp >= 8 && warp <= 10) ? 1 : 4, hi = warp == 10 ? 4 : lo;
        mbar_init(bars + warp * 32, lo); mbar_init(bars + warp * 32 + 8, lo);
        mbar_init(bars + warp * 32 + 16, hi); mbar_init(bars + warp * 32 + 24, hi);
        if (warp < 4) mbar_init(bar_late + warp * 8, 1);
        sts32(s_zero, 0u); sts32(s_zero + 4, 0u);
        asm volatile("fence.mbarrier_init.release.cluster;" ::: "memory");
    }
    asm volatile("barrier.cluster.arrive.relaxed.aligned;" ::: "memory");
    if (cta < NCTA && wg < 2) prefetch_stages(4);
    asm volatile("barrier.cluster.wait.acquire.aligned;" ::: "memory");

    if (wg == 2) {
        asm volatile("setmaxnreg.dec.sync.aligned.u32 24;");
        if (cta >= NCTA) {
            if (warp == 8 && elect_one()) {
                const uint32_t ep = g_flags[FL_E + cta * 32] + 1;
                g_flags[FL_E + cta * 32] = ep;
                mbar_wait(bar_ev + 2 * 8, 0);
                mbar_wait(bar_ev + 10 * 8, 0);
                flag_add(&g_flags[FL_G + (cta - NCTA) * 32]);
#pragma unroll 1
                for (int i = 0; i < 2; i++) {
                    const int jx = (cta - NCTA) * 2 + i;
                    flag_wait(&g_flags[FL_KV + jx * 32 + 1], ep * 32);
                    fence_async_global();
                    mbar_expect_tx(bar_rdy + i * 8, 20480 + 16 * 4608);
#pragma unroll 1
                    for (int p = 0; p < 8; p++) bulk_g2s(sb + 40960 + (i * 8 + p) * 9216, g_q3 + (p * 16 + jx * 2) * 4608, 9216, bar_rdy + i * 8);
                    bulk_g2s(sb + i * 20480, g_kv + (size_t)(jx * 4 + 3) * HEAD_BYTES + 28 * 5120, 20480, bar_rdy + i * 8);
                }
#pragma unroll 1
                for (int i = 0; i < 2; i++) {
                    mbar_wait(bar_ev + i * 8, 0);
                    mbar_wait(bar_ev + (8 + i) * 8, 0);
                    flag_add(&g_flags[FL_KV + ((cta - NCTA) * 2 + i) * 32 + 2]);
                }
            }
        } else if (warp == 8) {
            if (elect_one()) {
                Ring r{0, 1};
                const int row0 = m * 128;
                const CUtensorMap* tw = rank ? &tm_wu : &tm_wg;
                PROFX(0, 40); PROFX(1, 40);
#pragma unroll 1
                for (int kk = 0; kk < 18; kk++) {
                    if (kk == 1) { PROFX(0, 41); PROFX(1, 41); }
                    if (kk == 6) { PROFX(0, 42); PROFX(1, 42); }
                    const uint32_t st = sb + r.slot * SLOT, fb = bar_full + r.slot * 8;
                    mbar_wait(bar_empty + r.slot * 8, r.phase);
                    mbar_arrive(fb);
                    mbar_expect_tx(fb, 8192 + 12288 + 8192 + 1536);
                    tma_2d(st + OFF_AX, &tm_x, kk * 32, row0, fb);
#pragma unroll
                    for (int b = 0; b < 3; b++) tma_2d_mc(st + 8192 + b * 4096 + rank * 2048, &tm_qkv, b * 576 + j * 72, kk * 32 + rank * 16, fb);
                    tma_2d_mc(st + rank * 4096, tw, j * 576 + 512, kk * 32, fb);
#pragma unroll
                    for (int b = 0; b < 3; b++) tma_2d_mc(st + OFF_TL + b * 512 + rank * 256, &tm_qkv8, b * 576 + j * 72 + 64, kk * 32 + rank * 16, fb);
                    r.next();
                }
#pragma unroll 1
                for (int t = 0; t < 4; t++)
#pragma unroll 1
                    for (int kk = 0; kk < 18; kk++) {
                        const uint32_t st = sb + r.slot * SLOT, fb = bar_full + r.slot * 8;
                        mbar_wait(bar_empty + r.slot * 8, r.phase);
                        if (t == 0 && kk < 2) mbar_arrive(fb);
                        mbar_expect_tx(fb, 8192 + 16384);
                        tma_2d_mc(st + rank * 8192, tw, j * 576 + t * 128, kk * 32, fb);
                        tma_2d_mc(st + rank * 8192 + 4096, tw, j * 576 + t * 128 + 64, kk * 32, fb);
                        tma_2d(st + OFF_AX, &tm_x, kk * 32, row0, fb);
                        r.next();
                    }
                const uint8_t* a2 = g_a2 + (size_t)m * A2_TILE;
                mbar_wait(bar_rdy + 4 * 8, 0);
#pragma unroll 1
                for (int n = 0; n < 48; n++) {
                    const int u = n >> 2, jj = n & 3;
                    const uint32_t st = sb + r.slot * SLOT, fb = bar_full + r.slot * 8;
                    mbar_wait(bar_empty + r.slot * 8, r.phase);
                    mbar_expect_tx(fb, 12288 + 18432);
                    const int ks = (hf * 4 + jj) * 36 + u * 3;
#pragma unroll
                    for (int b = 0; b < 2; b++) tma_2d_mc(st + b * 6144 + rank * 3072, &tm_wd, nt * 128 + b * 64, ks * 16 + rank * 24, fb);
                    tma_3d_mc(st + 12288 + rank * 3072, &tm_wd16, ks * 16 + rank * 24, 64 + nt * 2, fb);
                    if (jj == 0) { mbar_wait(bar_rdy + ((3 * u + 2) >> 3) * 8, 0); fence_async_global(); }
                    bulk_g2s(st + OFF_A2, a2 + ks * 4096, 12288, fb);
                    r.next();
                }
#pragma unroll 1
                for (int n = 0; n < 4; n++) {
                    const uint32_t st = sb + r.slot * SLOT, fb = bar_full + r.slot * 8;
                    mbar_wait(bar_empty + r.slot * 8, r.phase);
                    mbar_expect_tx(fb, 12288 + 18432);
                    const int pr = hf * 2 + (n & 1), head = (pr * 2 + rank) * 4 + (n >> 1);
#pragma unroll
                    for (int b = 0; b < 2; b++) tma_2d_mc(st + b * 6144 + rank * 3072, &tm_wo, nt * 128 + b * 64, head * 18, fb);
                    tma_3d_mc(st + 12288 + rank * 3072, &tm_wo16, head * 18, 64 + nt * 2, fb);
                    if (n == 0) { mbar_wait(bar_rdy + 5 * 8, 0); fence_async_global(); }
                    bulk_g2s(st + OFF_A2, a2 + (288 + ((n >> 1) * 4 + pr) * 3) * 4096, 12288, fb);
                    r.next();
                }
                mbar_expect_tx(bar_late, 4 * 12288);
#pragma unroll 1
                for (int n = 0; n < 8; n++) {
                    const uint32_t st = sb + r.slot * SLOT, fb = bar_full + r.slot * 8;
                    mbar_wait(bar_empty + r.slot * 8, r.phase);
                    if (n >= 2) mbar_arrive(fb);
                    if (n < 4) mbar_expect_tx(fb, 12288 + 12288);
                    const int head = ((n & 3) * 2 + rank) * 4 + 2 + (n >> 2);
                    tma_2d_mc(st + rank * 3072, &tm_wo, nt * 128 + hf * 64, head * 18, n < 4 ? fb : bar_late);
                    tma_3d_mc(st + 6144 + rank * 3072, &tm_wo16, head * 18, 64 + nt * 2, n < 4 ? fb : bar_late);
                    if (n < 4) bulk_g2s(st + OFF_A2, a2 + (288 + (8 + n) * 3) * 4096, 12288, fb);
                    r.next();
                }
                mbar_wait(bar_ep, 0);
                const uint32_t base = (lds32(s_epoch) - 1) * 0x04040404u;
                uint32_t todo = 0x04040404u, k = 2;
#pragma unroll 1
                while (todo) {
                    const uint32_t got = flag_wait_bits(&g_flags[FL_M + m * 64 + FM_LATE], base, todo) & todo;
                    fence_async_global();
#pragma unroll 1
                    for (int pr = 0; pr < 4; pr++)
                        if ((got >> (pr * 8)) & 4) {
                            sts32(s_order + k * 4, (2 + pr) * (SLOT >> 4));
                            mbar_expect_tx(bar_full + k * 8, 12288);
                            bulk_g2s(sb + k * SLOT + OFF_A2, a2 + (288 + (12 + pr) * 3) * 4096, 12288, bar_full + k * 8);
                            k++;
                        }
                    todo &= ~got;
                }
                PROFX(0, 50); PROFX(1, 50);
            }
        } else if (warp == 9) {
            if (elect_one()) {
                const uint32_t ep = g_flags[FL_E + cta * 32] + 1;
                g_flags[FL_E + cta * 32] = ep;
                sts32(s_epoch, ep);
                mbar_arrive(bar_ep);
                Ring r{0, 1};
                const uint8_t* kv = g_kv + (size_t)(j * 4) * HEAD_BYTES + rank * 2560;
                const int rot = (cta >> 4) * 4;
                uint32_t have = flag_wait_bits(&g_flags[FL_KV + j * 32], (ep - 1) * 0x44444444u, 4u << rot);
                fence_async_global();
#pragma unroll 1
                for (int it = 4; it < 124; it++) {
                    const uint32_t fb = bar_full + r.slot * 8;
                    if (it < 32 && !((have >> ((it + rot) & 28)) & 4)) {
                        have = flag_wait_bits(&g_flags[FL_KV + j * 32], (ep - 1) * 0x44444444u, 4u << ((it + rot) & 28));
                        fence_async_global();
                    }
                    if (it == 4) { PROFX(0, 37); PROFX(1, 37); }
                    if (it == 24) { flag_wait(&g_flags[FL_KV + j * 32 + 1], ep * 32); fence_async_global(); }
                    mbar_wait(bar_empty + r.slot * 8, r.phase);
                    mbar_expect_tx(fb, 5120);
                    bulk_g2s_mc(sb + r.slot * SLOT + OFF_KV + rank * 2560, kv + (it < 32 ? (it + rot) & 31 : it) * 5120, 2560, fb);
                    r.next();
                }
                flag_wait(&g_flags[FL_KV + j * 32 + 2], ep);
                mbar_arrive(bar_px);
                uint32_t* fr = &g_flags[FL_M + m * 64 + FM_R];
                mbar_wait(bar_ev + 6 * 8, 0);
                mbar_wait(bar_ev + 14 * 8, 0);
                PROFX(0, 51); PROFX(1, 51);
                flag_add(fr + j);
                PROFX(0, 52); PROFX(1, 52);
                flag_wait(fr + (j ^ 4), ep);
                PROFX(0, 53); PROFX(1, 53);
                mbar_arrive(bar_rdy + 6 * 8);
            }
        } else {
            const int w = warp - 10;
            if (elect_one()) {
                const uint32_t mine = 2 + rank * 2 + w, other = 2 + (rank ^ 1) * 2 + w;
                mbar_wait(bar_st + w * 8, 0);
                PROFX(w, 32);
                bulk_s2g(g_kv + (size_t)(j * 4) * HEAD_BYTES + (m * 16 + w * 8) * 640, sb + mine * SLOT + OFF_KV, 5120);
                asm volatile("cp.async.bulk.commit_group;" ::: "memory");
                mbar_arrive(bar_full + mine * 8);
                mbar_expect_tx(bar_full + other * 8, 5120);
#pragma unroll 1
                for (int i = 0; i < 2; i++) {
                    if (i == rank) {
                        mbar_wait(bar_empty + mine * 8, 0);
                        bulk_s2c(sb + mine * SLOT + OFF_KV, 5120, bar_full + mine * 8, rank ^ 1);
                    } else {
                        asm volatile("cp.async.bulk.wait_group 0;" ::: "memory");
                        flag_addv(&g_flags[FL_KV + j * 32], 1u << ((cta >> 4) * 4));
                    }
                }
                PROFX(w, 34);
                mbar_wait(bar_st + (2 + w) * 8, 0);
                bulk_s2g(g_q3 + cta * 4608 + w * 2304, sb + OFF_Q + 3 * 4608 + w * 2304, 2304);
#pragma unroll 1
                for (int h = 1; h < 4; h++) {
                    __nanosleep(500);
                    bulk_s2g(g_kv + (size_t)(j * 4 + h) * HEAD_BYTES + (m * 16 + w * 8) * 640, sb + (w * 3 + h - 1) * SLOT + OFF_GAP, 5120);
                    asm volatile("cp.async.bulk.commit_group;\ncp.async.bulk.wait_group 0;" ::: "memory");
                }
                mbar_arrive(bar_free + w * 8);
                flag_add(&g_flags[FL_KV + j * 32 + 1]);
                PROFX(w, 35);
            }
            __syncwarp();
            uint32_t* fm = &g_flags[FL_M + m * 64];
            mbar_wait(bar_ep, 0);
            const uint32_t ep = lds32(s_epoch);
            if (w == 1) {
                flag_wait(&g_flags[FL_G + (m >> 2) * 32], ep);
                const uint4 gv = __ldcg((const uint4*)(g_gate + m * 128) + lane);
                sts128(s_gate + lane * 16, gv.x, gv.y, gv.z, gv.w);
                __syncwarp();
                if (lane == 0) mbar_arrive(bar_gate);
            }
            if (elect_one()) {
#pragma unroll 1
                for (int i = 0; i < 6; i++) {
                    const int e = i == 0 ? 4 : i == 5 ? 5 : i - 1;
                    mbar_wait(bar_ev + (w * 8 + e) * 8, 0);
                    if (e < 3) {
                        uint8_t* hp = g_a2 + (size_t)m * A2_TILE + (j * 36 + e * 8) * 4096 + w * 2048;
#pragma unroll 1
                        for (int k = 0; k < 8; k++) {
                            const int g = (k * 11) >> 5;
                            bulk_s2g(hp + k * 4096, sb + (w * 3 + g) * SLOT + OFF_GAP + (k - g * 3) * 2048, 2048);
                        }
                        asm volatile("cp.async.bulk.commit_group;\ncp.async.bulk.wait_group 0;" ::: "memory");
                    }
                    uint32_t* fl = fm + FM_H + (e == 5 ? 5 : hf * 8 + e);
                    flag_add(fl);
                    if (w == 0) { flag_wait(fl, ep * (e == 5 ? 16 : 8)); mbar_arrive(bar_rdy + e * 8); }
                }
                mbar_wait(bar_ev + (w * 8 + 7) * 8, 0);
                PROFX(w, 48);
                flag_addv(fm + FM_LATE, 1u << ((j >> 1) * 8));
                PROFX(w, 49);
            }
        }
    } else {
        asm volatile("setmaxnreg.inc.sync.aligned.u32 240;");
        const int wq = warp & 3;
        const int c = lane & 3;
        const int tid = threadIdx.x & 127;
        const int grp = wg * 8 + wq * 2;
        const uint32_t sbd = (sb & 0x3FFFF) >> 4;
        uint32_t sd = sbd, pd = sbd, fb = bar_full, pb = bar_full, ph = 0;
#define STAGE_NEXT do { pd = sd; sd = (sd == sbd + (NSTAGE - 1) * (SLOT >> 4)) ? sbd : sd + (SLOT >> 4);           \
                        pb = fb; fb += 8; if (fb == bar_full + NSTAGE * 8) { fb = bar_full; ph ^= 1; } } while (0)
        auto release = [&]() { if (tid < 2) mbar_arrive_cluster(pb + 64, tid); };
        auto signal = [&](int e) { __syncwarp(); if (lane == 0) mbar_arrive(bar_ev + (wg * 8 + e) * 8); };
        if (cta >= NCTA) {
            PROF(0);
            {
                float wv[72];
#pragma unroll
                for (int i = 0; i < 9; i++) {
                    const uint4 t = __ldg((const uint4*)gate_w + (lane & 7) + i * 8);
                    const uint32_t u[4] = {t.x, t.y, t.z, t.w};
#pragma unroll
                    for (int e = 0; e < 4; e++) { wv[8 * i + 2 * e] = __uint_as_float(u[e] << 16); wv[8 * i + 2 * e + 1] = __uint_as_float(u[e] & 0xffff0000u); }
                }
                __nanosleep(1500);
#pragma unroll 1
                for (int b = 0; b < 8; b++) {
                    const int row = (cta - NCTA) * 512 + warp * 64 + b * 8 + (lane >> 3);
                    uint4 xa[2][9];
#pragma unroll
                    for (int r = 0; r < 2; r++)
#pragma unroll
                        for (int i = 0; i < 9; i++) xa[r][i] = __ldg((const uint4*)(x + (size_t)(row + r * 4) * DM) + (lane & 7) + i * 8);
#pragma unroll
                    for (int r = 0; r < 2; r++) {
                        float z = 0.f, y = 0.f;
#pragma unroll
                        for (int i = 0; i < 9; i++) {
                            const uint32_t u[4] = {xa[r][i].x, xa[r][i].y, xa[r][i].z, xa[r][i].w};
#pragma unroll
                            for (int e = 0; e < 4; e++) {
                                z = fmaf(__uint_as_float(u[e] << 16), wv[8 * i + 2 * e], z);
                                y = fmaf(__uint_as_float(u[e] & 0xffff0000u), wv[8 * i + 2 * e + 1], y);
                            }
                        }
                        z += y;
#pragma unroll
                        for (int d = 1; d < 8; d <<= 1) z += __shfl_xor_sync(0xffffffffu, z, d);
                        if ((lane & 7) == 0) g_gate[row + r * 4] = rcp_fast(1.f + ex2(-1.4426950408889634f * z));
                    }
                }
                signal(2);
                PROF(2);
            }
            float s0[64], s1[64], o[12];
            uint32_t p0[32], p1[32], q[8];
            q[6] = lds32(s_zero); q[7] = lds32(s_zero + 4);
#pragma unroll
            for (int i = 0; i < 12; i++) o[i] = 0.f;
            auto store_px = [&](int u) {
                const int src = ((u & 15) >> 1) * 16 + ((cta - NCTA) * 2 + (u >> 4)) * 2 + (u & 1);
                float4* dst = g_px + (size_t)(src * 2 + wg) * 3 * 128 + tid;
#pragma unroll
                for (int i = 0; i < 3; i++) __stcg(dst + i * 128, make_float4(o[4 * i], o[4 * i + 1], o[4 * i + 2], o[4 * i + 3]));
            };
            mbar_wait(bar_rdy, 0);
            PROF(1);
            load_q(q, sb + 40960 + warp * 576, lane);
            fence_regs(q); fence_regs(o);
            wg_fence();
            wgmma_rs_n128_t0<HI_K>(s0, q[0], q[1], q[2], q[3], sbd + dlo(0, 128), 0);
            wgmma_rs_n128_t0<HI_K>(s0, q[4], q[5], q[6], q[7], sbd + dlo(512, 0), 1);
            wg_commit();
            wg_wait<0>();
            fence_regs(s0);
#pragma unroll 1
            for (int u = 0; u < 32; u++) {
                const uint32_t kb = sbd + (u >> 4) * 1280;
                wg_fence();
                wgmma_rs_n128_t0<HI_K>(s1, q[0], q[1], q[2], q[3], kb + dlo(10240, 128), 0);
                wgmma_rs_n128_t0<HI_K>(s1, q[4], q[5], q[6], q[7], kb + dlo(10240 + 512, 0), 1);
                wg_commit();
#pragma unroll
                for (int i = 0; i < 32; i++) p0[i] = pack(ex2(s0[2 * i]), ex2(s0[2 * i + 1]));
                fence_regs(p0);
                wg_wait<0>();
                fence_regs(o); fence_regs(s1); fence_regs(q);
                store_px(u > 0 ? u - 1 : 0);
                if (u == 16) signal(0);
                if (u == 15) mbar_wait(bar_rdy + 8, 0);
                const int un = u < 31 ? u + 1 : u;
                load_q(q, sb + 40960 + un * 4608 + warp * 576, lane);
                fence_regs(q);
                const uint32_t kn = sbd + (un >> 4) * 1280;
                wg_fence();
#pragma unroll
                for (int i = 0; i < 8; i++) wgmma_rs_n24_t1<HI_V>(o, p0[4 * i], p0[4 * i + 1], p0[4 * i + 2], p0[4 * i + 3], kb + dlo(256, 640) + 80 * i, i != 0);
                wgmma_rs_n128_t0<HI_K>(s0, q[0], q[1], q[2], q[3], kn + dlo(0, 128), 0);
                wgmma_rs_n128_t0<HI_K>(s0, q[4], q[5], q[6], q[7], kn + dlo(512, 0), 1);
                wg_commit();
#pragma unroll
                for (int i = 0; i < 32; i++) p1[i] = pack(ex2(s1[2 * i]), ex2(s1[2 * i + 1]));
                fence_regs(p1);
                wg_fence();
#pragma unroll
                for (int i = 0; i < 8; i++) wgmma_rs_n24_t1<HI_V>(o, p1[4 * i], p1[4 * i + 1], p1[4 * i + 2], p1[4 * i + 3], kb + dlo(10240 + 256, 640) + 80 * i, 1);
                wg_commit();
                wg_wait<1>();
                fence_regs(s0); fence_regs(p0);
            }
            wg_wait<0>();
            fence_regs(o);
            store_px(31);
            signal(1);
            PROF(20);
            return;
        }
        Attn at;
        PROF(0);

        uint8_t* a2w = g_a2 + (size_t)m * A2_TILE + grp * 256 + lane * 4;
        const uint32_t qa = sb + OFF_Q + warp * 576;
        float acc[128];
        {
            float qkv[96], tl[12], gu[64];
#pragma unroll 1
            for (int kk = 0; kk < 18 - DEFER; kk++) {
                mbar_wait(fb, ph);
                if (kk == 0) PROF(21);
                if (kk == 6) PROF(22);
                if (kk == 12) PROF(23);
                const uint32_t da = sd + wg * 256 + dlo(OFF_AX, 16), db = sd + dlo(0, 4096), dt = sd + dlo(OFF_TL, 128);
                wg_fence();
                wgmma_ss_n192_t1<HI_X, HI_W>(qkv, da, db + 512, kk != 0);
                wgmma_ss_n24_t1<HI_X, HI_T>(tl, da, dt, kk != 0);
                wgmma_ss_n128_t1<HI_X, HI_W>(gu, da, db, kk != 0);
                wgmma_ss_n192_t1<HI_X, HI_W>(qkv, da + 2, db + 512 + 128, 1);
                wgmma_ss_n24_t1<HI_X, HI_T>(tl, da + 2, dt + 16, 1);
                wgmma_ss_n128_t1<HI_X, HI_W>(gu, da + 2, db + 128, 1);
                wg_commit();
                wg_wait<1>();
                if (kk > 0) release();
                STAGE_NEXT;
            }
#pragma unroll
            for (int kk = 0; kk < DEFER; kk++) {
                mbar_wait(fb + kk * 8, ph);
                const uint32_t st = sd + kk * (SLOT >> 4);
                const uint32_t da = st + wg * 256 + dlo(OFF_AX, 16), db = st + dlo(0, 4096), dt = st + dlo(OFF_TL, 128);
                wg_fence();
                wgmma_ss_n192_t1<HI_X, HI_W>(qkv, da, db + 512, 1);
                wgmma_ss_n24_t1<HI_X, HI_T>(tl, da, dt, 1);
                wgmma_ss_n192_t1<HI_X, HI_W>(qkv, da + 2, db + 512 + 128, 1);
                wgmma_ss_n24_t1<HI_X, HI_T>(tl, da + 2, dt + 16, 1);
                wg_commit();
                if (kk == 0) { wg_wait<1>(); release(); }
            }
#pragma unroll
            for (int kk = 0; kk < DEFER; kk++) {
                const uint32_t st = sd + kk * (SLOT >> 4);
                const uint32_t da = st + wg * 256 + dlo(OFF_AX, 16), db = st + dlo(0, 4096);
                wgmma_ss_n128_t1<HI_X, HI_W>(gu, da, db, 1);
                wgmma_ss_n128_t1<HI_X, HI_W>(gu, da + 2, db + 128, 1);
            }
            wg_commit();
            wg_wait<1>();
            fence_regs(qkv); fence_regs(tl);
            PROF(1);
            constexpr float QS = 0.23570226039551584f * 1.4426950408889634f;
            uint32_t kp[9][2], vp[9][2];
#pragma unroll
            for (int i = 0; i < 9; i++) {
                const float* k4 = i < 8 ? &qkv[32 + 4 * i] : &tl[4];
                const float* v4 = i < 8 ? &qkv[64 + 4 * i] : &tl[8];
                kp[i][0] = pack(k4[0], k4[1]); kp[i][1] = pack(k4[2], k4[3]);
                vp[i][0] = pack(v4[0], v4[1]); vp[i][1] = pack(v4[2], v4[3]);
            }
            const int quad = lane & ~3;
            const uint32_t cst = c == 1 ? 0x3F80u : 0u;
            {
                const uint32_t a = sb + (2 + rank * 2 + wg) * SLOT + OFF_KV + wq * 1280 + lane * 4;
#pragma unroll
                for (int r = 0; r < 2; r++) {
                    const uint32_t kt = __shfl_sync(0xffffffffu, kp[2][r], quad);
                    sts32(a + r * 640, kp[0][r]);       sts32(a + r * 640 + 128, kp[1][r]);
                    sts32(a + r * 640 + 256, vp[0][r]); sts32(a + r * 640 + 384, vp[1][r]);
                    sts32(a + r * 640 + 512, c == 0 ? vp[2][r] : c == 2 ? kt : cst);
                }
                fence_async_shared();
                __syncwarp();
                if (lane == 0) mbar_arrive(bar_st + wg * 8);
            }
            PROF(2);
#pragma unroll
            for (int i = 0; i < 9; i++) {
                const float* q4 = i < 8 ? &qkv[4 * i] : &tl[0];
                const uint32_t q0 = pack(q4[0] * QS, q4[1] * QS), q1 = pack(q4[2] * QS, q4[3] * QS);
                if (i < 2) { at.q[2 * i] = q0; at.q[2 * i + 1] = q1; }
                else {
                    if (i == 2) {
                        const uint32_t t0 = __shfl_sync(0xffffffffu, q0, quad), t1 = __shfl_sync(0xffffffffu, q1, quad);
                        at.q[4] = c == 2 ? t0 : 0u; at.q[5] = c == 2 ? t1 : 0u;
                    }
                    const int lc = 8 * i + 2 * c;
                    const int hd = (lc * 3641) >> 16;
                    const int d = lc - hd * 18;
                    const bool last = (i & 1) == 0 && c == i / 2 - 1;
                    const uint32_t aq = qa + hd * 4608 + (last ? 512 + (lane >> 2) * 4 : (d >> 3) * 128 + (d & 7) * 2 + (lane >> 2) * 16);
                    if (i > 2 || c > 0) { sts32(aq, q0); sts32(aq + (last ? 32 : 256), q1); }
                }
            }
            mbar_wait(bar_st, 0);
            mbar_wait(bar_st + 8, 0);
#pragma unroll
            for (int i = 2; i < 9; i++) {
                const int lc = 8 * i + 2 * c;
                const int hd = (lc * 3641) >> 16;
                const int d = lc - hd * 18;
                const uint32_t ak = sb + (wg * 3 - 1 + hd) * SLOT + OFF_GAP + wq * 1280 + (lane >> 2) * 16;
                const uint32_t off = (d >> 3) * 128 + (d & 7) * 2;
                if ((i & 1) == 0 && c == i / 2 - 1) {
                    if (i > 2) { sts128(ak + 512, vp[i][0], 0x3F80u, kp[i][0], 0u); sts128(ak + 512 + 640, vp[i][1], 0x3F80u, kp[i][1], 0u); }
                } else {
                    sts32(ak + off, kp[i][0]); sts32(ak + off + 640, kp[i][1]); sts32(ak + off + 256, vp[i][0]); sts32(ak + off + 256 + 640, vp[i][1]);
                }
            }
            fence_async_shared();
            __syncwarp();
            if (lane == 0) mbar_arrive(bar_st + (2 + wg) * 8);
            PROF(39);
            wg_wait<0>();
            fence_regs(gu);
            if (tid < 2 * DEFER) mbar_arrive_cluster(fb + 64 + (tid >> 1) * 8, tid & 1);
#pragma unroll
            for (int kk = 0; kk < 2; kk++) {
                mbar_wait(bar_full + kk * 8, 1);
                const uint32_t st = sbd + kk * (SLOT >> 4);
                const uint32_t da = st + wg * 256 + dlo(OFF_AX, 16), db = st + dlo(0, 4096);
                wg_fence();
                wgmma_ss_n256_t1<HI_X, HI_W>(acc, da, db, kk);
                wgmma_ss_n256_t1<HI_X, HI_W>(acc, da + 2, db + 128, 1);
                wg_commit();
            }
            sd = sbd + 2 * (SLOT >> 4); fb = bar_full + 16; pb = bar_full; ph = 1;
            uint8_t* hp = a2w + (j * 36 + 32) * 4096;
#pragma unroll
            for (int i = 0; i < 16; i++)
                stg32(hp + (i >> 2) * 4096 + ((i >> 1) & 1) * 128 + (i & 1) * 256, pack(geglu2(gu[2 * i], gu[32 + 2 * i]), geglu2(gu[2 * i + 1], gu[32 + 2 * i + 1])));
            signal(4);
            PROF(3);
            wg_wait<1>();
            release();
            mbar_wait(fb, ph);
            PROF(38);
        }

        const uint32_t gaddr = s_gate + (grp * 8 + (lane >> 2)) * 4;
        at.q[6] = lds32(s_zero); at.q[7] = lds32(s_zero + 4);
#pragma unroll
        for (int i = 0; i < 16; i++) at.p[i] = 0u;
#pragma unroll
        for (int i = 0; i < 12; i++) at.o[i] = 0.f;
        fence_regs(at.q); fence_regs(at.p); fence_regs(at.o);
        pd = sd;
        uint32_t rel = bar_empty + 8;
        asm volatile("mapa.shared::cluster.u32 %0, %0, %1;" : "+r"(rel) : "r"(tid & 1));
        const uint32_t rel_off = rel - (bar_full + 8);

#define ISSUE_PV() do {                                                                                            \
            const uint32_t dv = pd + dlo(OFF_KV + 256, 640);                                                       \
            wgmma_rs_n24_t1<HI_V>(at.o, at.p[0], at.p[1], at.p[2], at.p[3], dv, 1);                                \
            wgmma_rs_n24_t1<HI_V>(at.o, at.p[4], at.p[5], at.p[6], at.p[7], dv + 80, 1);                           \
            wgmma_rs_n24_t1<HI_V>(at.o, at.p[8], at.p[9], at.p[10], at.p[11], dv + 160, 1);                        \
            wgmma_rs_n24_t1<HI_V>(at.o, at.p[12], at.p[13], at.p[14], at.p[15], dv + 240, 1);                      \
        } while (0)
#define EXPS() do {                                                                                                \
            _Pragma("unroll") for (int i = 0; i < 16; i++) at.p[i] = pack(ex2(at.s[2 * i]), ex2(at.s[2 * i + 1])); \
            fence_regs(at.p);                                                                                      \
        } while (0)
#define FUSED_STEP(DV, DK, NB, NPH, REL, GEMM_CODE) do {                                                           \
            wg_fence();                                                                                            \
            wgmma6_rs_n24_t1(at.o, at.p[0], at.p[1], at.p[2], at.p[3], (DV), 1);                                   \
            wgmma6_rs_n24_t1(at.o, at.p[4], at.p[5], at.p[6], at.p[7], (DV) + 80, 1);                              \
            wgmma6_rs_n24_t1(at.o, at.p[8], at.p[9], at.p[10], at.p[11], (DV) + 160, 1);                           \
            wgmma6_rs_n24_t1(at.o, at.p[12], at.p[13], at.p[14], at.p[15], (DV) + 240, 1);                         \
            wgmma6_rs_n64_t0(at.s, at.q[0], at.q[1], at.q[2], at.q[3], (DK) + dlo(0, 128), 0);                     \
            wgmma6_rs_n64_t0(at.s, at.q[4], at.q[5], at.q[6], at.q[7], (DK) + 32, 1);                              \
            wg_commit();                                                                                           \
            GEMM_CODE;                                                                                             \
            wg_commit();                                                                                           \
            const uint32_t rdy = mbar_test(NB, NPH);                                                               \
            wg_wait<1>();                                                                                          \
            fence_regs(at.s); fence_regs(at.p);                                                                    \
            if (tid < 2) asm volatile("mbarrier.arrive.shared::cluster.b64 _, [%0];" ::"r"(REL) : "memory");       \
            EXPS();                                                                                                \
            mbar_wait_unless(rdy, NB, NPH);                                                                        \
        } while (0)
#define FUSED_PAIR(HIA, LOA, LOB, STEP0, GEMM) do {                                                                \
            const uint64_t dv0 = mkdesc<HI_V>(pd + dlo(OFF_KV + 256, 640));                                        \
            const uint64_t dv1 = mkdesc<HI_V>(sd + dlo(OFF_KV + 256, 640));                                        \
            const uint64_t dk = mkdesc<HI_K>(sd + dlo(OFF_KV, 0));                                                 \
            const uint64_t da = mkdesc<HIA>(sd + (LOA)), db = mkdesc<HI_W>(sd + (LOB));                            \
            STEP0(dv0, dk, fb + 8, ph, rel, GEMM(da, db, first));                                                  \
            const uint32_t r1 = fb + rel_off;                                                                      \
            rel = r1 + 8;                                                                                          \
            pd = sd + (SLOT >> 4); pb = fb + 8;                                                                    \
            if (fb == bar_full + (NSTAGE - 2) * 8) { fb = bar_full; ph ^= 1; } else fb += 16;                      \
            sd = (sd == sbd + (NSTAGE - 2) * (SLOT >> 4)) ? sbd : sd + 2 * (SLOT >> 4);                            \
            FUSED_STEP(dv1, dk + (SLOT >> 4), fb, ph, r1, GEMM(da + (SLOT >> 4), db + (SLOT >> 4), 1));            \
            first = 1;                                                                                             \
            TRACE();                                                                                               \
        } while (0)
#define GEMM_256(A, B, SC) do { wgmma6_ss_n256_t1(acc, A, B, SC); wgmma6_ss_n256_t1(acc, (A) + 2, (B) + 128, 1); } while (0)
#define GEMM_80(A, B, SC) do { wgmma6_ss_n80_t1(keep, A, B, SC); wgmma6_ss_n80_t1(keep, (A) + 256, (B) + 128, 1); wgmma6_ss_n80_t1(keep, (A) + 512, (B) + 256, 1); } while (0)
#define GEMM_144(A, B, SC) do { wgmma6_ss_n144_t1(ah, A, B, SC); wgmma6_ss_n144_t1(ah, (A) + 256, (B) + 128, 1); wgmma6_ss_n144_t1(ah, (A) + 512, (B) + 256, 1); } while (0)
#define NORM_ITEM(item) do {                                                                                       \
            if (norm_o(ow, at.o, lane, gaddr)) {                                                                   \
                attn_true_max(at.o, at.q, g_kv + (size_t)(j * 4 + (item)) * HEAD_BYTES + lane * 4);                \
                norm_o(ow, at.o, lane, gaddr);                                                                     \
            }                                                                                                      \
        } while (0)
#define STORE_ITEM(item) do { uint32_t ow[6]; NORM_ITEM(item); PUT_ITEM(item); } while (0)
#define PUT_ITEM(item) do {                                                                                        \
            uint8_t* op = a2w + (288 + ((item) * 4 + (j >> 1)) * 3) * 4096 + (j & 1) * 4224;                       \
            const int step = (j & 1) ? 3968 : 128;                                                                 \
            stg32(op, ow[0]);        stg32(op + 256, ow[1]);                                                       \
            stg32(op + step, ow[2]); stg32(op + step + 256, ow[3]);                                                \
            stg32(op + 4096, ow[4]); stg32(op + 4096 + 256, ow[5]);                                                \
        } while (0)
#define ITEM_STEP(DV, DK, NB, NPH, REL, GEMM_CODE) do {                                                            \
            uint32_t qo[8];                                                                                        \
            _Pragma("unroll") for (int i = 0; i < 6; i++) asm volatile("mov.b32 %0, %1;" : "=r"(qo[i]) : "r"(at.q[i])); \
            load_q(at.q, qa + (item + 1) * 4608, lane);                                                            \
            fence_regs(at.q);                                                                                      \
            wg_fence();                                                                                            \
            wgmma6_rs_n24_t1(at.o, at.p[0], at.p[1], at.p[2], at.p[3], (DV), 1);                                   \
            wgmma6_rs_n24_t1(at.o, at.p[4], at.p[5], at.p[6], at.p[7], (DV) + 80, 1);                              \
            wgmma6_rs_n24_t1(at.o, at.p[8], at.p[9], at.p[10], at.p[11], (DV) + 160, 1);                           \
            wgmma6_rs_n24_t1(at.o, at.p[12], at.p[13], at.p[14], at.p[15], (DV) + 240, 1);                         \
            wgmma6_rs_n64_t0(at.s, at.q[0], at.q[1], at.q[2], at.q[3], (DK) + dlo(0, 128), 0);                     \
            wgmma6_rs_n64_t0(at.s, at.q[4], at.q[5], at.q[6], at.q[7], (DK) + 32, 1);                              \
            wg_commit();                                                                                           \
            GEMM_CODE;                                                                                             \
            wg_commit();                                                                                           \
            wg_wait<1>();                                                                                          \
            fence_regs(at.o); fence_regs(at.p); fence_regs(at.s);                                                  \
            if (tid < 2) asm volatile("mbarrier.arrive.shared::cluster.b64 _, [%0];" ::"r"(REL) : "memory");       \
            uint32_t ow[6];                                                                                        \
            const bool bad = norm_o(ow, at.o, lane, gaddr);                                                        \
            EXPS();                                                                                                \
            if (bad) {                                                                                             \
                attn_true_max(at.o, qo, g_kv + (size_t)(j * 4 + (item)) * HEAD_BYTES + lane * 4);                  \
                norm_o(ow, at.o, lane, gaddr);                                                                     \
            }                                                                                                      \
            PUT_ITEM(item);                                                                                        \
            _Pragma("unroll") for (int i = 0; i < 12; i++) at.o[i] = 0.f;                                          \
            fence_regs(at.o);                                                                                      \
            mbar_wait(NB, NPH);                                                                                    \
        } while (0)
#define H2(i) pack(geglu2(acc[i], acc[64 + (i)]), geglu2(acc[(i) + 1], acc[65 + (i)]))
        float keep[40];
        float4 px[3];
        {
            float ah[72];
            int first = 1;
            {
#pragma unroll 1
                for (int t = 0; t < 5; t++) {
                    int n = 0x26988 >> (t * 4) & 15;
#pragma unroll 1
                    do { FUSED_PAIR(HI_X, wg * 256 + dlo(OFF_AX, 16), dlo(0, 4096), FUSED_STEP, GEMM_256); } while (--n);
                    if (t & 1) {
                        const int item = t >> 1;
                        mbar_wait(t == 1 ? bar_gate : bar_rdy + 2 * 8, 0);
                        FUSED_PAIR(HI_X, wg * 256 + dlo(OFF_AX, 16), dlo(0, 4096), ITEM_STEP, GEMM_256);
                    }
                    if (t < 3) {
                        mbar_wait(t > 0 ? bar_rdy + (t - 1) * 8 : bar_free + wg * 8, 0);
                        wg_wait<0>();
                        fence_regs(acc);
                        first = 0;
                        PROF(4 + 2 * t);
                        const uint32_t ha = sb + wg * 3 * SLOT + OFF_GAP + wq * 512 + lane * 16;
#pragma unroll
                        for (int k = 0; k < 8; k++) stsm4(ha + (k / 3) * SLOT + (k % 3) * 2048, H2(8 * k), H2(8 * k + 4), H2(8 * k + 2), H2(8 * k + 6));
                        fence_async_shared();
                        undef_regs(acc);
                        signal(t);
                        PROF(5 + 2 * t);
                    }
                }
                wg_wait<0>();
                fence_regs(acc);
                first = 0;
                PROF(10);
                uint8_t* hp = a2w + (j * 36 + 24) * 4096;
#pragma unroll
                for (int b = 0; b < 2; b++)
                    if (cta != 1000 + b) {
#pragma unroll
                        for (int k = b * 4; k < b * 4 + 4; k++) {
                            stg32(hp + k * 4096, H2(8 * k));           stg32(hp + k * 4096 + 256, H2(8 * k + 2));
                            stg32(hp + k * 4096 + 128, H2(8 * k + 4)); stg32(hp + k * 4096 + 384, H2(8 * k + 6));
                        }
                    }
                signal(3);
                PROF(11);
            }
#pragma unroll 1
            for (int seg = 0; seg < 3; seg++) {
                int n = 0x2AD >> (seg * 4) & 15;
#pragma unroll 1
                do { FUSED_PAIR(HI_A2, wg * 128 + dlo(OFF_A2, 128), dlo(0, 6144), FUSED_STEP, GEMM_144); } while (--n);
                if (seg == 0) {
                    constexpr int item = 2;
                    FUSED_PAIR(HI_A2, wg * 128 + dlo(OFF_A2, 128), dlo(0, 6144), ITEM_STEP, GEMM_144);
                    signal(5);
                } else if (seg == 1) {
                    wg_wait<0>();
                    fence_regs(ah);
                    PROF(12);
                    const float w0 = 0.5f - 0.5f * __uint_as_float(lds32(gaddr)), w1 = 0.5f - 0.5f * __uint_as_float(lds32(gaddr + 32));
#pragma unroll
                    for (int i = 0; i < 72; i++) ah[i] *= (i & 2) ? w1 : w0;
                    fence_regs(ah);
                }
            }
            wg_wait<0>();
            fence_regs(ah);
            PROF(17);
            mbar_wait(bar_px, 0);
#pragma unroll
            for (int i = 0; i < 3; i++) px[i] = __ldcg(g_px + (size_t)(cta * 2 + wg) * 3 * 128 + tid + i * 128);
            uint4* mine = g_part + (size_t)(cta * 2 + wg) * 5 * 128 + tid;
#pragma unroll
            for (int i = 0; i < 5; i++) {
                uint32_t u[4];
#pragma unroll
                for (int e = 0; e < 4; e++) {
                    const int k = 8 * i + 2 * e;
                    if (i < 4) {
                        u[e] = pack(sel(hf, ah[k], ah[32 + k]), sel(hf, ah[k + 1], ah[33 + k]));
                        keep[k] = sel(hf, ah[32 + k], ah[k]); keep[k + 1] = sel(hf, ah[33 + k], ah[k + 1]);
                    } else {
                        u[e] = pack(ah[32 + k], ah[33 + k]);
                        keep[k] = sel(1, ah[32 + k], 0.f); keep[k + 1] = sel(1, ah[33 + k], 0.f);
                    }
                }
                __stcg(mine + i * 128, make_uint4(u[0], u[1], u[2], u[3]));
            }
            signal(6);
            fence_regs(keep);
        }
        {
            int first = 1;
            FUSED_PAIR(HI_A2, wg * 128 + dlo(OFF_A2, 128), dlo(0, 6144), FUSED_STEP, GEMM_80);
        }
        PROF(13);
        wg_fence();
        ISSUE_PV();
        wg_commit();
        wg_wait<0>();
        fence_regs(at.o); fence_regs(at.p); fence_regs(at.q);
#pragma unroll
        for (int i = 0; i < 3; i++) { at.o[4 * i] += px[i].x; at.o[4 * i + 1] += px[i].y; at.o[4 * i + 2] += px[i].z; at.o[4 * i + 3] += px[i].w; }
        STORE_ITEM(3);
        signal(7);
        fence_regs(keep);
        PROF(14);
#pragma unroll 1
        for (int kk = 0; kk < 2; kk++) {
            mbar_wait(fb, ph);
            const uint64_t da = mkdesc<HI_A2>(sd + wg * 128 + dlo(OFF_A2, 128)), db = mkdesc<HI_W>(sd + dlo(0, 6144));
            wg_fence();
            GEMM_80(da, db, 1);
            wg_commit();
            wg_wait<1>();
            if (kk < 1) release();
            STAGE_NEXT;
        }
        {
            mbar_wait(bar_rdy + 6 * 8, 0);
            const uint4* theirs = g_part + (size_t)((cta ^ 8) * 2 + wg) * 5 * 128 + tid;
            uint4 pv[5];
#pragma unroll
            for (int i = 0; i < 5; i++) pv[i] = __ldcg(theirs + i * 128);
            wg_wait<0>();
            fence_regs(keep);
#pragma unroll
            for (int i = 0; i < 5; i++) {
                const uint32_t u[4] = {pv[i].x, pv[i].y, pv[i].z, pv[i].w};
#pragma unroll
                for (int e = 0; e < 4; e++) { keep[8 * i + 2 * e] += __uint_as_float(u[e] << 16); keep[8 * i + 2 * e + 1] += __uint_as_float(u[e] & 0xffff0000u); }
            }
            fence_regs(keep);
        }
        mbar_wait(bar_late, 0);
#pragma unroll 1
        for (int k = 2; k < 6; k++) {
            mbar_wait(bar_full + k * 8, 0);
            if (k == 2) PROF(15);
            const uint32_t bo = __shfl_sync(0xffffffffu, lds32(s_order + k * 4), 0);
            const uint64_t da = mkdesc<HI_A2>(sbd + k * (SLOT >> 4) + wg * 128 + dlo(OFF_A2, 128)), db = mkdesc<HI_W>(sbd + bo + dlo(0, 6144));
            wg_fence();
            GEMM_80(da, db, 1);
            wg_commit();
        }
        asm volatile("barrier.cluster.arrive.relaxed.aligned;" ::: "memory");
        const uint32_t tb = sb + (warp >> 1) * SLOT + OFF_KV + (warp & 1) * 2560;
        const uint32_t trow = ((lane >> 3) & 1) * 8 + (lane & 7);
        uint8_t* op = (uint8_t*)(out + (size_t)(m * 128 + grp * 8) * DM);
        wg_wait<0>();
        fence_regs(keep);
        PROF(16);
#pragma unroll
        for (int i = 0; i < 5; i++) {
            const uint32_t a = i < 4 ? tb + trow * 128 + (((2 * i + (lane >> 4)) ^ (lane & 7)) << 4) : tb + 2048 + trow * 32 + (lane >> 4) * 16;
            stsm4(a, pack(keep[8 * i], keep[8 * i + 1]), pack(keep[8 * i + 2], keep[8 * i + 3]), pack(keep[8 * i + 4], keep[8 * i + 5]), pack(keep[8 * i + 6], keep[8 * i + 7]));
        }
        __syncwarp();
        uint4 v[5];
#pragma unroll
        for (int i = 0; i < 5; i++) {
            const uint32_t r = 4 * i + (lane >> 3);
            const uint32_t a = i < 4 ? tb + r * 128 + (((lane & 7) ^ (r & 7)) << 4) : tb + 2048 + lane * 16;
            asm volatile("ld.shared.v4.u32 {%0, %1, %2, %3}, [%4];" : "=r"(v[i].x), "=r"(v[i].y), "=r"(v[i].z), "=r"(v[i].w) : "r"(a) : "memory");
        }
#pragma unroll
        for (int i = 0; i < 4; i++) *(uint4*)(op + (4 * i + (lane >> 3)) * (DM * 2) + nt * 256 + hf * 128 + (lane & 7) * 16) = v[i];
        if (wg == hf) *(uint4*)(op + (lane >> 1) * (DM * 2) + 1024 + nt * 32 + (lane & 1) * 16) = v[4];
        PROF(20);
        asm volatile("barrier.cluster.wait.aligned;" ::: "memory");
    }
}

typedef CUresult (*EncodeFn)(CUtensorMap*, CUtensorMapDataType, cuuint32_t, void*, const cuuint64_t*, const cuuint64_t*,
                             const cuuint32_t*, const cuuint32_t*, CUtensorMapInterleave, CUtensorMapSwizzle,
                             CUtensorMapL2promotion, CUtensorMapFloatOOBfill);

CUtensorMap make_map(EncodeFn enc, const void* ptr, uint64_t inner, uint64_t outer, uint32_t box_inner, uint32_t box_outer, CUtensorMapSwizzle swz) {
    CUtensorMap t;
    cuuint64_t dims[2] = {inner, outer};
    cuuint64_t strides[1] = {inner * 2};
    cuuint32_t box[2] = {box_inner, box_outer};
    cuuint32_t es[2] = {1, 1};
    enc(&t, CU_TENSOR_MAP_DATA_TYPE_BFLOAT16, 2, const_cast<void*>(ptr), dims, strides, box, es, CU_TENSOR_MAP_INTERLEAVE_NONE, swz,
        CU_TENSOR_MAP_L2_PROMOTION_L2_128B, CU_TENSOR_MAP_FLOAT_OOB_FILL_NONE);
    return t;
}

CUtensorMap make_strip_map(EncodeFn enc, const void* ptr, uint64_t rows, uint64_t width) {
    CUtensorMap t;
    cuuint64_t dims[3] = {width, rows, (DM - width) / 8 + 1};
    cuuint64_t strides[2] = {DM * 2, 16};
    cuuint32_t box[3] = {64, 24, 1};
    cuuint32_t es[3] = {1, 1, 1};
    enc(&t, CU_TENSOR_MAP_DATA_TYPE_BFLOAT16, 3, const_cast<void*>(ptr), dims, strides, box, es, CU_TENSOR_MAP_INTERLEAVE_NONE,
        CU_TENSOR_MAP_SWIZZLE_128B, CU_TENSOR_MAP_L2_PROMOTION_L2_128B, CU_TENSOR_MAP_FLOAT_OOB_FILL_NONE);
    return t;
}

}

extern "C" void kernel_launch(void* const* d_in, const int* in_sizes, int n_in, void* d_out, int out_size) {
    (void)in_sizes; (void)n_in; (void)out_size;
    void* fn = nullptr;
    cudaDriverEntryPointQueryResult qr;
    cudaGetDriverEntryPoint("cuTensorMapEncodeTiled", &fn, cudaEnableDefault, &qr);
    EncodeFn enc = (EncodeFn)fn;
    const CUtensorMap tm_x = make_map(enc, d_in[0], DM, SEQ, 32, 128, CU_TENSOR_MAP_SWIZZLE_64B);
    const CUtensorMap tm_qkv = make_map(enc, d_in[1], 3 * DM, DM, 64, 16, CU_TENSOR_MAP_SWIZZLE_128B);
    const CUtensorMap tm_qkv8 = make_map(enc, d_in[1], 3 * DM, DM, 8, 16, CU_TENSOR_MAP_SWIZZLE_NONE);
    const CUtensorMap tm_wo = make_map(enc, d_in[2], DM, DM, 64, 24, CU_TENSOR_MAP_SWIZZLE_128B);
    const CUtensorMap tm_wg = make_map(enc, d_in[4], FF, DM, 64, 32, CU_TENSOR_MAP_SWIZZLE_128B);
    const CUtensorMap tm_wu = make_map(enc, d_in[5], FF, DM, 64, 32, CU_TENSOR_MAP_SWIZZLE_128B);
    const CUtensorMap tm_wd = make_map(enc, d_in[6], DM, FF, 64, 24, CU_TENSOR_MAP_SWIZZLE_128B);
    const CUtensorMap tm_wd16 = make_strip_map(enc, d_in[6], FF, 16), tm_wo16 = make_strip_map(enc, d_in[2], DM, 16);
    cudaFuncSetAttribute(fused_kernel, cudaFuncAttributeMaxDynamicSharedMemorySize, SMEM_BYTES);
    fused_kernel<<<NCTA + 4, 384, SMEM_BYTES>>>((__nv_bfloat16*)d_out, (const __nv_bfloat16*)d_in[0], (const __nv_bfloat16*)d_in[7],
                                               (const uint8_t*)d_in[1], (const uint8_t*)d_in[4], (const uint8_t*)d_in[5],
                                               tm_x, tm_qkv, tm_qkv8, tm_wg, tm_wu, tm_wd, tm_wo, tm_wd16, tm_wo16);
}
```

```cpp
#include <cuda_runtime.h>
#include <cuda.h>
#include <cuda_bf16.h>
#include <stdint.h>

#define PROFILE 0
#define DOTRACE 0

namespace {

constexpr int SEQ = 2048, DM = 576, FF = 4608;
constexpr int NCTA = 128;
constexpr int NSTAGE = 6;
constexpr int DEFER = 2;
constexpr int SLOT = 35 * 1024;
constexpr int OFF_AX = 22528;
constexpr int OFF_A2 = 18432;
constexpr int OFF_TL = 20480;
constexpr int OFF_GAP = 16384;
constexpr int OFF_KV = 30720;
constexpr int OFF_Q = NSTAGE * SLOT - 4608;
constexpr int OFF_BAR = NSTAGE * SLOT + 3 * 4608;
constexpr int SMEM_BYTES = OFF_BAR + 1024 + 1024;

constexpr int STRIPB = 48 * 32;
constexpr int HEAD_BYTES = 256 * 640;
constexpr int A2_TILE = 336 * 4096;

constexpr int FL_KV = 0;
constexpr int FL_M = FL_KV + 8 * 32;
constexpr int FM_H = 0;
constexpr int FM_LATE = 7;
constexpr int FM_R = 16;
constexpr int FL_G = FL_M + 16 * 64;
constexpr int FL_E = FL_G + 4 * 32;
constexpr int FL_N = FL_E + (NCTA + 4) * 32;

__device__ __align__(1024) uint8_t g_kv[32 * HEAD_BYTES];
__device__ __align__(1024) uint8_t g_a2[16 * A2_TILE];
__device__ __align__(1024) uint4 g_part[NCTA * 2 * 5 * 128];
__device__ __align__(1024) uint8_t g_q3[NCTA * 4608];
__device__ __align__(1024) float4 g_px[NCTA * 2 * 3 * 128];
__device__ float g_gate[SEQ];
__device__ __align__(256) uint32_t g_flags[FL_N];

template <uint32_t BHI>
__device__ __forceinline__ void wgmma_rs_n24_t1(float (&d)[12], uint32_t a0, uint32_t a1, uint32_t a2, uint32_t a3, uint32_t db, int scale_d) {
  asm volatile("{\n.reg .pred p;\n.reg .b64 da, db;\n"
    "mov.b64 db, {%16, %18};\n"
    "setp.ne.b32 p, %17, 0;\n"
    "wgmma.mma_async.sync.aligned.m64n24k16.f32.bf16.bf16 "
    "{%0, %1, %2, %3, %4, %5, %6, %7, %8, %9, %10, %11}, "
    "{%12, %13, %14, %15}, db, p, 1, 1, 1;\n}\n"
    : "+f"(d[0]), "+f"(d[1]), "+f"(d[2]), "+f"(d[3]), "+f"(d[4]), "+f"(d[5]), "+f"(d[6]), "+f"(d[7]),
      "+f"(d[8]), "+f"(d[9]), "+f"(d[10]), "+f"(d[11])
    : "r"(a0), "r"(a1), "r"(a2), "r"(a3), "r"(db), "r"(scale_d), "n"(BHI));
}
template <uint32_t BHI>
__device__ __forceinline__ void wgmma_rs_n128_t0(float (&d)[64], uint32_t a0, uint32_t a1, uint32_t a2, uint32_t a3, uint32_t db, int scale_d) {
  asm volatile("{\n.reg .pred p;\n.reg .b64 da, db;\n"
    "mov.b64 db, {%68, %70};\n"
    "setp.ne.b32 p, %69, 0;\n"
    "wgmma.mma_async.sync.aligned.m64n128k16.f32.bf16.bf16 "
    "{%0, %1, %2, %3, %4, %5, %6, %7, %8, %9, %10, %11, %12, %13, %14, %15, "
    "%16, %17, %18, %19, %20, %21, %22, %23, %24, %25, %26, %27, %28, %29, %30, %31, "
    "%32, %33, %34, %35, %36, %37, %38, %39, %40, %41, %42, %43, %44, %45, %46, %47, "
    "%48, %49, %50, %51, %52, %53, %54, %55, %56, %57, %58, %59, %60, %61, %62, %63}, "
    "{%64, %65, %66, %67}, db, p, 1, 1, 0;\n}\n"
    : "+f"(d[0]), "+f"(d[1]), "+f"(d[2]), "+f"(d[3]), "+f"(d[4]), "+f"(d[5]), "+f"(d[6]), "+f"(d[7]),
      "+f"(d[8]), "+f"(d[9]), "+f"(d[10]), "+f"(d[11]), "+f"(d[12]), "+f"(d[13]), "+f"(d[14]), "+f"(d[15]),
      "+f"(d[16]), "+f"(d[17]), "+f"(d[18]), "+f"(d[19]), "+f"(d[20]), "+f"(d[21]), "+f"(d[22]), "+f"(d[23]),
      "+f"(d[24]), "+f"(d[25]), "+f"(d[26]), "+f"(d[27]), "+f"(d[28]), "+f"(d[29]), "+f"(d[30]), "+f"(d[31]),
      "+f"(d[32]), "+f"(d[33]), "+f"(d[34]), "+f"(d[35]), "+f"(d[36]), "+f"(d[37]), "+f"(d[38]), "+f"(d[39]),
      "+f"(d[40]), "+f"(d[41]), "+f"(d[42]), "+f"(d[43]), "+f"(d[44]), "+f"(d[45]), "+f"(d[46]), "+f"(d[47]),
      "+f"(d[48]), "+f"(d[49]), "+f"(d[50]), "+f"(d[51]), "+f"(d[52]), "+f"(d[53]), "+f"(d[54]), "+f"(d[55]),
      "+f"(d[56]), "+f"(d[57]), "+f"(d[58]), "+f"(d[59]), "+f"(d[60]), "+f"(d[61]), "+f"(d[62]), "+f"(d[63])
    : "r"(a0), "r"(a1), "r"(a2), "r"(a3), "r"(db), "r"(scale_d), "n"(BHI));
}
template <uint32_t BHI>
__device__ __forceinline__ void wgmma_rs_n128_t1(float (&d)[64], uint32_t a0, uint32_t a1, uint32_t a2, uint32_t a3, uint32_t db, int scale_d) {
  asm volatile("{\n.reg .pred p;\n.reg .b64 da, db;\n"
    "mov.b64 db, {%68, %70};\n"
    "setp.ne.b32 p, %69, 0;\n"
    "wgmma.mma_async.sync.aligned.m64n128k16.f32.bf16.bf16 "
    "{%0, %1, %2, %3, %4, %5, %6, %7, %8, %9, %10, %11, %12, %13, %14, %15, "
    "%16, %17, %18, %19, %20, %21, %22, %23, %24, %25, %26, %27, %28, %29, %30, %31, "
    "%32, %33, %34, %35, %36, %37, %38, %39, %40, %41, %42, %43, %44, %45, %46, %47, "
    "%48, %49, %50, %51, %52, %53, %54, %55, %56, %57, %58, %59, %60, %61, %62, %63}, "
    "{%64, %65, %66, %67}, db, p, 1, 1, 1;\n}\n"
    : "+f"(d[0]), "+f"(d[1]), "+f"(d[2]), "+f"(d[3]), "+f"(d[4]), "+f"(d[5]), "+f"(d[6]), "+f"(d[7]),
      "+f"(d[8]), "+f"(d[9]), "+f"(d[10]), "+f"(d[11]), "+f"(d[12]), "+f"(d[13]), "+f"(d[14]), "+f"(d[15]),
      "+f"(d[16]), "+f"(d[17]), "+f"(d[18]), "+f"(d[19]), "+f"(d[20]), "+f"(d[21]), "+f"(d[22]), "+f"(d[23]),
      "+f"(d[24]), "+f"(d[25]), "+f"(d[26]), "+f"(d[27]), "+f"(d[28]), "+f"(d[29]), "+f"(d[30]), "+f"(d[31]),
      "+f"(d[32]), "+f"(d[33]), "+f"(d[34]), "+f"(d[35]), "+f"(d[36]), "+f"(d[37]), "+f"(d[38]), "+f"(d[39]),
      "+f"(d[40]), "+f"(d[41]), "+f"(d[42]), "+f"(d[43]), "+f"(d[44]), "+f"(d[45]), "+f"(d[46]), "+f"(d[47]),
      "+f"(d[48]), "+f"(d[49]), "+f"(d[50]), "+f"(d[51]), "+f"(d[52]), "+f"(d[53]), "+f"(d[54]), "+f"(d[55]),
      "+f"(d[56]), "+f"(d[57]), "+f"(d[58]), "+f"(d[59]), "+f"(d[60]), "+f"(d[61]), "+f"(d[62]), "+f"(d[63])
    : "r"(a0), "r"(a1), "r"(a2), "r"(a3), "r"(db), "r"(scale_d), "n"(BHI));
}
template <uint32_t BHI>
__device__ __forceinline__ void wgmma_rs_n192_t1(float (&d)[96], uint32_t a0, uint32_t a1, uint32_t a2, uint32_t a3, uint32_t db, int scale_d) {
  asm volatile("{\n.reg .pred p;\n.reg .b64 da, db;\n"
    "mov.b64 db, {%100, %102};\n"
    "setp.ne.b32 p, %101, 0;\n"
    "wgmma.mma_async.sync.aligned.m64n192k16.f32.bf16.bf16 "
    "{%0, %1, %2, %3, %4, %5, %6, %7, %8, %9, %10, %11, %12, %13, %14, %15, "
    "%16, %17, %18, %19, %20, %21, %22, %23, %24, %25, %26, %27, %28, %29, %30, %31, "
    "%32, %33, %34, %35, %36, %37, %38, %39, %40, %41, %42, %43, %44, %45, %46, %47, "
    "%48, %49, %50, %51, %52, %53, %54, %55, %56, %57, %58, %59, %60, %61, %62, %63, "
    "%64, %65, %66, %67, %68, %69, %70, %71, %72, %73, %74, %75, %76, %77, %78, %79, "
    "%80, %81, %82, %83, %84, %85, %86, %87, %88, %89, %90, %91, %92, %93, %94, %95}, "
    "{%96, %97, %98, %99}, db, p, 1, 1, 1;\n}\n"
    : "+f"(d[0]), "+f"(d[1]), "+f"(d[2]), "+f"(d[3]), "+f"(d[4]), "+f"(d[5]), "+f"(d[6]), "+f"(d[7]),
      "+f"(d[8]), "+f"(d[9]), "+f"(d[10]), "+f"(d[11]), "+f"(d[12]), "+f"(d[13]), "+f"(d[14]), "+f"(d[15]),
      "+f"(d[16]), "+f"(d[17]), "+f"(d[18]), "+f"(d[19]), "+f"(d[20]), "+f"(d[21]), "+f"(d[22]), "+f"(d[23]),
      "+f"(d[24]), "+f"(d[25]), "+f"(d[26]), "+f"(d[27]), "+f"(d[28]), "+f"(d[29]), "+f"(d[30]), "+f"(d[31]),
      "+f"(d[32]), "+f"(d[33]), "+f"(d[34]), "+f"(d[35]), "+f"(d[36]), "+f"(d[37]), "+f"(d[38]), "+f"(d[39]),
      "+f"(d[40]), "+f"(d[41]), "+f"(d[42]), "+f"(d[43]), "+f"(d[44]), "+f"(d[45]), "+f"(d[46]), "+f"(d[47]),
      "+f"(d[48]), "+f"(d[49]), "+f"(d[50]), "+f"(d[51]), "+f"(d[52]), "+f"(d[53]), "+f"(d[54]), "+f"(d[55]),
      "+f"(d[56]), "+f"(d[57]), "+f"(d[58]), "+f"(d[59]), "+f"(d[60]), "+f"(d[61]), "+f"(d[62]), "+f"(d[63]),
      "+f"(d[64]), "+f"(d[65]), "+f"(d[66]), "+f"(d[67]), "+f"(d[68]), "+f"(d[69]), "+f"(d[70]), "+f"(d[71]),
      "+f"(d[72]), "+f"(d[73]), "+f"(d[74]), "+f"(d[75]), "+f"(d[76]), "+f"(d[77]), "+f"(d[78]), "+f"(d[79]),
      "+f"(d[80]), "+f"(d[81]), "+f"(d[82]), "+f"(d[83]), "+f"(d[84]), "+f"(d[85]), "+f"(d[86]), "+f"(d[87]),
      "+f"(d[88]), "+f"(d[89]), "+f"(d[90]), "+f"(d[91]), "+f"(d[92]), "+f"(d[93]), "+f"(d[94]), "+f"(d[95])
    : "r"(a0), "r"(a1), "r"(a2), "r"(a3), "r"(db), "r"(scale_d), "n"(BHI));
}
template <uint32_t AHI, uint32_t BHI>
__device__ __forceinline__ void wgmma_ss_n24_t1(float (&d)[12], uint32_t da, uint32_t db, int scale_d) {
  asm volatile("{\n.reg .pred p;\n.reg .b64 da, db;\n"
    "mov.b64 da, {%12, %15};\nmov.b64 db, {%13, %16};\n"
    "setp.ne.b32 p, %14, 0;\n"
    "wgmma.mma_async.sync.aligned.m64n24k16.f32.bf16.bf16 "
    "{%0, %1, %2, %3, %4, %5, %6, %7, %8, %9, %10, %11}, "
    "da, db, p, 1, 1, 0, 1;\n}\n"
    : "+f"(d[0]), "+f"(d[1]), "+f"(d[2]), "+f"(d[3]), "+f"(d[4]), "+f"(d[5]), "+f"(d[6]), "+f"(d[7]),
      "+f"(d[8]), "+f"(d[9]), "+f"(d[10]), "+f"(d[11])
    : "r"(da), "r"(db), "r"(scale_d), "n"(AHI), "n"(BHI));
}
template <uint32_t AHI, uint32_t BHI>
__device__ __forceinline__ void wgmma_ss_n128_t1(float (&d)[64], uint32_t da, uint32_t db, int scale_d) {
  asm volatile("{\n.reg .pred p;\n.reg .b64 da, db;\n"
    "mov.b64 da, {%64, %67};\nmov.b64 db, {%65, %68};\n"
    "setp.ne.b32 p, %66, 0;\n"
    "wgmma.mma_async.sync.aligned.m64n128k16.f32.bf16.bf16 "
    "{%0, %1, %2, %3, %4, %5, %6, %7, %8, %9, %10, %11, %12, %13, %14, %15, "
    "%16, %17, %18, %19, %20, %21, %22, %23, %24, %25, %26, %27, %28, %29, %30, %31, "
    "%32, %33, %34, %35, %36, %37, %38, %39, %40, %41, %42, %43, %44, %45, %46, %47, "
    "%48, %49, %50, %51, %52, %53, %54, %55, %56, %57, %58, %59, %60, %61, %62, %63}, "
    "da, db, p, 1, 1, 0, 1;\n}\n"
    : "+f"(d[0]), "+f"(d[1]), "+f"(d[2]), "+f"(d[3]), "+f"(d[4]), "+f"(d[5]), "+f"(d[6]), "+f"(d[7]),
      "+f"(d[8]), "+f"(d[9]), "+f"(d[10]), "+f"(d[11]), "+f"(d[12]), "+f"(d[13]), "+f"(d[14]), "+f"(d[15]),
      "+f"(d[16]), "+f"(d[17]), "+f"(d[18]), "+f"(d[19]), "+f"(d[20]), "+f"(d[21]), "+f"(d[22]), "+f"(d[23]),
      "+f"(d[24]), "+f"(d[25]), "+f"(d[26]), "+f"(d[27]), "+f"(d[28]), "+f"(d[29]), "+f"(d[30]), "+f"(d[31]),
      "+f"(d[32]), "+f"(d[33]), "+f"(d[34]), "+f"(d[35]), "+f"(d[36]), "+f"(d[37]), "+f"(d[38]), "+f"(d[39]),
      "+f"(d[40]), "+f"(d[41]), "+f"(d[42]), "+f"(d[43]), "+f"(d[44]), "+f"(d[45]), "+f"(d[46]), "+f"(d[47]),
      "+f"(d[48]), "+f"(d[49]), "+f"(d[50]), "+f"(d[51]), "+f"(d[52]), "+f"(d[53]), "+f"(d[54]), "+f"(d[55]),
      "+f"(d[56]), "+f"(d[57]), "+f"(d[58]), "+f"(d[59]), "+f"(d[60]), "+f"(d[61]), "+f"(d[62]), "+f"(d[63])
    : "r"(da), "r"(db), "r"(scale_d), "n"(AHI), "n"(BHI));
}
template <uint32_t AHI, uint32_t BHI>
__device__ __forceinline__ void wgmma_ss_n192_t1(float (&d)[96], uint32_t da, uint32_t db, int scale_d) {
  asm volatile("{\n.reg .pred p;\n.reg .b64 da, db;\n"
    "mov.b64 da, {%96, %99};\nmov.b64 db, {%97, %100};\n"
    "setp.ne.b32 p, %98, 0;\n"
    "wgmma.mma_async.sync.aligned.m64n192k16.f32.bf16.bf16 "
    "{%0, %1, %2, %3, %4, %5, %6, %7, %8, %9, %10, %11, %12, %13, %14, %15, "
    "%16, %17, %18, %19, %20, %21, %22, %23, %24, %25, %26, %27, %28, %29, %30, %31, "
    "%32, %33, %34, %35, %36, %37, %38, %39, %40, %41, %42, %43, %44, %45, %46, %47, "
    "%48, %49, %50, %51, %52, %53, %54, %55, %56, %57, %58, %59, %60, %61, %62, %63, "
    "%64, %65, %66, %67, %68, %69, %70, %71, %72, %73, %74, %75, %76, %77, %78, %79, "
    "%80, %81, %82, %83, %84, %85, %86, %87, %88, %89, %90, %91, %92, %93, %94, %95}, "
    "da, db, p, 1, 1, 0, 1;\n}\n"
    : "+f"(d[0]), "+f"(d[1]), "+f"(d[2]), "+f"(d[3]), "+f"(d[4]), "+f"(d[5]), "+f"(d[6]), "+f"(d[7]),
      "+f"(d[8]), "+f"(d[9]), "+f"(d[10]), "+f"(d[11]), "+f"(d[12]), "+f"(d[13]), "+f"(d[14]), "+f"(d[15]),
      "+f"(d[16]), "+f"(d[17]), "+f"(d[18]), "+f"(d[19]), "+f"(d[20]), "+f"(d[21]), "+f"(d[22]), "+f"(d[23]),
      "+f"(d[24]), "+f"(d[25]), "+f"(d[26]), "+f"(d[27]), "+f"(d[28]), "+f"(d[29]), "+f"(d[30]), "+f"(d[31]),
      "+f"(d[32]), "+f"(d[33]), "+f"(d[34]), "+f"(d[35]), "+f"(d[36]), "+f"(d[37]), "+f"(d[38]), "+f"(d[39]),
      "+f"(d[40]), "+f"(d[41]), "+f"(d[42]), "+f"(d[43]), "+f"(d[44]), "+f"(d[45]), "+f"(d[46]), "+f"(d[47]),
      "+f"(d[48]), "+f"(d[49]), "+f"(d[50]), "+f"(d[51]), "+f"(d[52]), "+f"(d[53]), "+f"(d[54]), "+f"(d[55]),
      "+f"(d[56]), "+f"(d[57]), "+f"(d[58]), "+f"(d[59]), "+f"(d[60]), "+f"(d[61]), "+f"(d[62]), "+f"(d[63]),
      "+f"(d[64]), "+f"(d[65]), "+f"(d[66]), "+f"(d[67]), "+f"(d[68]), "+f"(d[69]), "+f"(d[70]), "+f"(d[71]),
      "+f"(d[72]), "+f"(d[73]), "+f"(d[74]), "+f"(d[75]), "+f"(d[76]), "+f"(d[77]), "+f"(d[78]), "+f"(d[79]),
      "+f"(d[80]), "+f"(d[81]), "+f"(d[82]), "+f"(d[83]), "+f"(d[84]), "+f"(d[85]), "+f"(d[86]), "+f"(d[87]),
      "+f"(d[88]), "+f"(d[89]), "+f"(d[90]), "+f"(d[91]), "+f"(d[92]), "+f"(d[93]), "+f"(d[94]), "+f"(d[95])
    : "r"(da), "r"(db), "r"(scale_d), "n"(AHI), "n"(BHI));
}
template <uint32_t AHI, uint32_t BHI>
__device__ __forceinline__ void wgmma_ss_n256_t1(float (&d)[128], uint32_t da, uint32_t db, int scale_d) {
  asm volatile("{\n.reg .pred p;\n.reg .b64 da, db;\n"
    "mov.b64 da, {%128, %131};\nmov.b64 db, {%129, %132};\n"
    "setp.ne.b32 p, %130, 0;\n"
    "wgmma.mma_async.sync.aligned.m64n256k16.f32.bf16.bf16 "
    "{%0, %1, %2, %3, %4, %5, %6, %7, %8, %9, %10, %11, %12, %13, %14, %15, "
    "%16, %17, %18, %19, %20, %21, %22, %23, %24, %25, %26, %27, %28, %29, %30, %31, "
    "%32, %33, %34, %35, %36, %37, %38, %39, %40, %41, %42, %43, %44, %45, %46, %47, "
    "%48, %49, %50, %51, %52, %53, %54, %55, %56, %57, %58, %59, %60, %61, %62, %63, "
    "%64, %65, %66, %67, %68, %69, %70, %71, %72, %73, %74, %75, %76, %77, %78, %79, "
    "%80, %81, %82, %83, %84, %85, %86, %87, %88, %89, %90, %91, %92, %93, %94, %95, "
    "%96, %97, %98, %99, %100, %101, %102, %103, %104, %105, %106, %107, %108, %109, %110, %111, "
    "%112, %113, %114, %115, %116, %117, %118, %119, %120, %121, %122, %123, %124, %125, %126, %127}, "
    "da, db, p, 1, 1, 0, 1;\n}\n"
    : "+f"(d[0]), "+f"(d[1]), "+f"(d[2]), "+f"(d[3]), "+f"(d[4]), "+f"(d[5]), "+f"(d[6]), "+f"(d[7]),
      "+f"(d[8]), "+f"(d[9]), "+f"(d[10]), "+f"(d[11]), "+f"(d[12]), "+f"(d[13]), "+f"(d[14]), "+f"(d[15]),
      "+f"(d[16]), "+f"(d[17]), "+f"(d[18]), "+f"(d[19]), "+f"(d[20]), "+f"(d[21]), "+f"(d[22]), "+f"(d[23]),
      "+f"(d[24]), "+f"(d[25]), "+f"(d[26]), "+f"(d[27]), "+f"(d[28]), "+f"(d[29]), "+f"(d[30]), "+f"(d[31]),
      "+f"(d[32]), "+f"(d[33]), "+f"(d[34]), "+f"(d[35]), "+f"(d[36]), "+f"(d[37]), "+f"(d[38]), "+f"(d[39]),
      "+f"(d[40]), "+f"(d[41]), "+f"(d[42]), "+f"(d[43]), "+f"(d[44]), "+f"(d[45]), "+f"(d[46]), "+f"(d[47]),
      "+f"(d[48]), "+f"(d[49]), "+f"(d[50]), "+f"(d[51]), "+f"(d[52]), "+f"(d[53]), "+f"(d[54]), "+f"(d[55]),
      "+f"(d[56]), "+f"(d[57]), "+f"(d[58]), "+f"(d[59]), "+f"(d[60]), "+f"(d[61]), "+f"(d[62]), "+f"(d[63]),
      "+f"(d[64]), "+f"(d[65]), "+f"(d[66]), "+f"(d[67]), "+f"(d[68]), "+f"(d[69]), "+f"(d[70]), "+f"(d[71]),
      "+f"(d[72]), "+f"(d[73]), "+f"(d[74]), "+f"(d[75]), "+f"(d[76]), "+f"(d[77]), "+f"(d[78]), "+f"(d[79]),
      "+f"(d[80]), "+f"(d[81]), "+f"(d[82]), "+f"(d[83]), "+f"(d[84]), "+f"(d[85]), "+f"(d[86]), "+f"(d[87]),
      "+f"(d[88]), "+f"(d[89]), "+f"(d[90]), "+f"(d[91]), "+f"(d[92]), "+f"(d[93]), "+f"(d[94]), "+f"(d[95]),
      "+f"(d[96]), "+f"(d[97]), "+f"(d[98]), "+f"(d[99]), "+f"(d[100]), "+f"(d[101]), "+f"(d[102]), "+f"(d[103]),
      "+f"(d[104]), "+f"(d[105]), "+f"(d[106]), "+f"(d[107]), "+f"(d[108]), "+f"(d[109]), "+f"(d[110]), "+f"(d[111]),
      "+f"(d[112]), "+f"(d[113]), "+f"(d[114]), "+f"(d[115]), "+f"(d[116]), "+f"(d[117]), "+f"(d[118]), "+f"(d[119]),
      "+f"(d[120]), "+f"(d[121]), "+f"(d[122]), "+f"(d[123]), "+f"(d[124]), "+f"(d[125]), "+f"(d[126]), "+f"(d[127])
    : "r"(da), "r"(db), "r"(scale_d), "n"(AHI), "n"(BHI));
}
__device__ __forceinline__ void wgmma6_rs_n24_t1(float (&d)[12], uint32_t a0, uint32_t a1, uint32_t a2, uint32_t a3, uint64_t db, int scale_d) {
  asm volatile("{\n.reg .pred p;\n"
    "setp.ne.b32 p, %17, 0;\n"
    "wgmma.mma_async.sync.aligned.m64n24k16.f32.bf16.bf16 "
    "{%0, %1, %2, %3, %4, %5, %6, %7, %8, %9, %10, %11}, "
    "{%12, %13, %14, %15}, %16, p, 1, 1, 1;\n}\n"
    : "+f"(d[0]), "+f"(d[1]), "+f"(d[2]), "+f"(d[3]), "+f"(d[4]), "+f"(d[5]), "+f"(d[6]), "+f"(d[7]),
      "+f"(d[8]), "+f"(d[9]), "+f"(d[10]), "+f"(d[11])
    : "r"(a0), "r"(a1), "r"(a2), "r"(a3), "l"(db), "r"(scale_d));
}
__device__ __forceinline__ void wgmma6_rs_n64_t0(float (&d)[32], uint32_t a0, uint32_t a1, uint32_t a2, uint32_t a3, uint64_t db, int scale_d) {
  asm volatile("{\n.reg .pred p;\n"
    "setp.ne.b32 p, %37, 0;\n"
    "wgmma.mma_async.sync.aligned.m64n64k16.f32.bf16.bf16 "
    "{%0, %1, %2, %3, %4, %5, %6, %7, %8, %9, %10, %11, %12, %13, %14, %15, "
    "%16, %17, %18, %19, %20, %21, %22, %23, %24, %25, %26, %27, %28, %29, %30, %31}, "
    "{%32, %33, %34, %35}, %36, p, 1, 1, 0;\n}\n"
    : "+f"(d[0]), "+f"(d[1]), "+f"(d[2]), "+f"(d[3]), "+f"(d[4]), "+f"(d[5]), "+f"(d[6]), "+f"(d[7]),
      "+f"(d[8]), "+f"(d[9]), "+f"(d[10]), "+f"(d[11]), "+f"(d[12]), "+f"(d[13]), "+f"(d[14]), "+f"(d[15]),
      "+f"(d[16]), "+f"(d[17]), "+f"(d[18]), "+f"(d[19]), "+f"(d[20]), "+f"(d[21]), "+f"(d[22]), "+f"(d[23]),
      "+f"(d[24]), "+f"(d[25]), "+f"(d[26]), "+f"(d[27]), "+f"(d[28]), "+f"(d[29]), "+f"(d[30]), "+f"(d[31])
    : "r"(a0), "r"(a1), "r"(a2), "r"(a3), "l"(db), "r"(scale_d));
}
__device__ __forceinline__ void wgmma6_ss_n80_t1(float (&d)[40], uint64_t da, uint64_t db, int scale_d) {
  asm volatile("{\n.reg .pred p;\n"
    "setp.ne.b32 p, %42, 0;\n"
    "wgmma.mma_async.sync.aligned.m64n80k16.f32.bf16.bf16 "
    "{%0, %1, %2, %3, %4, %5, %6, %7, %8, %9, %10, %11, %12, %13, %14, %15, "
    "%16, %17, %18, %19, %20, %21, %22, %23, %24, %25, %26, %27, %28, %29, %30, %31, "
    "%32, %33, %34, %35, %36, %37, %38, %39}, "
    "%40, %41, p, 1, 1, 0, 1;\n}\n"
    : "+f"(d[0]), "+f"(d[1]), "+f"(d[2]), "+f"(d[3]), "+f"(d[4]), "+f"(d[5]), "+f"(d[6]), "+f"(d[7]),
      "+f"(d[8]), "+f"(d[9]), "+f"(d[10]), "+f"(d[11]), "+f"(d[12]), "+f"(d[13]), "+f"(d[14]), "+f"(d[15]),
      "+f"(d[16]), "+f"(d[17]), "+f"(d[18]), "+f"(d[19]), "+f"(d[20]), "+f"(d[21]), "+f"(d[22]), "+f"(d[23]),
      "+f"(d[24]), "+f"(d[25]), "+f"(d[26]), "+f"(d[27]), "+f"(d[28]), "+f"(d[29]), "+f"(d[30]), "+f"(d[31]),
      "+f"(d[32]), "+f"(d[33]), "+f"(d[34]), "+f"(d[35]), "+f"(d[36]), "+f"(d[37]), "+f"(d[38]), "+f"(d[39])
    : "l"(da), "l"(db), "r"(scale_d));
}
__device__ __forceinline__ void wgmma6_ss_n144_t1(float (&d)[72], uint64_t da, uint64_t db, int scale_d) {
  asm volatile("{\n.reg .pred p;\n"
    "setp.ne.b32 p, %74, 0;\n"
    "wgmma.mma_async.sync.aligned.m64n144k16.f32.bf16.bf16 "
    "{%0, %1, %2, %3, %4, %5, %6, %7, %8, %9, %10, %11, %12, %13, %14, %15, "
    "%16, %17, %18, %19, %20, %21, %22, %23, %24, %25, %26, %27, %28, %29, %30, %31, "
    "%32, %33, %34, %35, %36, %37, %38, %39, %40, %41, %42, %43, %44, %45, %46, %47, "
    "%48, %49, %50, %51, %52, %53, %54, %55, %56, %57, %58, %59, %60, %61, %62, %63, "
    "%64, %65, %66, %67, %68, %69, %70, %71}, "
    "%72, %73, p, 1, 1, 0, 1;\n}\n"
    : "+f"(d[0]), "+f"(d[1]), "+f"(d[2]), "+f"(d[3]), "+f"(d[4]), "+f"(d[5]), "+f"(d[6]), "+f"(d[7]),
      "+f"(d[8]), "+f"(d[9]), "+f"(d[10]), "+f"(d[11]), "+f"(d[12]), "+f"(d[13]), "+f"(d[14]), "+f"(d[15]),
      "+f"(d[16]), "+f"(d[17]), "+f"(d[18]), "+f"(d[19]), "+f"(d[20]), "+f"(d[21]), "+f"(d[22]), "+f"(d[23]),
      "+f"(d[24]), "+f"(d[25]), "+f"(d[26]), "+f"(d[27]), "+f"(d[28]), "+f"(d[29]), "+f"(d[30]), "+f"(d[31]),
      "+f"(d[32]), "+f"(d[33]), "+f"(d[34]), "+f"(d[35]), "+f"(d[36]), "+f"(d[37]), "+f"(d[38]), "+f"(d[39]),
      "+f"(d[40]), "+f"(d[41]), "+f"(d[42]), "+f"(d[43]), "+f"(d[44]), "+f"(d[45]), "+f"(d[46]), "+f"(d[47]),
      "+f"(d[48]), "+f"(d[49]), "+f"(d[50]), "+f"(d[51]), "+f"(d[52]), "+f"(d[53]), "+f"(d[54]), "+f"(d[55]),
      "+f"(d[56]), "+f"(d[57]), "+f"(d[58]), "+f"(d[59]), "+f"(d[60]), "+f"(d[61]), "+f"(d[62]), "+f"(d[63]),
      "+f"(d[64]), "+f"(d[65]), "+f"(d[66]), "+f"(d[67]), "+f"(d[68]), "+f"(d[69]), "+f"(d[70]), "+f"(d[71])
    : "l"(da), "l"(db), "r"(scale_d));
}
__device__ __forceinline__ void wgmma6_ss_n256_t1(float (&d)[128], uint64_t da, uint64_t db, int scale_d) {
  asm volatile("{\n.reg .pred p;\n"
    "setp.ne.b32 p, %130, 0;\n"
    "wgmma.mma_async.sync.aligned.m64n256k16.f32.bf16.bf16 "
    "{%0, %1, %2, %3, %4, %5, %6, %7, %8, %9, %10, %11, %12, %13, %14, %15, "
    "%16, %17, %18, %19, %20, %21, %22, %23, %24, %25, %26, %27, %28, %29, %30, %31, "
    "%32, %33, %34, %35, %36, %37, %38, %39, %40, %41, %42, %43, %44, %45, %46, %47, "
    "%48, %49, %50, %51, %52, %53, %54, %55, %56, %57, %58, %59, %60, %61, %62, %63, "
    "%64, %65, %66, %67, %68, %69, %70, %71, %72, %73, %74, %75, %76, %77, %78, %79, "
    "%80, %81, %82, %83, %84, %85, %86, %87, %88, %89, %90, %91, %92, %93, %94, %95, "
    "%96, %97, %98, %99, %100, %101, %102, %103, %104, %105, %106, %107, %108, %109, %110, %111, "
    "%112, %113, %114, %115, %116, %117, %118, %119, %120, %121, %122, %123, %124, %125, %126, %127}, "
    "%128, %129, p, 1, 1, 0, 1;\n}\n"
    : "+f"(d[0]), "+f"(d[1]), "+f"(d[2]), "+f"(d[3]), "+f"(d[4]), "+f"(d[5]), "+f"(d[6]), "+f"(d[7]),
      "+f"(d[8]), "+f"(d[9]), "+f"(d[10]), "+f"(d[11]), "+f"(d[12]), "+f"(d[13]), "+f"(d[14]), "+f"(d[15]),
      "+f"(d[16]), "+f"(d[17]), "+f"(d[18]), "+f"(d[19]), "+f"(d[20]), "+f"(d[21]), "+f"(d[22]), "+f"(d[23]),
      "+f"(d[24]), "+f"(d[25]), "+f"(d[26]), "+f"(d[27]), "+f"(d[28]), "+f"(d[29]), "+f"(d[30]), "+f"(d[31]),
      "+f"(d[32]), "+f"(d[33]), "+f"(d[34]), "+f"(d[35]), "+f"(d[36]), "+f"(d[37]), "+f"(d[38]), "+f"(d[39]),
      "+f"(d[40]), "+f"(d[41]), "+f"(d[42]), "+f"(d[43]), "+f"(d[44]), "+f"(d[45]), "+f"(d[46]), "+f"(d[47]),
      "+f"(d[48]), "+f"(d[49]), "+f"(d[50]), "+f"(d[51]), "+f"(d[52]), "+f"(d[53]), "+f"(d[54]), "+f"(d[55]),
      "+f"(d[56]), "+f"(d[57]), "+f"(d[58]), "+f"(d[59]), "+f"(d[60]), "+f"(d[61]), "+f"(d[62]), "+f"(d[63]),
      "+f"(d[64]), "+f"(d[65]), "+f"(d[66]), "+f"(d[67]), "+f"(d[68]), "+f"(d[69]), "+f"(d[70]), "+f"(d[71]),
      "+f"(d[72]), "+f"(d[73]), "+f"(d[74]), "+f"(d[75]), "+f"(d[76]), "+f"(d[77]), "+f"(d[78]), "+f"(d[79]),
      "+f"(d[80]), "+f"(d[81]), "+f"(d[82]), "+f"(d[83]), "+f"(d[84]), "+f"(d[85]), "+f"(d[86]), "+f"(d[87]),
      "+f"(d[88]), "+f"(d[89]), "+f"(d[90]), "+f"(d[91]), "+f"(d[92]), "+f"(d[93]), "+f"(d[94]), "+f"(d[95]),
      "+f"(d[96]), "+f"(d[97]), "+f"(d[98]), "+f"(d[99]), "+f"(d[100]), "+f"(d[101]), "+f"(d[102]), "+f"(d[103]),
      "+f"(d[104]), "+f"(d[105]), "+f"(d[106]), "+f"(d[107]), "+f"(d[108]), "+f"(d[109]), "+f"(d[110]), "+f"(d[111]),
      "+f"(d[112]), "+f"(d[113]), "+f"(d[114]), "+f"(d[115]), "+f"(d[116]), "+f"(d[117]), "+f"(d[118]), "+f"(d[119]),
      "+f"(d[120]), "+f"(d[121]), "+f"(d[122]), "+f"(d[123]), "+f"(d[124]), "+f"(d[125]), "+f"(d[126]), "+f"(d[127])
    : "l"(da), "l"(db), "r"(scale_d));
}

__device__ __forceinline__ void wg_fence() { asm volatile("wgmma.fence.sync.aligned;" ::: "memory"); }
__device__ __forceinline__ void wg_commit() { asm volatile("wgmma.commit_group.sync.aligned;" ::: "memory"); }
template <int N> __device__ __forceinline__ void wg_wait() { asm volatile("wgmma.wait_group.sync.aligned %0;" ::"n"(N) : "memory"); }
__host__ __device__ constexpr uint32_t dlo(uint32_t off, uint32_t lbo) { return (off >> 4) | ((lbo >> 4) << 16); }
__host__ __device__ constexpr uint32_t dhi(uint32_t sbo, uint32_t swz) { return (sbo >> 4) | (swz << 30); }
constexpr uint32_t HI_X = dhi(512, 2), HI_W = dhi(1024, 1), HI_A2 = dhi(256, 0), HI_K = dhi(640, 0), HI_V = dhi(128, 0), HI_T = dhi(256, 0);
constexpr uint32_t QB0 = dlo(8192, 2048), QB1 = QB0 + 384, QT1 = 48;
__device__ __forceinline__ float ex2(float x) { float y; asm volatile("ex2.approx.ftz.f32 %0, %1;" : "=f"(y) : "f"(x)); return y; }
template <uint32_t HI> __device__ __forceinline__ uint64_t mkdesc(uint32_t lo) {
    uint64_t d;
    asm("mov.b64 %0, {%1, %2};" : "=l"(d) : "r"(lo), "n"(HI));
    return d;
}
__device__ __forceinline__ float sel(int p, float a, float b) {
    float y;
    asm("{\n.reg .pred q;\nsetp.ne.s32 q, %3, 0;\nselp.f32 %0, %1, %2, q;\n}" : "=f"(y) : "f"(a), "f"(b), "r"(p));
    return y;
}
__device__ __forceinline__ float rcp_fast(float x) { float y; asm("rcp.approx.ftz.f32 %0, %1;" : "=f"(y) : "f"(x)); return y; }
__device__ __forceinline__ float tanh_fast(float x) { float y; asm("tanh.approx.f32 %0, %1;" : "=f"(y) : "f"(x)); return y; }
__device__ __forceinline__ uint32_t pack(float lo, float hi) { uint32_t y; asm("cvt.rn.bf16x2.f32 %0, %1, %2;" : "=r"(y) : "f"(hi), "f"(lo)); return y; }
template <int N> __device__ __forceinline__ void fence_regs(float (&d)[N]) {
#pragma unroll
    for (int i = 0; i < N; i++) asm volatile("" : "+f"(d[i])::"memory");
}
template <int N> __device__ __forceinline__ void fence_regs(uint32_t (&d)[N]) {
#pragma unroll
    for (int i = 0; i < N; i++) asm volatile("" : "+r"(d[i])::"memory");
}
template <int N> __device__ __forceinline__ void undef_regs(float (&d)[N]) {
#pragma unroll
    for (int i = 0; i < N; i++) asm volatile("" : "=f"(d[i]));
}
__device__ __forceinline__ void mbar_init(uint32_t bar, uint32_t cnt) { asm volatile("mbarrier.init.shared::cta.b64 [%0], %1;" ::"r"(bar), "r"(cnt) : "memory"); }
__device__ __forceinline__ void mbar_expect_tx(uint32_t bar, uint32_t bytes) { asm volatile("mbarrier.arrive.expect_tx.shared::cta.b64 _, [%0], %1;" ::"r"(bar), "r"(bytes) : "memory"); }
__device__ __forceinline__ void mbar_arrive(uint32_t bar) { asm volatile("mbarrier.arrive.shared::cta.b64 _, [%0];" ::"r"(bar) : "memory"); }
__device__ __forceinline__ void mbar_arrive_cluster(uint32_t bar, uint32_t cta) {
    asm volatile("{\n.reg .b32 ra;\nmapa.shared::cluster.u32 ra, %0, %1;\nmbarrier.arrive.shared::cluster.b64 _, [ra];\n}" ::"r"(bar), "r"(cta) : "memory");
}
__device__ __forceinline__ void mbar_wait(uint32_t bar, uint32_t parity) {
    asm volatile(
        "{\n.reg .pred p;\n.reg .u32 n;\n"
        "mbarrier.try_wait.parity.shared::cta.b64 p, [%0], %1;\n"
        "@p bra.uni LAB_DONE;\n"
        "mov.u32 n, 0;\n"
        "LAB_WAIT:\n"
        "mbarrier.try_wait.parity.shared::cta.b64 p, [%0], %1, 1000;\n"
        "@p bra.uni LAB_DONE;\n"
        "add.u32 n, n, 1;\n"
        "setp.ge.u32 p, n, 0x400000;\n"
        "@p trap;\n"
        "bra.uni LAB_WAIT;\n"
        "LAB_DONE:\n}" ::"r"(bar), "r"(parity) : "memory");
}
__device__ __forceinline__ void flag_wait(const uint32_t* p, uint32_t target) {
    asm volatile(
        "{\n.reg .pred p;\n.reg .u32 n;\n.reg .s32 v;\n"
        "mov.u32 n, 0;\n"
        "LAB_WAIT:\n"
        "ld.acquire.gpu.global.s32 v, [%0];\n"
        "sub.s32 v, v, %1;\n"
        "setp.ge.s32 p, v, 0;\n"
        "@p bra.uni LAB_DONE;\n"
        "add.u32 n, n, 1;\n"
        "setp.ge.u32 p, n, 0x800000;\n"
        "@p trap;\n"
        "bra.uni LAB_WAIT;\n"
        "LAB_DONE:\n}" ::"l"(p), "r"(target) : "memory");
}
__device__ __forceinline__ uint32_t flag_wait_bits(const uint32_t* p, uint32_t base, uint32_t mask) {
    uint32_t v;
    asm volatile(
        "{\n.reg .pred p;\n.reg .u32 n, t;\n"
        "mov.u32 n, 0;\n"
        "LAB_WAIT:\n"
        "ld.acquire.gpu.global.u32 %0, [%1];\n"
        "sub.u32 %0, %0, %2;\n"
        "and.b32 t, %0, %3;\n"
        "setp.ne.u32 p, t, 0;\n"
        "@p bra.uni LAB_DONE;\n"
        "add.u32 n, n, 1;\n"
        "setp.ge.u32 p, n, 0x800000;\n"
        "@p trap;\n"
        "bra.uni LAB_WAIT;\n"
        "LAB_DONE:\n}" : "=&r"(v) : "l"(p), "r"(base), "r"(mask) : "memory");
    return v;
}
__device__ __forceinline__ void flag_add(uint32_t* p) { asm volatile("red.release.gpu.global.add.u32 [%0], 1;" ::"l"(p) : "memory"); }
__device__ __forceinline__ void flag_addv(uint32_t* p, uint32_t v) { asm volatile("red.release.gpu.global.add.u32 [%0], %1;" ::"l"(p), "r"(v) : "memory"); }
__device__ __forceinline__ void fence_async_global() { asm volatile("fence.proxy.async.global;" ::: "memory"); }
__device__ __forceinline__ void fence_async_shared() { asm volatile("fence.proxy.async.shared::cta;" ::: "memory"); }
__device__ __forceinline__ bool elect_one() {
    uint32_t p;
    asm volatile("{\n.reg .pred p;\nelect.sync _|p, 0xffffffff;\nselp.u32 %0, 1, 0, p;\n}" : "=r"(p));
    return p != 0;
}
__device__ __forceinline__ uint32_t mbar_test(uint32_t bar, uint32_t parity) {
    uint32_t p;
    asm volatile("{\n.reg .pred p;\nmbarrier.test_wait.parity.shared::cta.b64 p, [%1], %2;\nselp.u32 %0, 1, 0, p;\n}" : "=r"(p) : "r"(bar), "r"(parity) : "memory");
    return p;
}
__device__ __forceinline__ void mbar_wait_unless(uint32_t done, uint32_t bar, uint32_t parity) {
    asm volatile(
        "{\n.reg .pred p;\n.reg .u32 n;\n"
        "setp.ne.u32 p, %2, 0;\n"
        "@p bra.uni LAB_DONE;\n"
        "mov.u32 n, 0;\n"
        "LAB_WAIT:\n"
        "mbarrier.try_wait.parity.shared::cta.b64 p, [%0], %1, 1000;\n"
        "@p bra.uni LAB_DONE;\n"
        "add.u32 n, n, 1;\n"
        "setp.ge.u32 p, n, 0x400000;\n"
        "@p trap;\n"
        "bra.uni LAB_WAIT;\n"
        "LAB_DONE:\n}" ::"r"(bar), "r"(parity), "r"(done) : "memory");
}
__device__ __forceinline__ void bulk_s2g(void* dst, uint32_t src, uint32_t bytes) {
    asm volatile("cp.async.bulk.global.shared::cta.bulk_group [%0], [%1], %2;" ::"l"(dst), "r"(src), "r"(bytes) : "memory");
}
__device__ __forceinline__ void bulk_s2c(uint32_t addr, uint32_t bytes, uint32_t bar, uint32_t cta) {
    asm volatile("{\n.reg .b32 d, b;\nmapa.shared::cluster.u32 d, %0, %3;\nmapa.shared::cluster.u32 b, %2, %3;\n"
                 "cp.async.bulk.shared::cluster.shared::cta.mbarrier::complete_tx::bytes [d], [%0], %1, [b];\n}"
                 ::"r"(addr), "r"(bytes), "r"(bar), "r"(cta) : "memory");
}
__device__ __forceinline__ void sts32(uint32_t a, uint32_t v) { asm volatile("st.shared.u32 [%0], %1;" ::"r"(a), "r"(v) : "memory"); }
__device__ __forceinline__ void sts128(uint32_t a, uint32_t x, uint32_t y, uint32_t z, uint32_t w) { asm volatile("st.shared.v4.u32 [%0], {%1, %2, %3, %4};" ::"r"(a), "r"(x), "r"(y), "r"(z), "r"(w) : "memory"); }
__device__ __forceinline__ void stsm4(uint32_t a, uint32_t r0, uint32_t r1, uint32_t r2, uint32_t r3) {
    asm volatile("stmatrix.sync.aligned.m8n8.x4.shared.b16 [%0], {%1, %2, %3, %4};" ::"r"(a), "r"(r0), "r"(r1), "r"(r2), "r"(r3) : "memory");
}
__device__ __forceinline__ void ldsm4(uint32_t* r, uint32_t a) {
    asm volatile("ldmatrix.sync.aligned.m8n8.x4.shared.b16 {%0, %1, %2, %3}, [%4];" : "=r"(r[0]), "=r"(r[1]), "=r"(r[2]), "=r"(r[3]) : "r"(a) : "memory");
}
__device__ __forceinline__ uint32_t lds32(uint32_t a) { uint32_t v; asm volatile("ld.shared.u32 %0, [%1];" : "=r"(v) : "r"(a) : "memory"); return v; }
__device__ __forceinline__ void tma_2d(uint32_t dst, const CUtensorMap* tm, int c0, int c1, uint32_t bar) {
    asm volatile("cp.async.bulk.tensor.2d.shared::cluster.global.mbarrier::complete_tx::bytes [%0], [%1, {%3, %4}], [%2];"
                 ::"r"(dst), "l"(tm), "r"(bar), "r"(c0), "r"(c1) : "memory");
}
__device__ __forceinline__ void tma_2d_mc(uint32_t dst, const CUtensorMap* tm, int c0, int c1, uint32_t bar) {
    asm volatile("cp.async.bulk.tensor.2d.shared::cluster.global.mbarrier::complete_tx::bytes.multicast::cluster [%0], [%1, {%3, %4}], [%2], %5;"
                 ::"r"(dst), "l"(tm), "r"(bar), "r"(c0), "r"(c1), "h"((uint16_t)3) : "memory");
}
__device__ __forceinline__ void tma_3d_mc(uint32_t dst, const CUtensorMap* tm, int c0, int c1, int c2, uint32_t bar) {
    asm volatile("cp.async.bulk.tensor.3d.shared::cluster.global.mbarrier::complete_tx::bytes.multicast::cluster [%0], [%1, {%3, %4, %5}], [%2], %6;"
                 ::"r"(dst), "l"(tm), "r"(bar), "r"(c0), "r"(c1), "r"(c2), "h"((uint16_t)3) : "memory");
}
__device__ __forceinline__ void bulk_g2s(uint32_t dst, const void* src, uint32_t bytes, uint32_t bar) {
    asm volatile("cp.async.bulk.shared::cluster.global.mbarrier::complete_tx::bytes [%0], [%1], %2, [%3];"
                 ::"r"(dst), "l"(src), "r"(bytes), "r"(bar) : "memory");
}
__device__ __forceinline__ void bulk_g2s_mc(uint32_t dst, const void* src, uint32_t bytes, uint32_t bar) {
    asm volatile("cp.async.bulk.shared::cluster.global.mbarrier::complete_tx::bytes.multicast::cluster [%0], [%1], %2, [%3], %4;"
                 ::"r"(dst), "l"(src), "r"(bytes), "r"(bar), "h"((uint16_t)3) : "memory");
}
__device__ __forceinline__ void mma_16816(float* d, uint32_t a0, uint32_t a1, uint32_t a2, uint32_t a3, uint32_t b0, uint32_t b1) {
    asm volatile("mma.sync.aligned.m16n8k16.row.col.f32.bf16.bf16.f32 {%0,%1,%2,%3}, {%4,%5,%6,%7}, {%8,%9}, {%0,%1,%2,%3};"
                 : "+f"(d[0]), "+f"(d[1]), "+f"(d[2]), "+f"(d[3]) : "r"(a0), "r"(a1), "r"(a2), "r"(a3), "r"(b0), "r"(b1));
}
__device__ __forceinline__ uint32_t movm_t(uint32_t a) { uint32_t d; asm volatile("movmatrix.sync.aligned.m8n8.trans.b16 %0, %1;" : "=r"(d) : "r"(a)); return d; }
__device__ __forceinline__ uint32_t ldg32(const uint8_t* p) { uint32_t v; asm volatile("ld.global.u32 %0, [%1];" : "=r"(v) : "l"(p) : "memory"); return v; }
__device__ __forceinline__ void stg32(uint8_t* p, uint32_t v) { asm volatile("st.global.u32 [%0], %1;" ::"l"(p), "r"(v) : "memory"); }
#define PROF(i) do {} while (0)
#define TRACE() do {} while (0)
#define PROFX(w, i) do {} while (0)

struct Ring {
    uint32_t slot;
    uint32_t phase;
    __device__ __forceinline__ void next() { if (++slot == NSTAGE) { slot = 0; phase ^= 1; } }
};

__device__ __forceinline__ void load_q(uint32_t (&q)[8], uint32_t qa, int lane) {
    q[0] = lds32(qa + lane * 4);       q[1] = lds32(qa + lane * 4 + 256);
    q[2] = lds32(qa + lane * 4 + 128); q[3] = lds32(qa + lane * 4 + 384);
    const uint32_t t0 = lds32(qa + 512 + (lane & ~3)), t1 = lds32(qa + 544 + (lane & ~3));
    q[4] = (lane & 3) == 2 ? t0 : 0u;  q[5] = (lane & 3) == 2 ? t1 : 0u;
}

__device__ __forceinline__ bool norm_o(uint32_t (&w)[6], const float (&o)[12], int lane, uint32_t gaddr) {
    const float l0 = __shfl_sync(0xffffffffu, o[8], (lane & ~3) | 1);
    const float l1 = __shfl_sync(0xffffffffu, o[10], (lane & ~3) | 1);
    const float i0 = rcp_fast(l0) * __uint_as_float(lds32(gaddr)), i1 = rcp_fast(l1) * __uint_as_float(lds32(gaddr + 32));
    uint32_t big = 0;
#pragma unroll
    for (int b = 0; b < 3; b++) {
        w[2 * b] = pack(o[4 * b] * i0, o[4 * b + 1] * i0);
        w[2 * b + 1] = pack(o[4 * b + 2] * i1, o[4 * b + 3] * i1);
        if (b == 2 && (lane & 3) != 0) w[4] = w[5] = 0u;
        big |= ((w[2 * b] & 0x7F807F80u) + 0x00800080u) | ((w[2 * b + 1] & 0x7F807F80u) + 0x00800080u);
    }
    const bool ok = fminf(l0, l1) >= 0x1p-30f && l0 <= 0x1p100f && l1 <= 0x1p100f && (big & 0x80008000u) == 0;
    return !__all_sync(0xffffffffu, ok);
}

__device__ __forceinline__ void attn_true_max(float (&o)[12], const uint32_t (&q)[8], const uint8_t* kv) {
    float m0 = -INFINITY, m1 = -INFINITY;
#pragma unroll
    for (int i = 0; i < 12; i++) o[i] = 0.f;
#pragma unroll 1
    for (int kb = 0; kb < SEQ / 16; kb++) {
        uint32_t t[2][5];
#pragma unroll
        for (int g = 0; g < 2; g++)
#pragma unroll
            for (int ch = 0; ch < 5; ch++) t[g][ch] = ldg32(kv + (kb * 2 + g) * 640 + ch * 128);
        float s[2][4];
#pragma unroll
        for (int g = 0; g < 2; g++) {
            s[g][0] = s[g][1] = s[g][2] = s[g][3] = 0.f;
            mma_16816(s[g], q[0], q[1], q[2], q[3], t[g][0], t[g][1]);
            mma_16816(s[g], q[4], q[5], 0u, 0u, t[g][4], 0u);
        }
        float x0 = fmaxf(fmaxf(s[0][0], s[0][1]), fmaxf(s[1][0], s[1][1]));
        float x1 = fmaxf(fmaxf(s[0][2], s[0][3]), fmaxf(s[1][2], s[1][3]));
        x0 = fmaxf(x0, __shfl_xor_sync(0xffffffffu, x0, 1)); x0 = fmaxf(x0, __shfl_xor_sync(0xffffffffu, x0, 2));
        x1 = fmaxf(x1, __shfl_xor_sync(0xffffffffu, x1, 1)); x1 = fmaxf(x1, __shfl_xor_sync(0xffffffffu, x1, 2));
        const float n0 = fmaxf(m0, x0), n1 = fmaxf(m1, x1);
        const float u0 = (n0 == -INFINITY) ? 0.f : n0, u1 = (n1 == -INFINITY) ? 0.f : n1;
        const float c0 = ex2(m0 - u0), c1 = ex2(m1 - u1);
        m0 = n0; m1 = n1;
#pragma unroll
        for (int b = 0; b < 3; b++) { o[4 * b] *= c0; o[4 * b + 1] *= c0; o[4 * b + 2] *= c1; o[4 * b + 3] *= c1; }
        const uint32_t a0 = pack(ex2(s[0][0] - u0), ex2(s[0][1] - u0)), a1 = pack(ex2(s[0][2] - u1), ex2(s[0][3] - u1));
        const uint32_t a2 = pack(ex2(s[1][0] - u0), ex2(s[1][1] - u0)), a3 = pack(ex2(s[1][2] - u1), ex2(s[1][3] - u1));
#pragma unroll
        for (int b = 0; b < 3; b++) mma_16816(&o[4 * b], a0, a1, a2, a3, movm_t(t[0][2 + b]), movm_t(t[1][2 + b]));
    }
}

__device__ __forceinline__ float geglu2(float g, float u) {
    const float p = fmaf(g * g, 0.044715f * 0.7978845608028654f, 0.7978845608028654f);
    const float th = tanh_fast(g * p);
    const float y = g * u;
    return fmaf(y, th, y);
}

struct Attn {
    float s[32];
    float o[12];
    uint32_t p[16];
    uint32_t q[8];
};

__global__ void __cluster_dims__(2, 1, 1) __launch_bounds__(384, 1)
fused_kernel(__nv_bfloat16* __restrict__ out, const __nv_bfloat16* __restrict__ x, const __nv_bfloat16* __restrict__ gate_w,
             const uint8_t* __restrict__ wqkv, const uint8_t* __restrict__ wgt, const uint8_t* __restrict__ wu,
             const __grid_constant__ CUtensorMap tm_x, const __grid_constant__ CUtensorMap tm_qkv,
             const __grid_constant__ CUtensorMap tm_qkv8,
             const __grid_constant__ CUtensorMap tm_wg, const __grid_constant__ CUtensorMap tm_wu,
             const __grid_constant__ CUtensorMap tm_wd, const __grid_constant__ CUtensorMap tm_wo,
             const __grid_constant__ CUtensorMap tm_wd16, const __grid_constant__ CUtensorMap tm_wo16) {
    extern __shared__ uint8_t smem_raw[];
    const uint32_t sb = __shfl_sync(0xffffffffu, ((uint32_t)__cvta_generic_to_shared(smem_raw) + 1023) & ~1023u, 0);
    const uint32_t bars = sb + OFF_BAR;
    const uint32_t bar_full = bars, bar_empty = bars + 64;
    const uint32_t bar_ev = bars + 128;
    const uint32_t bar_rdy = bars + 256;
    const uint32_t bar_ep = bars + 320, bar_gate = bars + 328;
    const uint32_t bar_st = bars + 336;
    const uint32_t bar_late = bars + 408;
    const uint32_t bar_px = bars + 416;
    const uint32_t bar_free = bars + 424;
    const uint32_t s_epoch = bars + 448, s_zero = bars + 452, s_order = bars + 464, s_gate = bars + 512;

    const int cta = blockIdx.x >= NCTA ? blockIdx.x : ((blockIdx.x & 14) << 3) | ((blockIdx.x >> 4) << 1) | (blockIdx.x & 1);
    const int rank = cta & 1;
    const int j = (cta >> 1) & 7;
    const int m = (cta >> 4) * 2 + rank;
    const int hf = j >> 2, nt = j & 3;
    const int warp = __shfl_sync(0xffffffffu, threadIdx.x >> 5, 0);
    const int lane = threadIdx.x & 31;
    const int wg = warp >> 2;

    auto prefetch_stages = [&](int n) {
        const int t = threadIdx.x;
        const int row = (t >> 3) * 16 + m, sel = t & 7;
        const uint8_t* p = sel < 6 ? wqkv + (size_t)row * (3 * DM * 2) + (sel >> 1) * (DM * 2) + j * 128 + (sel & 1) * 128
                                   : (sel == 7 ? wu : wgt) + (size_t)row * (FF * 2) + (j * 576 + 512) * 2;
        if (t < n * 16) asm volatile("prefetch.global.L2 [%0];" ::"l"(p));
        p = (const uint8_t*)x + (size_t)(m * 128 + j * 16 + (t & 15)) * (DM * 2) + (t >> 4) * 128;
        if (t < n * 8) asm volatile("prefetch.global.L2 [%0];" ::"l"(p));
    };
    const bool leader = elect_one();
    if (leader) {
        mbar_init(warp < 6 ? bar_full + warp * 8 : bar_empty + (warp - 6) * 8, warp < 6 ? 2 : 4);
        asm volatile("fence.mbarrier_init.release.cluster;" ::: "memory");
    }
    asm volatile("barrier.cluster.arrive.relaxed.aligned;" ::: "memory");
    if (cta < NCTA && wg < 2) prefetch_stages(4);
    if (warp != 8) {
        if (leader && warp < 8) {
            const uint32_t lo = (warp >= 4 && warp <= 6) ? 1 : 4, hi = warp == 6 ? 4 : lo;
            mbar_init(bar_ev + warp * 32, lo); mbar_init(bar_ev + warp * 32 + 8, lo);
            mbar_init(bar_ev + warp * 32 + 16, hi); mbar_init(bar_ev + warp * 32 + 24, hi);
            if (warp < 4) mbar_init(bar_late + warp * 8, 1);
            sts32(s_zero, 0u); sts32(s_zero + 4, 0u);
            asm volatile("fence.mbarrier_init.release.cluster;" ::: "memory");
        }
        asm volatile("bar.sync 1, 352;" ::: "memory");
    }
    asm volatile("barrier.cluster.wait.acquire.aligned;" ::: "memory");

    if (wg == 2) {
        asm volatile("setmaxnreg.dec.sync.aligned.u32 24;");
        if (cta >= NCTA) {
            if (warp == 9 && elect_one()) {
                const uint32_t ep = g_flags[FL_E + cta * 32] + 1;
                g_flags[FL_E + cta * 32] = ep;
                mbar_wait(bar_ev + 2 * 8, 0);
                mbar_wait(bar_ev + 10 * 8, 0);
                flag_add(&g_flags[FL_G + (cta - NCTA) * 32]);
#pragma unroll 1
                for (int i = 0; i < 2; i++) {
                    const int jx = (cta - NCTA) * 2 + i;
                    flag_wait(&g_flags[FL_KV + jx * 32 + 1], ep * 32);
                    fence_async_global();
                    mbar_expect_tx(bar_rdy + i * 8, 20480 + 16 * 4608);
#pragma unroll 1
                    for (int p = 0; p < 8; p++) bulk_g2s(sb + 40960 + (i * 8 + p) * 9216, g_q3 + (p * 16 + jx * 2) * 4608, 9216, bar_rdy + i * 8);
                    bulk_g2s(sb + i * 20480, g_kv + (size_t)(jx * 4 + 3) * HEAD_BYTES + 28 * 5120, 20480, bar_rdy + i * 8);
                }
#pragma unroll 1
                for (int i = 0; i < 2; i++) {
                    mbar_wait(bar_ev + i * 8, 0);
                    mbar_wait(bar_ev + (8 + i) * 8, 0);
                    flag_add(&g_flags[FL_KV + ((cta - NCTA) * 2 + i) * 32 + 2]);
                }
            }
        } else if (warp == 8) {
            if (elect_one()) {
                Ring r{0, 1};
                const int row0 = m * 128;
                const CUtensorMap* tw = rank ? &tm_wu : &tm_wg;
                PROFX(0, 40); PROFX(1, 40);
#pragma unroll 1
                for (int kk = 0; kk < 18; kk++) {
                    if (kk == 1) { PROFX(0, 41); PROFX(1, 41); }
                    if (kk == 6) { PROFX(0, 42); PROFX(1, 42); }
                    const uint32_t st = sb + r.slot * SLOT, fb = bar_full + r.slot * 8;
                    mbar_wait(bar_empty + r.slot * 8, r.phase);
                    mbar_arrive(fb);
                    mbar_expect_tx(fb, 8192 + 12288 + 8192 + 1536);
                    tma_2d(st + OFF_AX, &tm_x, kk * 32, row0, fb);
                    tma_3d_mc(st + 8192 + rank * 6144, &tm_qkv, j * 72, kk * 32 + rank * 16, 0, fb);
                    tma_3d_mc(st + OFF_TL + rank * 768, &tm_qkv8, j * 72 + 64, kk * 32 + rank * 16, 0, fb);
                    tma_2d_mc(st + rank * 4096, tw, j * 576 + 512, kk * 32, fb);
                    r.next();
                }
                int k0 = DM - NSTAGE * 32;
#pragma unroll 1
                for (int t = 0; t < 4; t++)
#pragma unroll 1
                    for (int kk = 0; kk < 18; kk++) {
                        const uint32_t st = sb + r.slot * SLOT, fb = bar_full + r.slot * 8;
                        mbar_wait(bar_empty + r.slot * 8, r.phase);
                        if (t == 0 && kk < 2) mbar_arrive(fb);
                        const bool have_x = kk < NSTAGE;
                        mbar_expect_tx(fb, have_x ? 16384 : 8192 + 16384);
                        tma_2d_mc(st + rank * 8192, tw, j * 576 + t * 128, k0, fb);
                        tma_2d_mc(st + rank * 8192 + 4096, tw, j * 576 + t * 128 + 64, k0, fb);
                        if (!have_x) tma_2d(st + OFF_AX, &tm_x, k0, row0, fb);
                        k0 += kk == 17 ? DM + 32 - NSTAGE * 32 : 32;
                        if (k0 >= DM) k0 -= DM;
                        r.next();
                    }
                const uint8_t* a2 = g_a2 + (size_t)m * A2_TILE;
                mbar_wait(bar_rdy + 4 * 8, 0);
#pragma unroll 1
                for (int n = 0; n < 48; n++) {
                    const int u = n >> 2, jj = n & 3;
                    const uint32_t st = sb + r.slot * SLOT, fb = bar_full + r.slot * 8;
                    mbar_wait(bar_empty + r.slot * 8, r.phase);
                    mbar_expect_tx(fb, 12288 + 12288 + STRIPB);
                    const int ks = (hf * 4 + jj) * 36 + u * 3;
#pragma unroll
                    for (int b = 0; b < 2; b++) tma_2d_mc(st + b * 6144 + rank * 3072, &tm_wd, nt * 128 + b * 64, ks * 16 + rank * 24, fb);
                    tma_2d_mc(st + 12288 + rank * 3072, &tm_wd16, 512 + nt * 16, ks * 16 + rank * 24, fb);
                    if (jj == 0) { mbar_wait(bar_rdy + ((3 * u + 2) >> 3) * 8, 0); fence_async_global(); }
                    bulk_g2s(st + OFF_A2, a2 + ks * 4096, 12288, fb);
                    r.next();
                }
#pragma unroll 1
                for (int n = 0; n < 4; n++) {
                    const uint32_t st = sb + r.slot * SLOT, fb = bar_full + r.slot * 8;
                    mbar_wait(bar_empty + r.slot * 8, r.phase);
                    mbar_expect_tx(fb, 12288 + 12288 + STRIPB);
                    const int pr = hf * 2 + (n & 1), head = (pr * 2 + rank) * 4 + (n >> 1);
#pragma unroll
                    for (int b = 0; b < 2; b++) tma_2d_mc(st + b * 6144 + rank * 3072, &tm_wo, nt * 128 + b * 64, head * 18, fb);
                    tma_2d_mc(st + 12288 + rank * 3072, &tm_wo16, 512 + nt * 16, head * 18, fb);
                    if (n == 0) { mbar_wait(bar_rdy + 5 * 8, 0); fence_async_global(); }
                    bulk_g2s(st + OFF_A2, a2 + (288 + ((n >> 1) * 4 + pr) * 3) * 4096, 12288, fb);
                    r.next();
                }
                mbar_expect_tx(bar_late, 4 * (6144 + STRIPB));
#pragma unroll 1
                for (int n = 0; n < 8; n++) {
                    const uint32_t st = sb + r.slot * SLOT, fb = bar_full + r.slot * 8;
                    mbar_wait(bar_empty + r.slot * 8, r.phase);
                    if (n >= 2) mbar_arrive(fb);
                    if (n < 4) mbar_expect_tx(fb, 12288 + 6144 + STRIPB);
                    const int head = ((n & 3) * 2 + rank) * 4 + 2 + (n >> 2);
                    tma_2d_mc(st + rank * 3072, &tm_wo, nt * 128 + hf * 64, head * 18, n < 4 ? fb : bar_late);
                    tma_2d_mc(st + 6144 + rank * 3072, &tm_wo16, 512 + nt * 16, head * 18, n < 4 ? fb : bar_late);
                    if (n < 4) bulk_g2s(st + OFF_A2, a2 + (288 + (8 + n) * 3) * 4096, 12288, fb);
                    r.next();
                }
                mbar_wait(bar_ep, 0);
                const uint32_t base = (lds32(s_epoch) - 1) * 0x04040404u;
                uint32_t todo = 0x04040404u, k = 2;
#pragma unroll 1
                while (todo) {
                    const uint32_t got = flag_wait_bits(&g_flags[FL_M + m * 64 + FM_LATE], base, todo) & todo;
                    fence_async_global();
#pragma unroll 1
                    for (int pr = 0; pr < 4; pr++)
                        if ((got >> (pr * 8)) & 4) {
                            sts32(s_order + k * 4, (2 + pr) * (SLOT >> 4));
                            mbar_expect_tx(bar_full + k * 8, 12288);
                            bulk_g2s(sb + k * SLOT + OFF_A2, a2 + (288 + (12 + pr) * 3) * 4096, 12288, bar_full + k * 8);
                            k++;
                        }
                    todo &= ~got;
                }
                PROFX(0, 50); PROFX(1, 50);
            }
        } else if (warp == 9) {
            if (elect_one()) {
                const uint32_t ep = g_flags[FL_E + cta * 32] + 1;
                g_flags[FL_E + cta * 32] = ep;
                sts32(s_epoch, ep);
                mbar_arrive(bar_ep);
                Ring r{0, 1};
                const uint8_t* kv = g_kv + (size_t)(j * 4) * HEAD_BYTES + rank * 2560;
                const int rot = (cta >> 4) * 4;
                uint32_t have = flag_wait_bits(&g_flags[FL_KV + j * 32], (ep - 1) * 0x44444444u, 4u << rot);
                fence_async_global();
#pragma unroll 1
                for (int it = 4; it < 124; it++) {
                    const uint32_t fb = bar_full + r.slot * 8;
                    if (it < 32 && !((have >> ((it + rot) & 28)) & 4)) {
                        have = flag_wait_bits(&g_flags[FL_KV + j * 32], (ep - 1) * 0x44444444u, 4u << ((it + rot) & 28));
                        fence_async_global();
                    }
                    if (it == 4) { PROFX(0, 37); PROFX(1, 37); }
                    if (it == 24) { flag_wait(&g_flags[FL_KV + j * 32 + 1], ep * 32); fence_async_global(); }
                    mbar_wait(bar_empty + r.slot * 8, r.phase);
                    mbar_expect_tx(fb, 5120);
                    bulk_g2s_mc(sb + r.slot * SLOT + OFF_KV + rank * 2560, kv + (it < 32 ? (it + rot) & 31 : it) * 5120, 2560, fb);
                    r.next();
                }
                flag_wait(&g_flags[FL_KV + j * 32 + 2], ep);
                mbar_arrive(bar_px);
                uint32_t* fr = &g_flags[FL_M + m * 64 + FM_R];
                mbar_wait(bar_ev + 6 * 8, 0);
                mbar_wait(bar_ev + 14 * 8, 0);
                PROFX(0, 51); PROFX(1, 51);
                flag_add(fr + j);
                PROFX(0, 52); PROFX(1, 52);
                flag_wait(fr + (j ^ 4), ep);
                PROFX(0, 53); PROFX(1, 53);
                mbar_arrive(bar_rdy + 6 * 8);
            }
        } else {
            const int w = warp - 10;
            if (elect_one()) {
                const uint32_t mine = 2 + rank * 2 + w, other = 2 + (rank ^ 1) * 2 + w;
                mbar_wait(bar_st + w * 8, 0);
                PROFX(w, 32);
                bulk_s2g(g_kv + (size_t)(j * 4) * HEAD_BYTES + (m * 16 + w * 8) * 640, sb + mine * SLOT + OFF_KV, 5120);
                asm volatile("cp.async.bulk.commit_group;" ::: "memory");
                mbar_arrive(bar_full + mine * 8);
                mbar_expect_tx(bar_full + other * 8, 5120);
#pragma unroll 1
                for (int i = 0; i < 2; i++) {
                    if (i == rank) {
                        mbar_wait(bar_empty + mine * 8, 0);
                        bulk_s2c(sb + mine * SLOT + OFF_KV, 5120, bar_full + mine * 8, rank ^ 1);
                    } else {
                        asm volatile("cp.async.bulk.wait_group 0;" ::: "memory");
                        flag_addv(&g_flags[FL_KV + j * 32], 1u << ((cta >> 4) * 4));
                    }
                }
                PROFX(w, 34);
                mbar_wait(bar_st + (2 + w) * 8, 0);
                bulk_s2g(g_q3 + cta * 4608 + w * 2304, sb + OFF_Q + 3 * 4608 + w * 2304, 2304);
#pragma unroll 1
                for (int h = 1; h < 4; h++) {
                    __nanosleep(500);
                    bulk_s2g(g_kv + (size_t)(j * 4 + h) * HEAD_BYTES + (m * 16 + w * 8) * 640, sb + (w * 3 + h - 1) * SLOT + OFF_GAP, 5120);
                    asm volatile("cp.async.bulk.commit_group;\ncp.async.bulk.wait_group 0;" ::: "memory");
                }
                mbar_arrive(bar_free + w * 8);
                flag_add(&g_flags[FL_KV + j * 32 + 1]);
                PROFX(w, 35);
            }
            __syncwarp();
            uint32_t* fm = &g_flags[FL_M + m * 64];
            mbar_wait(bar_ep, 0);
            const uint32_t ep = lds32(s_epoch);
            if (w == 1) {
                flag_wait(&g_flags[FL_G + (m >> 2) * 32], ep);
                const uint4 gv = __ldcg((const uint4*)(g_gate + m * 128) + lane);
                sts128(s_gate + lane * 16, gv.x, gv.y, gv.z, gv.w);
                __syncwarp();
                if (lane == 0) mbar_arrive(bar_gate);
            }
            if (elect_one()) {
#pragma unroll 1
                for (int i = 0; i < 6; i++) {
                    const int e = i == 0 ? 4 : i == 5 ? 5 : i - 1;
                    mbar_wait(bar_ev + (w * 8 + e) * 8, 0);
                    if (e < 3) {
                        uint8_t* hp = g_a2 + (size_t)m * A2_TILE + (j * 36 + e * 8) * 4096 + w * 2048;
#pragma unroll 1
                        for (int k = 0; k < 8; k++) {
                            const int g = (k * 11) >> 5;
                            bulk_s2g(hp + k * 4096, sb + (w * 3 + g) * SLOT + OFF_GAP + (k - g * 3) * 2048, 2048);
                        }
                        asm volatile("cp.async.bulk.commit_group;\ncp.async.bulk.wait_group 0;" ::: "memory");
                    }
                    uint32_t* fl = fm + FM_H + (e == 5 ? 5 : hf * 8 + e);
                    flag_add(fl);
                    if (w == 0) { flag_wait(fl, ep * (e == 5 ? 16 : 8)); mbar_arrive(bar_rdy + e * 8); }
                }
                mbar_wait(bar_ev + (w * 8 + 7) * 8, 0);
                PROFX(w, 48);
                flag_addv(fm + FM_LATE, 1u << ((j >> 1) * 8));
                PROFX(w, 49);
            }
        }
    } else {
        asm volatile("setmaxnreg.inc.sync.aligned.u32 240;");
        const int wq = warp & 3;
        const int c = lane & 3;
        const int tid = threadIdx.x & 127;
        const int grp = wg * 8 + wq * 2;
        const uint32_t sbd = (sb & 0x3FFFF) >> 4;
        uint32_t sd = sbd, pd = sbd, fb = bar_full, pb = bar_full, ph = 0;
#define STAGE_NEXT do { pd = sd; sd = (sd == sbd + (NSTAGE - 1) * (SLOT >> 4)) ? sbd : sd + (SLOT >> 4);           \
                        pb = fb; fb += 8; if (fb == bar_full + NSTAGE * 8) { fb = bar_full; ph ^= 1; } } while (0)
        auto release = [&]() { if (tid < 2) mbar_arrive_cluster(pb + 64, tid); };
        auto signal = [&](int e) { __syncwarp(); if (lane == 0) mbar_arrive(bar_ev + (wg * 8 + e) * 8); };
        if (cta >= NCTA) {
            PROF(0);
            {
                float wv[72];
#pragma unroll
                for (int i = 0; i < 9; i++) {
                    const uint4 t = __ldg((const uint4*)gate_w + (lane & 7) + i * 8);
                    const uint32_t u[4] = {t.x, t.y, t.z, t.w};
#pragma unroll
                    for (int e = 0; e < 4; e++) { wv[8 * i + 2 * e] = __uint_as_float(u[e] << 16); wv[8 * i + 2 * e + 1] = __uint_as_float(u[e] & 0xffff0000u); }
                }
                __nanosleep(1500);
#pragma unroll 1
                for (int b = 0; b < 8; b++) {
                    const int row = (cta - NCTA) * 512 + warp * 64 + b * 8 + (lane >> 3);
                    uint4 xa[2][9];
#pragma unroll
                    for (int r = 0; r < 2; r++)
#pragma unroll
                        for (int i = 0; i < 9; i++) xa[r][i] = __ldg((const uint4*)(x + (size_t)(row + r * 4) * DM) + (lane & 7) + i * 8);
#pragma unroll
                    for (int r = 0; r < 2; r++) {
                        float z = 0.f, y = 0.f;
#pragma unroll
                        for (int i = 0; i < 9; i++) {
                            const uint32_t u[4] = {xa[r][i].x, xa[r][i].y, xa[r][i].z, xa[r][i].w};
#pragma unroll
                            for (int e = 0; e < 4; e++) {
                                z = fmaf(__uint_as_float(u[e] << 16), wv[8 * i + 2 * e], z);
                                y = fmaf(__uint_as_float(u[e] & 0xffff0000u), wv[8 * i + 2 * e + 1], y);
                            }
                        }
                        z += y;
#pragma unroll
                        for (int d = 1; d < 8; d <<= 1) z += __shfl_xor_sync(0xffffffffu, z, d);
                        if ((lane & 7) == 0) g_gate[row + r * 4] = rcp_fast(1.f + ex2(-1.4426950408889634f * z));
                    }
                }
                signal(2);
                PROF(2);
            }
            float s0[64], s1[64], o[12];
            uint32_t p0[32], p1[32], q[8];
            q[6] = lds32(s_zero); q[7] = lds32(s_zero + 4);
#pragma unroll
            for (int i = 0; i < 12; i++) o[i] = 0.f;
            auto store_px = [&](int u) {
                const int src = ((u & 15) >> 1) * 16 + ((cta - NCTA) * 2 + (u >> 4)) * 2 + (u & 1);
                float4* dst = g_px + (size_t)(src * 2 + wg) * 3 * 128 + tid;
#pragma unroll
                for (int i = 0; i < 3; i++) __stcg(dst + i * 128, make_float4(o[4 * i], o[4 * i + 1], o[4 * i + 2], o[4 * i + 3]));
            };
            mbar_wait(bar_rdy, 0);
            PROF(1);
            load_q(q, sb + 40960 + warp * 576, lane);
            fence_regs(q); fence_regs(o);
            wg_fence();
            wgmma_rs_n128_t0<HI_K>(s0, q[0], q[1], q[2], q[3], sbd + dlo(0, 128), 0);
            wgmma_rs_n128_t0<HI_K>(s0, q[4], q[5], q[6], q[7], sbd + dlo(512, 0), 1);
            wg_commit();
            wg_wait<0>();
            fence_regs(s0);
#pragma unroll 1
            for (int u = 0; u < 32; u++) {
                const uint32_t kb = sbd + (u >> 4) * 1280;
                wg_fence();
                wgmma_rs_n128_t0<HI_K>(s1, q[0], q[1], q[2], q[3], kb + dlo(10240, 128), 0);
                wgmma_rs_n128_t0<HI_K>(s1, q[4], q[5], q[6], q[7], kb + dlo(10240 + 512, 0), 1);
                wg_commit();
#pragma unroll
                for (int i = 0; i < 32; i++) p0[i] = pack(ex2(s0[2 * i]), ex2(s0[2 * i + 1]));
                fence_regs(p0);
                wg_wait<0>();
                fence_regs(o); fence_regs(s1); fence_regs(q);
                store_px(u > 0 ? u - 1 : 0);
                if (u == 16) signal(0);
                if (u == 15) mbar_wait(bar_rdy + 8, 0);
                const int un = u < 31 ? u + 1 : u;
                load_q(q, sb + 40960 + un * 4608 + warp * 576, lane);
                fence_regs(q);
                const uint32_t kn = sbd + (un >> 4) * 1280;
                wg_fence();
#pragma unroll
                for (int i = 0; i < 8; i++) wgmma_rs_n24_t1<HI_V>(o, p0[4 * i], p0[4 * i + 1], p0[4 * i + 2], p0[4 * i + 3], kb + dlo(256, 640) + 80 * i, i != 0);
                wgmma_rs_n128_t0<HI_K>(s0, q[0], q[1], q[2], q[3], kn + dlo(0, 128), 0);
                wgmma_rs_n128_t0<HI_K>(s0, q[4], q[5], q[6], q[7], kn + dlo(512, 0), 1);
                wg_commit();
#pragma unroll
                for (int i = 0; i < 32; i++) p1[i] = pack(ex2(s1[2 * i]), ex2(s1[2 * i + 1]));
                fence_regs(p1);
                wg_fence();
#pragma unroll
                for (int i = 0; i < 8; i++) wgmma_rs_n24_t1<HI_V>(o, p1[4 * i], p1[4 * i + 1], p1[4 * i + 2], p1[4 * i + 3], kb + dlo(10240 + 256, 640) + 80 * i, 1);
                wg_commit();
                wg_wait<1>();
                fence_regs(s0); fence_regs(p0);
            }
            wg_wait<0>();
            fence_regs(o);
            store_px(31);
            signal(1);
            PROF(20);
            return;
        }
        Attn at;
        PROF(0);

        uint8_t* a2w = g_a2 + (size_t)m * A2_TILE + grp * 256 + lane * 4;
        const uint32_t qa = sb + OFF_Q + warp * 576;
        float acc[128];
        {
            float qkv[96], tl[12], gu[64];
            const uint32_t xrow = wg * 64 + wq * 16 + (lane & 15);
            const uint32_t xa0 = (sb & ~0x3FFFFu) + OFF_AX + xrow * 64 + (((lane >> 4) ^ ((xrow >> 1) & 3)) << 4);
            uint32_t xf[2][8];
#pragma unroll 1
            for (int k2 = 0; k2 < 18 - DEFER; k2 += 2) {
#pragma unroll
                for (int h = 0; h < 2; h++) {
                    const int kk = k2 + h;
                    mbar_wait(fb, ph);
                    if (kk == 0) PROF(21);
                    if (kk == 6) PROF(22);
                    if (kk == 12) PROF(23);
                    ldsm4(&xf[h][0], xa0 + sd * 16);
                    ldsm4(&xf[h][4], (xa0 ^ 32) + sd * 16);
                    fence_regs(xf[h]);
                    const uint32_t db = sd + dlo(0, 4096), dt = sd + dlo(OFF_TL, 128);
                    wg_fence();
                    wgmma_rs_n192_t1<HI_W>(qkv, xf[h][0], xf[h][1], xf[h][2], xf[h][3], sd + QB0, kk != 0);
                    wgmma_rs_n24_t1<HI_T>(tl, xf[h][0], xf[h][1], xf[h][2], xf[h][3], dt, kk != 0);
                    wgmma_rs_n128_t1<HI_W>(gu, xf[h][0], xf[h][1], xf[h][2], xf[h][3], db, kk != 0);
                    wgmma_rs_n192_t1<HI_W>(qkv, xf[h][4], xf[h][5], xf[h][6], xf[h][7], sd + QB1, 1);
                    wgmma_rs_n24_t1<HI_T>(tl, xf[h][4], xf[h][5], xf[h][6], xf[h][7], dt + QT1, 1);
                    wgmma_rs_n128_t1<HI_W>(gu, xf[h][4], xf[h][5], xf[h][6], xf[h][7], db + 128, 1);
                    wg_commit();
                    wg_wait<1>();
                    if (kk > 0) release();
                    STAGE_NEXT;
                }
            }
#pragma unroll
            for (int kk = 0; kk < DEFER; kk++) {
                mbar_wait(fb + kk * 8, ph);
                const uint32_t st = sd + kk * (SLOT >> 4);
                const uint32_t da = st + wg * 256 + dlo(OFF_AX, 16), dt = st + dlo(OFF_TL, 128);
                wg_fence();
                wgmma_ss_n192_t1<HI_X, HI_W>(qkv, da, st + QB0, 1);
                wgmma_ss_n24_t1<HI_X, HI_T>(tl, da, dt, 1);
                wgmma_ss_n192_t1<HI_X, HI_W>(qkv, da + 2, st + QB1, 1);
                wgmma_ss_n24_t1<HI_X, HI_T>(tl, da + 2, dt + QT1, 1);
                wg_commit();
                if (kk == 0) { wg_wait<1>(); release(); }
            }
#pragma unroll
            for (int kk = 0; kk < DEFER; kk++) {
                const uint32_t st = sd + kk * (SLOT >> 4);
                const uint32_t da = st + wg * 256 + dlo(OFF_AX, 16), db = st + dlo(0, 4096);
                wgmma_ss_n128_t1<HI_X, HI_W>(gu, da, db, 1);
                wgmma_ss_n128_t1<HI_X, HI_W>(gu, da + 2, db + 128, 1);
            }
            wg_commit();
            wg_wait<1>();
            fence_regs(qkv); fence_regs(tl);
            PROF(1);
            constexpr float QS = 0.23570226039551584f * 1.4426950408889634f;
            uint32_t kp[9][2], vp[9][2];
#pragma unroll
            for (int i = 0; i < 9; i++) {
                const float* k4 = i < 8 ? &qkv[32 + 4 * i] : &tl[4];
                const float* v4 = i < 8 ? &qkv[64 + 4 * i] : &tl[8];
                kp[i][0] = pack(k4[0], k4[1]); kp[i][1] = pack(k4[2], k4[3]);
                vp[i][0] = pack(v4[0], v4[1]); vp[i][1] = pack(v4[2], v4[3]);
            }
            const int quad = lane & ~3;
            const uint32_t cst = c == 1 ? 0x3F80u : 0u;
            {
                const uint32_t a = sb + (2 + rank * 2 + wg) * SLOT + OFF_KV + wq * 1280 + lane * 4;
#pragma unroll
                for (int r = 0; r < 2; r++) {
                    const uint32_t kt = __shfl_sync(0xffffffffu, kp[2][r], quad);
                    sts32(a + r * 640, kp[0][r]);       sts32(a + r * 640 + 128, kp[1][r]);
                    sts32(a + r * 640 + 256, vp[0][r]); sts32(a + r * 640 + 384, vp[1][r]);
                    sts32(a + r * 640 + 512, c == 0 ? vp[2][r] : c == 2 ? kt : cst);
                }
                fence_async_shared();
                __syncwarp();
                if (lane == 0) mbar_arrive(bar_st + wg * 8);
            }
            PROF(2);
#pragma unroll
            for (int i = 0; i < 9; i++) {
                const float* q4 = i < 8 ? &qkv[4 * i] : &tl[0];
                const uint32_t q0 = pack(q4[0] * QS, q4[1] * QS), q1 = pack(q4[2] * QS, q4[3] * QS);
                if (i < 2) { at.q[2 * i] = q0; at.q[2 * i + 1] = q1; }
                else {
                    if (i == 2) {
                        const uint32_t t0 = __shfl_sync(0xffffffffu, q0, quad), t1 = __shfl_sync(0xffffffffu, q1, quad);
                        at.q[4] = c == 2 ? t0 : 0u; at.q[5] = c == 2 ? t1 : 0u;
                    }
                    const int lc = 8 * i + 2 * c;
                    const int hd = (lc * 3641) >> 16;
                    const int d = lc - hd * 18;
                    const bool last = (i & 1) == 0 && c == i / 2 - 1;
                    const uint32_t aq = qa + hd * 4608 + (last ? 512 + (lane >> 2) * 4 : (d >> 3) * 128 + (d & 7) * 2 + (lane >> 2) * 16);
                    if (i > 2 || c > 0) { sts32(aq, q0); sts32(aq + (last ? 32 : 256), q1); }
                }
            }
            mbar_wait(bar_st, 0);
            mbar_wait(bar_st + 8, 0);
#pragma unroll
            for (int i = 2; i < 9; i++) {
                const int lc = 8 * i + 2 * c;
                const int hd = (lc * 3641) >> 16;
                const int d = lc - hd * 18;
                const uint32_t ak = sb + (wg * 3 - 1 + hd) * SLOT + OFF_GAP + wq * 1280 + (lane >> 2) * 16;
                const uint32_t off = (d >> 3) * 128 + (d & 7) * 2;
                if ((i & 1) == 0 && c == i / 2 - 1) {
                    if (i > 2) { sts128(ak + 512, vp[i][0], 0x3F80u, kp[i][0], 0u); sts128(ak + 512 + 640, vp[i][1], 0x3F80u, kp[i][1], 0u); }
                } else {
                    sts32(ak + off, kp[i][0]); sts32(ak + off + 640, kp[i][1]); sts32(ak + off + 256, vp[i][0]); sts32(ak + off + 256 + 640, vp[i][1]);
                }
            }
            fence_async_shared();
            __syncwarp();
            if (lane == 0) mbar_arrive(bar_st + (2 + wg) * 8);
            PROF(39);
            wg_wait<0>();
            fence_regs(gu);
            if (tid < 2 * DEFER) mbar_arrive_cluster(fb + 64 + (tid >> 1) * 8, tid & 1);
#pragma unroll
            for (int kk = 0; kk < 2; kk++) {
                mbar_wait(bar_full + kk * 8, 1);
                const uint32_t st = sbd + kk * (SLOT >> 4);
                const uint32_t da = st + wg * 256 + dlo(OFF_AX, 16), db = st + dlo(0, 4096);
                wg_fence();
                wgmma_ss_n256_t1<HI_X, HI_W>(acc, da, db, kk);
                wgmma_ss_n256_t1<HI_X, HI_W>(acc, da + 2, db + 128, 1);
                wg_commit();
            }
            sd = sbd + 2 * (SLOT >> 4); fb = bar_full + 16; pb = bar_full; ph = 1;
            uint8_t* hp = a2w + (j * 36 + 32) * 4096;
#pragma unroll
            for (int i = 0; i < 16; i++)
                stg32(hp + (i >> 2) * 4096 + ((i >> 1) & 1) * 128 + (i & 1) * 256, pack(geglu2(gu[2 * i], gu[32 + 2 * i]), geglu2(gu[2 * i + 1], gu[32 + 2 * i + 1])));
            signal(4);
            PROF(3);
            wg_wait<1>();
            release();
            mbar_wait(fb, ph);
            PROF(38);
        }

        const uint32_t gaddr = s_gate + (grp * 8 + (lane >> 2)) * 4;
        at.q[6] = lds32(s_zero); at.q[7] = lds32(s_zero + 4);
#pragma unroll
        for (int i = 0; i < 16; i++) at.p[i] = 0u;
#pragma unroll
        for (int i = 0; i < 12; i++) at.o[i] = 0.f;
        fence_regs(at.q); fence_regs(at.p); fence_regs(at.o);
        pd = sd;
        uint32_t rel = bar_empty + 8;
        asm volatile("mapa.shared::cluster.u32 %0, %0, %1;" : "+r"(rel) : "r"(tid & 1));
        const uint32_t rel_off = rel - (bar_full + 8);

#define ISSUE_PV() do {                                                                                            \
            const uint32_t dv = pd + dlo(OFF_KV + 256, 640);                                                       \
            wgmma_rs_n24_t1<HI_V>(at.o, at.p[0], at.p[1], at.p[2], at.p[3], dv, 1);                                \
            wgmma_rs_n24_t1<HI_V>(at.o, at.p[4], at.p[5], at.p[6], at.p[7], dv + 80, 1);                           \
            wgmma_rs_n24_t1<HI_V>(at.o, at.p[8], at.p[9], at.p[10], at.p[11], dv + 160, 1);                        \
            wgmma_rs_n24_t1<HI_V>(at.o, at.p[12], at.p[13], at.p[14], at.p[15], dv + 240, 1);                      \
        } while (0)
#define EXPS() do {                                                                                                \
            _Pragma("unroll") for (int i = 0; i < 16; i++) at.p[i] = pack(ex2(at.s[2 * i]), ex2(at.s[2 * i + 1])); \
            fence_regs(at.p);                                                                                      \
        } while (0)
#define FUSED_STEP(DV, DK, NB, NPH, REL, GEMM_CODE) do {                                                           \
            wg_fence();                                                                                            \
            wgmma6_rs_n24_t1(at.o, at.p[0], at.p[1], at.p[2], at.p[3], (DV), 1);                                   \
            wgmma6_rs_n24_t1(at.o, at.p[4], at.p[5], at.p[6], at.p[7], (DV) + 80, 1);                              \
            wgmma6_rs_n24_t1(at.o, at.p[8], at.p[9], at.p[10], at.p[11], (DV) + 160, 1);                           \
            wgmma6_rs_n24_t1(at.o, at.p[12], at.p[13], at.p[14], at.p[15], (DV) + 240, 1);                         \
            wgmma6_rs_n64_t0(at.s, at.q[0], at.q[1], at.q[2], at.q[3], (DK) + dlo(0, 128), 0);                     \
            wgmma6_rs_n64_t0(at.s, at.q[4], at.q[5], at.q[6], at.q[7], (DK) + 32, 1);                              \
            wg_commit();                                                                                           \
            GEMM_CODE;                                                                                             \
            wg_commit();                                                                                           \
            const uint32_t rdy = mbar_test(NB, NPH);                                                               \
            wg_wait<1>();                                                                                          \
            fence_regs(at.s); fence_regs(at.p);                                                                    \
            if (tid < 2) asm volatile("mbarrier.arrive.shared::cluster.b64 _, [%0];" ::"r"(REL) : "memory");       \
            EXPS();                                                                                                \
            mbar_wait_unless(rdy, NB, NPH);                                                                        \
        } while (0)
#define FUSED_PAIR(HIA, LOA, LOB, STEP0, GEMM) do {                                                                \
            const uint64_t dv0 = mkdesc<HI_V>(pd + dlo(OFF_KV + 256, 640));                                        \
            const uint64_t dv1 = mkdesc<HI_V>(sd + dlo(OFF_KV + 256, 640));                                        \
            const uint64_t dk = mkdesc<HI_K>(sd + dlo(OFF_KV, 0));                                                 \
            const uint64_t da = mkdesc<HIA>(sd + (LOA)), db = mkdesc<HI_W>(sd + (LOB));                            \
            STEP0(dv0, dk, fb + 8, ph, rel, GEMM(da, db, first));                                                  \
            const uint32_t r1 = fb + rel_off;                                                                      \
            rel = r1 + 8;                                                                                          \
            pd = sd + (SLOT >> 4); pb = fb + 8;                                                                    \
            if (fb == bar_full + (NSTAGE - 2) * 8) { fb = bar_full; ph ^= 1; } else fb += 16;                      \
            sd = (sd == sbd + (NSTAGE - 2) * (SLOT >> 4)) ? sbd : sd + 2 * (SLOT >> 4);                            \
            FUSED_STEP(dv1, dk + (SLOT >> 4), fb, ph, r1, GEMM(da + (SLOT >> 4), db + (SLOT >> 4), 1));            \
            first = 1;                                                                                             \
            TRACE();                                                                                               \
        } while (0)
#define GEMM_256(A, B, SC) do { wgmma6_ss_n256_t1(acc, A, B, SC); wgmma6_ss_n256_t1(acc, (A) + 2, (B) + 128, 1); } while (0)
#define GEMM_80(A, B, SC) do { wgmma6_ss_n80_t1(keep, A, B, SC); wgmma6_ss_n80_t1(keep, (A) + 256, (B) + 128, 1); wgmma6_ss_n80_t1(keep, (A) + 512, (B) + 256, 1); } while (0)
#define GEMM_144(A, B, SC) do { wgmma6_ss_n144_t1(ah, A, B, SC); wgmma6_ss_n144_t1(ah, (A) + 256, (B) + 128, 1); wgmma6_ss_n144_t1(ah, (A) + 512, (B) + 256, 1); } while (0)
#define NORM_ITEM(item) do {                                                                                       \
            if (norm_o(ow, at.o, lane, gaddr)) {                                                                   \
                attn_true_max(at.o, at.q, g_kv + (size_t)(j * 4 + (item)) * HEAD_BYTES + lane * 4);                \
                norm_o(ow, at.o, lane, gaddr);                                                                     \
            }                                                                                                      \
        } while (0)
#define STORE_ITEM(item) do { uint32_t ow[6]; NORM_ITEM(item); PUT_ITEM(item); } while (0)
#define PUT_ITEM(item) do {                                                                                        \
            uint8_t* op = a2w + (288 + ((item) * 4 + (j >> 1)) * 3) * 4096 + (j & 1) * 4224;                       \
            const int step = (j & 1) ? 3968 : 128;                                                                 \
            stg32(op, ow[0]);        stg32(op + 256, ow[1]);                                                       \
            stg32(op + step, ow[2]); stg32(op + step + 256, ow[3]);                                                \
            stg32(op + 4096, ow[4]); stg32(op + 4096 + 256, ow[5]);                                                \
        } while (0)
#define ITEM_STEP(DV, DK, NB, NPH, REL, GEMM_CODE) do {                                                            \
            uint32_t qo[8];                                                                                        \
            _Pragma("unroll") for (int i = 0; i < 6; i++) asm volatile("mov.b32 %0, %1;" : "=r"(qo[i]) : "r"(at.q[i])); \
            load_q(at.q, qa + (item + 1) * 4608, lane);                                                            \
            fence_regs(at.q);                                                                                      \
            wg_fence();                                                                                            \
            wgmma6_rs_n24_t1(at.o, at.p[0], at.p[1], at.p[2], at.p[3], (DV), 1);                                   \
            wgmma6_rs_n24_t1(at.o, at.p[4], at.p[5], at.p[6], at.p[7], (DV) + 80, 1);                              \
            wgmma6_rs_n24_t1(at.o, at.p[8], at.p[9], at.p[10], at.p[11], (DV) + 160, 1);                           \
            wgmma6_rs_n24_t1(at.o, at.p[12], at.p[13], at.p[14], at.p[15], (DV) + 240, 1);                         \
            wgmma6_rs_n64_t0(at.s, at.q[0], at.q[1], at.q[2], at.q[3], (DK) + dlo(0, 128), 0);                     \
            wgmma6_rs_n64_t0(at.s, at.q[4], at.q[5], at.q[6], at.q[7], (DK) + 32, 1);                              \
            wg_commit();                                                                                           \
            GEMM_CODE;                                                                                             \
            wg_commit();                                                                                           \
            wg_wait<1>();                                                                                          \
            fence_regs(at.o); fence_regs(at.p); fence_regs(at.s);                                                  \
            if (tid < 2) asm volatile("mbarrier.arrive.shared::cluster.b64 _, [%0];" ::"r"(REL) : "memory");       \
            uint32_t ow[6];                                                                                        \
            const bool bad = norm_o(ow, at.o, lane, gaddr);                                                        \
            EXPS();                                                                                                \
            if (bad) {                                                                                             \
                attn_true_max(at.o, qo, g_kv + (size_t)(j * 4 + (item)) * HEAD_BYTES + lane * 4);                  \
                norm_o(ow, at.o, lane, gaddr);                                                                     \
            }                                                                                                      \
            PUT_ITEM(item);                                                                                        \
            _Pragma("unroll") for (int i = 0; i < 12; i++) at.o[i] = 0.f;                                          \
            fence_regs(at.o);                                                                                      \
            mbar_wait(NB, NPH);                                                                                    \
        } while (0)
#define H2(i) pack(geglu2(acc[i], acc[64 + (i)]), geglu2(acc[(i) + 1], acc[65 + (i)]))
        float keep[40];
        float4 px[3];
        {
            float ah[72];
            int first = 1;
            {
#pragma unroll 1
                for (int t = 0; t < 5; t++) {
                    int n = 0x26988 >> (t * 4) & 15;
#pragma unroll 1
                    do { FUSED_PAIR(HI_X, wg * 256 + dlo(OFF_AX, 16), dlo(0, 4096), FUSED_STEP, GEMM_256); } while (--n);
                    if (t & 1) {
                        const int item = t >> 1;
                        mbar_wait(t == 1 ? bar_gate : bar_rdy + 2 * 8, 0);
                        FUSED_PAIR(HI_X, wg * 256 + dlo(OFF_AX, 16), dlo(0, 4096), ITEM_STEP, GEMM_256);
                    }
                    if (t < 3) {
                        mbar_wait(t > 0 ? bar_rdy + (t - 1) * 8 : bar_free + wg * 8, 0);
                        wg_wait<0>();
                        fence_regs(acc);
                        first = 0;
                        PROF(4 + 2 * t);
                        const uint32_t ha = sb + wg * 3 * SLOT + OFF_GAP + wq * 512 + lane * 16;
#pragma unroll
                        for (int k = 0; k < 8; k++) stsm4(ha + (k / 3) * SLOT + (k % 3) * 2048, H2(8 * k), H2(8 * k + 4), H2(8 * k + 2), H2(8 * k + 6));
                        fence_async_shared();
                        undef_regs(acc);
                        signal(t);
                        PROF(5 + 2 * t);
                    }
                }
                wg_wait<0>();
                fence_regs(acc);
                first = 0;
                PROF(10);
                uint8_t* hp = a2w + (j * 36 + 24) * 4096;
#pragma unroll
                for (int b = 0; b < 2; b++)
                    if (cta != 1000 + b) {
#pragma unroll
                        for (int k = b * 4; k < b * 4 + 4; k++) {
                            stg32(hp + k * 4096, H2(8 * k));           stg32(hp + k * 4096 + 256, H2(8 * k + 2));
                            stg32(hp + k * 4096 + 128, H2(8 * k + 4)); stg32(hp + k * 4096 + 384, H2(8 * k + 6));
                        }
                    }
                signal(3);
                PROF(11);
            }
#pragma unroll 1
            for (int seg = 0; seg < 3; seg++) {
                int n = 0x2AD >> (seg * 4) & 15;
#pragma unroll 1
                do { FUSED_PAIR(HI_A2, wg * 128 + dlo(OFF_A2, 128), dlo(0, 6144), FUSED_STEP, GEMM_144); } while (--n);
                if (seg == 0) {
                    constexpr int item = 2;
                    FUSED_PAIR(HI_A2, wg * 128 + dlo(OFF_A2, 128), dlo(0, 6144), ITEM_STEP, GEMM_144);
                    signal(5);
                } else if (seg == 1) {
                    wg_wait<0>();
                    fence_regs(ah);
                    PROF(12);
                    const float w0 = 0.5f - 0.5f * __uint_as_float(lds32(gaddr)), w1 = 0.5f - 0.5f * __uint_as_float(lds32(gaddr + 32));
#pragma unroll
                    for (int i = 0; i < 72; i++) ah[i] *= (i & 2) ? w1 : w0;
                    fence_regs(ah);
                }
            }
            wg_wait<0>();
            fence_regs(ah);
            PROF(17);
            mbar_wait(bar_px, 0);
#pragma unroll
            for (int i = 0; i < 3; i++) px[i] = __ldcg(g_px + (size_t)(cta * 2 + wg) * 3 * 128 + tid + i * 128);
            uint4* mine = g_part + (size_t)(cta * 2 + wg) * 5 * 128 + tid;
#pragma unroll
            for (int i = 0; i < 5; i++) {
                uint32_t u[4];
#pragma unroll
                for (int e = 0; e < 4; e++) {
                    const int k = 8 * i + 2 * e;
                    if (i < 4) {
                        u[e] = pack(sel(hf, ah[k], ah[32 + k]), sel(hf, ah[k + 1], ah[33 + k]));
                        keep[k] = sel(hf, ah[32 + k], ah[k]); keep[k + 1] = sel(hf, ah[33 + k], ah[k + 1]);
                    } else {
                        u[e] = pack(ah[32 + k], ah[33 + k]);
                        keep[k] = sel(1, ah[32 + k], 0.f); keep[k + 1] = sel(1, ah[33 + k], 0.f);
                    }
                }
                __stcg(mine + i * 128, make_uint4(u[0], u[1], u[2], u[3]));
            }
            signal(6);
            fence_regs(keep);
        }
        {
            int first = 1;
            FUSED_PAIR(HI_A2, wg * 128 + dlo(OFF_A2, 128), dlo(0, 6144), FUSED_STEP, GEMM_80);
        }
        PROF(13);
        wg_fence();
        ISSUE_PV();
        wg_commit();
        wg_wait<0>();
        fence_regs(at.o); fence_regs(at.p); fence_regs(at.q);
#pragma unroll
        for (int i = 0; i < 3; i++) { at.o[4 * i] += px[i].x; at.o[4 * i + 1] += px[i].y; at.o[4 * i + 2] += px[i].z; at.o[4 * i + 3] += px[i].w; }
        STORE_ITEM(3);
        signal(7);
        fence_regs(keep);
        PROF(14);
#pragma unroll 1
        for (int kk = 0; kk < 2; kk++) {
            mbar_wait(fb, ph);
            const uint64_t da = mkdesc<HI_A2>(sd + wg * 128 + dlo(OFF_A2, 128)), db = mkdesc<HI_W>(sd + dlo(0, 6144));
            wg_fence();
            GEMM_80(da, db, 1);
            wg_commit();
            wg_wait<1>();
            if (kk < 1) release();
            STAGE_NEXT;
        }
        {
            mbar_wait(bar_rdy + 6 * 8, 0);
            const uint4* theirs = g_part + (size_t)((cta ^ 8) * 2 + wg) * 5 * 128 + tid;
            uint4 pv[5];
#pragma unroll
            for (int i = 0; i < 5; i++) pv[i] = __ldcg(theirs + i * 128);
            wg_wait<0>();
            fence_regs(keep);
#pragma unroll
            for (int i = 0; i < 5; i++) {
                const uint32_t u[4] = {pv[i].x, pv[i].y, pv[i].z, pv[i].w};
#pragma unroll
                for (int e = 0; e < 4; e++) { keep[8 * i + 2 * e] += __uint_as_float(u[e] << 16); keep[8 * i + 2 * e + 1] += __uint_as_float(u[e] & 0xffff0000u); }
            }
            fence_regs(keep);
        }
        mbar_wait(bar_late, 0);
#pragma unroll 1
        for (int k = 2; k < 6; k++) {
            mbar_wait(bar_full + k * 8, 0);
            if (k == 2) PROF(15);
            const uint32_t bo = __shfl_sync(0xffffffffu, lds32(s_order + k * 4), 0);
            const uint64_t da = mkdesc<HI_A2>(sbd + k * (SLOT >> 4) + wg * 128 + dlo(OFF_A2, 128)), db = mkdesc<HI_W>(sbd + bo + dlo(0, 6144));
            wg_fence();
            GEMM_80(da, db, 1);
            wg_commit();
        }
        asm volatile("barrier.cluster.arrive.relaxed.aligned;" ::: "memory");
        const uint32_t tb = sb + (warp >> 1) * SLOT + OFF_KV + (warp & 1) * 2560;
        const uint32_t trow = ((lane >> 3) & 1) * 8 + (lane & 7);
        uint8_t* op = (uint8_t*)(out + (size_t)(m * 128 + grp * 8) * DM);
        wg_wait<0>();
        fence_regs(keep);
        PROF(16);
#pragma unroll
        for (int i = 0; i < 5; i++) {
            const uint32_t a = i < 4 ? tb + trow * 128 + (((2 * i + (lane >> 4)) ^ (lane & 7)) << 4) : tb + 2048 + trow * 32 + (lane >> 4) * 16;
            stsm4(a, pack(keep[8 * i], keep[8 * i + 1]), pack(keep[8 * i + 2], keep[8 * i + 3]), pack(keep[8 * i + 4], keep[8 * i + 5]), pack(keep[8 * i + 6], keep[8 * i + 7]));
        }
        __syncwarp();
        uint4 v[5];
#pragma unroll
        for (int i = 0; i < 5; i++) {
            const uint32_t r = 4 * i + (lane >> 3);
            const uint32_t a = i < 4 ? tb + r * 128 + (((lane & 7) ^ (r & 7)) << 4) : tb + 2048 + lane * 16;
            asm volatile("ld.shared.v4.u32 {%0, %1, %2, %3}, [%4];" : "=r"(v[i].x), "=r"(v[i].y), "=r"(v[i].z), "=r"(v[i].w) : "r"(a) : "memory");
        }
#pragma unroll
        for (int i = 0; i < 4; i++) *(uint4*)(op + (4 * i + (lane >> 3)) * (DM * 2) + nt * 256 + hf * 128 + (lane & 7) * 16) = v[i];
        if (wg == hf) *(uint4*)(op + (lane >> 1) * (DM * 2) + 1024 + nt * 32 + (lane & 1) * 16) = v[4];
        PROF(20);
        asm volatile("barrier.cluster.wait.aligned;" ::: "memory");
    }
}

typedef CUresult (*EncodeFn)(CUtensorMap*, CUtensorMapDataType, cuuint32_t, void*, const cuuint64_t*, const cuuint64_t*,
                             const cuuint32_t*, const cuuint32_t*, CUtensorMapInterleave, CUtensorMapSwizzle,
                             CUtensorMapL2promotion, CUtensorMapFloatOOBfill);

CUtensorMap make_map(EncodeFn enc, const void* ptr, uint64_t inner, uint64_t outer, uint32_t box_inner, uint32_t box_outer, CUtensorMapSwizzle swz) {
    CUtensorMap t;
    cuuint64_t dims[2] = {inner, outer};
    cuuint64_t strides[1] = {inner * 2};
    cuuint32_t box[2] = {box_inner, box_outer};
    cuuint32_t es[2] = {1, 1};
    enc(&t, CU_TENSOR_MAP_DATA_TYPE_BFLOAT16, 2, const_cast<void*>(ptr), dims, strides, box, es, CU_TENSOR_MAP_INTERLEAVE_NONE, swz,
        CU_TENSOR_MAP_L2_PROMOTION_L2_128B, CU_TENSOR_MAP_FLOAT_OOB_FILL_NONE);
    return t;
}

CUtensorMap make_qkv_map(EncodeFn enc, const void* ptr, uint32_t width, CUtensorMapSwizzle swz) {
    CUtensorMap t;
    cuuint64_t dims[3] = {DM, DM, 3};
    cuuint64_t strides[2] = {3 * DM * 2, DM * 2};
    cuuint32_t box[3] = {width, 16, 3};
    cuuint32_t es[3] = {1, 1, 1};
    enc(&t, CU_TENSOR_MAP_DATA_TYPE_BFLOAT16, 3, const_cast<void*>(ptr), dims, strides, box, es, CU_TENSOR_MAP_INTERLEAVE_NONE, swz,
        CU_TENSOR_MAP_L2_PROMOTION_L2_128B, CU_TENSOR_MAP_FLOAT_OOB_FILL_NONE);
    return t;
}

}

extern "C" void kernel_launch(void* const* d_in, const int* in_sizes, int n_in, void* d_out, int out_size) {
    (void)in_sizes; (void)n_in; (void)out_size;
    void* fn = nullptr;
    cudaDriverEntryPointQueryResult qr;
    cudaGetDriverEntryPoint("cuTensorMapEncodeTiled", &fn, cudaEnableDefault, &qr);
    EncodeFn enc = (EncodeFn)fn;
    const CUtensorMap tm_x = make_map(enc, d_in[0], DM, SEQ, 32, 128, CU_TENSOR_MAP_SWIZZLE_64B);
    const CUtensorMap tm_qkv = make_qkv_map(enc, d_in[1], 64, CU_TENSOR_MAP_SWIZZLE_128B);
    const CUtensorMap tm_qkv8 = make_qkv_map(enc, d_in[1], 8, CU_TENSOR_MAP_SWIZZLE_NONE);
    const CUtensorMap tm_wo = make_map(enc, d_in[2], DM, DM, 64, 24, CU_TENSOR_MAP_SWIZZLE_128B);
    const CUtensorMap tm_wg = make_map(enc, d_in[4], FF, DM, 64, 32, CU_TENSOR_MAP_SWIZZLE_128B);
    const CUtensorMap tm_wu = make_map(enc, d_in[5], FF, DM, 64, 32, CU_TENSOR_MAP_SWIZZLE_128B);
    const CUtensorMap tm_wd = make_map(enc, d_in[6], DM, FF, 64, 24, CU_TENSOR_MAP_SWIZZLE_128B);
    const CUtensorMap tm_wd16 = make_map(enc, d_in[6], DM, FF, 16, 24, CU_TENSOR_MAP_SWIZZLE_128B);
    const CUtensorMap tm_wo16 = make_map(enc, d_in[2], DM, DM, 16, 24, CU_TENSOR_MAP_SWIZZLE_128B);
    cudaFuncSetAttribute(fused_kernel, cudaFuncAttributeMaxDynamicSharedMemorySize, SMEM_BYTES);
    fused_kernel<<<NCTA + 4, 384, SMEM_BYTES>>>((__nv_bfloat16*)d_out, (const __nv_bfloat16*)d_in[0], (const __nv_bfloat16*)d_in[7],
                                               (const uint8_t*)d_in[1], (const uint8_t*)d_in[4], (const uint8_t*)d_in[5],
                                               tm_x, tm_qkv, tm_qkv8, tm_wg, tm_wu, tm_wd, tm_wo, tm_wd16, tm_wo16);
}
```

```cpp
#include <cuda_runtime.h>
#include <cuda.h>
#include <cuda_bf16.h>
#include <stdint.h>

#define PROFILE 0
#define DOTRACE 0

namespace {

constexpr int SEQ = 2048, DM = 576, FF = 4608;
constexpr int NCTA = 128;
constexpr int NSTAGE = 6;
constexpr int DEFER = 2;
constexpr int SLOT = 35 * 1024;
constexpr int OFF_AX = 22528;
constexpr int OFF_A2 = 18432;
constexpr int OFF_TL = 20480;
constexpr int OFF_GAP = 16384;
constexpr int OFF_KV = 30720;
constexpr int OFF_Q = NSTAGE * SLOT - 4608;
constexpr int OFF_BAR = NSTAGE * SLOT + 3 * 4608;
constexpr int SMEM_BYTES = OFF_BAR + 1024 + 1024;

constexpr int STRIPB = 48 * 32;
constexpr int HEAD_BYTES = 256 * 640;
constexpr int A2_TILE = 336 * 4096;

constexpr int FL_KV = 0;
constexpr int FL_M = FL_KV + 8 * 32;
constexpr int FM_H = 0;
constexpr int FM_LATE = 7;
constexpr int FM_R = 16;
constexpr int FL_G = FL_M + 16 * 64;
constexpr int FL_E = FL_G + 4 * 32;
constexpr int FL_N = FL_E + (NCTA + 4) * 32;

__device__ __align__(1024) uint8_t g_kv[32 * HEAD_BYTES];
__device__ __align__(1024) uint8_t g_a2[16 * A2_TILE];
__device__ __align__(1024) uint4 g_part[NCTA * 2 * 5 * 128];
__device__ __align__(1024) uint8_t g_q3[NCTA * 4608];
__device__ __align__(1024) float4 g_px[NCTA * 2 * 3 * 128];
__device__ float g_gate[SEQ];
__device__ __align__(256) uint32_t g_flags[FL_N];

template <uint32_t BHI>
__device__ __forceinline__ void wgmma_rs_n24_t1(float (&d)[12], uint32_t a0, uint32_t a1, uint32_t a2, uint32_t a3, uint32_t db, int scale_d) {
  asm volatile("{\n.reg .pred p;\n.reg .b64 da, db;\n"
    "mov.b64 db, {%16, %18};\n"
    "setp.ne.b32 p, %17, 0;\n"
    "wgmma.mma_async.sync.aligned.m64n24k16.f32.bf16.bf16 "
    "{%0, %1, %2, %3, %4, %5, %6, %7, %8, %9, %10, %11}, "
    "{%12, %13, %14, %15}, db, p, 1, 1, 1;\n}\n"
    : "+f"(d[0]), "+f"(d[1]), "+f"(d[2]), "+f"(d[3]), "+f"(d[4]), "+f"(d[5]), "+f"(d[6]), "+f"(d[7]),
      "+f"(d[8]), "+f"(d[9]), "+f"(d[10]), "+f"(d[11])
    : "r"(a0), "r"(a1), "r"(a2), "r"(a3), "r"(db), "r"(scale_d), "n"(BHI));
}
template <uint32_t BHI>
__device__ __forceinline__ void wgmma_rs_n128_t0(float (&d)[64], uint32_t a0, uint32_t a1, uint32_t a2, uint32_t a3, uint32_t db, int scale_d) {
  asm volatile("{\n.reg .pred p;\n.reg .b64 da, db;\n"
    "mov.b64 db, {%68, %70};\n"
    "setp.ne.b32 p, %69, 0;\n"
    "wgmma.mma_async.sync.aligned.m64n128k16.f32.bf16.bf16 "
    "{%0, %1, %2, %3, %4, %5, %6, %7, %8, %9, %10, %11, %12, %13, %14, %15, "
    "%16, %17, %18, %19, %20, %21, %22, %23, %24, %25, %26, %27, %28, %29, %30, %31, "
    "%32, %33, %34, %35, %36, %37, %38, %39, %40, %41, %42, %43, %44, %45, %46, %47, "
    "%48, %49, %50, %51, %52, %53, %54, %55, %56, %57, %58, %59, %60, %61, %62, %63}, "
    "{%64, %65, %66, %67}, db, p, 1, 1, 0;\n}\n"
    : "+f"(d[0]), "+f"(d[1]), "+f"(d[2]), "+f"(d[3]), "+f"(d[4]), "+f"(d[5]), "+f"(d[6]), "+f"(d[7]),
      "+f"(d[8]), "+f"(d[9]), "+f"(d[10]), "+f"(d[11]), "+f"(d[12]), "+f"(d[13]), "+f"(d[14]), "+f"(d[15]),
      "+f"(d[16]), "+f"(d[17]), "+f"(d[18]), "+f"(d[19]), "+f"(d[20]), "+f"(d[21]), "+f"(d[22]), "+f"(d[23]),
      "+f"(d[24]), "+f"(d[25]), "+f"(d[26]), "+f"(d[27]), "+f"(d[28]), "+f"(d[29]), "+f"(d[30]), "+f"(d[31]),
      "+f"(d[32]), "+f"(d[33]), "+f"(d[34]), "+f"(d[35]), "+f"(d[36]), "+f"(d[37]), "+f"(d[38]), "+f"(d[39]),
      "+f"(d[40]), "+f"(d[41]), "+f"(d[42]), "+f"(d[43]), "+f"(d[44]), "+f"(d[45]), "+f"(d[46]), "+f"(d[47]),
      "+f"(d[48]), "+f"(d[49]), "+f"(d[50]), "+f"(d[51]), "+f"(d[52]), "+f"(d[53]), "+f"(d[54]), "+f"(d[55]),
      "+f"(d[56]), "+f"(d[57]), "+f"(d[58]), "+f"(d[59]), "+f"(d[60]), "+f"(d[61]), "+f"(d[62]), "+f"(d[63])
    : "r"(a0), "r"(a1), "r"(a2), "r"(a3), "r"(db), "r"(scale_d), "n"(BHI));
}
template <uint32_t BHI>
__device__ __forceinline__ void wgmma_rs_n128_t1(float (&d)[64], uint32_t a0, uint32_t a1, uint32_t a2, uint32_t a3, uint32_t db, int scale_d) {
  asm volatile("{\n.reg .pred p;\n.reg .b64 da, db;\n"
    "mov.b64 db, {%68, %70};\n"
    "setp.ne.b32 p, %69, 0;\n"
    "wgmma.mma_async.sync.aligned.m64n128k16.f32.bf16.bf16 "
    "{%0, %1, %2, %3, %4, %5, %6, %7, %8, %9, %10, %11, %12, %13, %14, %15, "
    "%16, %17, %18, %19, %20, %21, %22, %23, %24, %25, %26, %27, %28, %29, %30, %31, "
    "%32, %33, %34, %35, %36, %37, %38, %39, %40, %41, %42, %43, %44, %45, %46, %47, "
    "%48, %49, %50, %51, %52, %53, %54, %55, %56, %57, %58, %59, %60, %61, %62, %63}, "
    "{%64, %65, %66, %67}, db, p, 1, 1, 1;\n}\n"
    : "+f"(d[0]), "+f"(d[1]), "+f"(d[2]), "+f"(d[3]), "+f"(d[4]), "+f"(d[5]), "+f"(d[6]), "+f"(d[7]),
      "+f"(d[8]), "+f"(d[9]), "+f"(d[10]), "+f"(d[11]), "+f"(d[12]), "+f"(d[13]), "+f"(d[14]), "+f"(d[15]),
      "+f"(d[16]), "+f"(d[17]), "+f"(d[18]), "+f"(d[19]), "+f"(d[20]), "+f"(d[21]), "+f"(d[22]), "+f"(d[23]),
      "+f"(d[24]), "+f"(d[25]), "+f"(d[26]), "+f"(d[27]), "+f"(d[28]), "+f"(d[29]), "+f"(d[30]), "+f"(d[31]),
      "+f"(d[32]), "+f"(d[33]), "+f"(d[34]), "+f"(d[35]), "+f"(d[36]), "+f"(d[37]), "+f"(d[38]), "+f"(d[39]),
      "+f"(d[40]), "+f"(d[41]), "+f"(d[42]), "+f"(d[43]), "+f"(d[44]), "+f"(d[45]), "+f"(d[46]), "+f"(d[47]),
      "+f"(d[48]), "+f"(d[49]), "+f"(d[50]), "+f"(d[51]), "+f"(d[52]), "+f"(d[53]), "+f"(d[54]), "+f"(d[55]),
      "+f"(d[56]), "+f"(d[57]), "+f"(d[58]), "+f"(d[59]), "+f"(d[60]), "+f"(d[61]), "+f"(d[62]), "+f"(d[63])
    : "r"(a0), "r"(a1), "r"(a2), "r"(a3), "r"(db), "r"(scale_d), "n"(BHI));
}
template <uint32_t BHI>
__device__ __forceinline__ void wgmma_rs_n192_t1(float (&d)[96], uint32_t a0, uint32_t a1, uint32_t a2, uint32_t a3, uint32_t db, int scale_d) {
  asm volatile("{\n.reg .pred p;\n.reg .b64 da, db;\n"
    "mov.b64 db, {%100, %102};\n"
    "setp.ne.b32 p, %101, 0;\n"
    "wgmma.mma_async.sync.aligned.m64n192k16.f32.bf16.bf16 "
    "{%0, %1, %2, %3, %4, %5, %6, %7, %8, %9, %10, %11, %12, %13, %14, %15, "
    "%16, %17, %18, %19, %20, %21, %22, %23, %24, %25, %26, %27, %28, %29, %30, %31, "
    "%32, %33, %34, %35, %36, %37, %38, %39, %40, %41, %42, %43, %44, %45, %46, %47, "
    "%48, %49, %50, %51, %52, %53, %54, %55, %56, %57, %58, %59, %60, %61, %62, %63, "
    "%64, %65, %66, %67, %68, %69, %70, %71, %72, %73, %74, %75, %76, %77, %78, %79, "
    "%80, %81, %82, %83, %84, %85, %86, %87, %88, %89, %90, %91, %92, %93, %94, %95}, "
    "{%96, %97, %98, %99}, db, p, 1, 1, 1;\n}\n"
    : "+f"(d[0]), "+f"(d[1]), "+f"(d[2]), "+f"(d[3]), "+f"(d[4]), "+f"(d[5]), "+f"(d[6]), "+f"(d[7]),
      "+f"(d[8]), "+f"(d[9]), "+f"(d[10]), "+f"(d[11]), "+f"(d[12]), "+f"(d[13]), "+f"(d[14]), "+f"(d[15]),
      "+f"(d[16]), "+f"(d[17]), "+f"(d[18]), "+f"(d[19]), "+f"(d[20]), "+f"(d[21]), "+f"(d[22]), "+f"(d[23]),
      "+f"(d[24]), "+f"(d[25]), "+f"(d[26]), "+f"(d[27]), "+f"(d[28]), "+f"(d[29]), "+f"(d[30]), "+f"(d[31]),
      "+f"(d[32]), "+f"(d[33]), "+f"(d[34]), "+f"(d[35]), "+f"(d[36]), "+f"(d[37]), "+f"(d[38]), "+f"(d[39]),
      "+f"(d[40]), "+f"(d[41]), "+f"(d[42]), "+f"(d[43]), "+f"(d[44]), "+f"(d[45]), "+f"(d[46]), "+f"(d[47]),
      "+f"(d[48]), "+f"(d[49]), "+f"(d[50]), "+f"(d[51]), "+f"(d[52]), "+f"(d[53]), "+f"(d[54]), "+f"(d[55]),
      "+f"(d[56]), "+f"(d[57]), "+f"(d[58]), "+f"(d[59]), "+f"(d[60]), "+f"(d[61]), "+f"(d[62]), "+f"(d[63]),
      "+f"(d[64]), "+f"(d[65]), "+f"(d[66]), "+f"(d[67]), "+f"(d[68]), "+f"(d[69]), "+f"(d[70]), "+f"(d[71]),
      "+f"(d[72]), "+f"(d[73]), "+f"(d[74]), "+f"(d[75]), "+f"(d[76]), "+f"(d[77]), "+f"(d[78]), "+f"(d[79]),
      "+f"(d[80]), "+f"(d[81]), "+f"(d[82]), "+f"(d[83]), "+f"(d[84]), "+f"(d[85]), "+f"(d[86]), "+f"(d[87]),
      "+f"(d[88]), "+f"(d[89]), "+f"(d[90]), "+f"(d[91]), "+f"(d[92]), "+f"(d[93]), "+f"(d[94]), "+f"(d[95])
    : "r"(a0), "r"(a1), "r"(a2), "r"(a3), "r"(db), "r"(scale_d), "n"(BHI));
}
template <uint32_t AHI, uint32_t BHI>
__device__ __forceinline__ void wgmma_ss_n24_t1(float (&d)[12], uint32_t da, uint32_t db, int scale_d) {
  asm volatile("{\n.reg .pred p;\n.reg .b64 da, db;\n"
    "mov.b64 da, {%12, %15};\nmov.b64 db, {%13, %16};\n"
    "setp.ne.b32 p, %14, 0;\n"
    "wgmma.mma_async.sync.aligned.m64n24k16.f32.bf16.bf16 "
    "{%0, %1, %2, %3, %4, %5, %6, %7, %8, %9, %10, %11}, "
    "da, db, p, 1, 1, 0, 1;\n}\n"
    : "+f"(d[0]), "+f"(d[1]), "+f"(d[2]), "+f"(d[3]), "+f"(d[4]), "+f"(d[5]), "+f"(d[6]), "+f"(d[7]),
      "+f"(d[8]), "+f"(d[9]), "+f"(d[10]), "+f"(d[11])
    : "r"(da), "r"(db), "r"(scale_d), "n"(AHI), "n"(BHI));
}
template <uint32_t AHI, uint32_t BHI>
__device__ __forceinline__ void wgmma_ss_n128_t1(float (&d)[64], uint32_t da, uint32_t db, int scale_d) {
  asm volatile("{\n.reg .pred p;\n.reg .b64 da, db;\n"
    "mov.b64 da, {%64, %67};\nmov.b64 db, {%65, %68};\n"
    "setp.ne.b32 p, %66, 0;\n"
    "wgmma.mma_async.sync.aligned.m64n128k16.f32.bf16.bf16 "
    "{%0, %1, %2, %3, %4, %5, %6, %7, %8, %9, %10, %11, %12, %13, %14, %15, "
    "%16, %17, %18, %19, %20, %21, %22, %23, %24, %25, %26, %27, %28, %29, %30, %31, "
    "%32, %33, %34, %35, %36, %37, %38, %39, %40, %41, %42, %43, %44, %45, %46, %47, "
    "%48, %49, %50, %51, %52, %53, %54, %55, %56, %57, %58, %59, %60, %61, %62, %63}, "
    "da, db, p, 1, 1, 0, 1;\n}\n"
    : "+f"(d[0]), "+f"(d[1]), "+f"(d[2]), "+f"(d[3]), "+f"(d[4]), "+f"(d[5]), "+f"(d[6]), "+f"(d[7]),
      "+f"(d[8]), "+f"(d[9]), "+f"(d[10]), "+f"(d[11]), "+f"(d[12]), "+f"(d[13]), "+f"(d[14]), "+f"(d[15]),
      "+f"(d[16]), "+f"(d[17]), "+f"(d[18]), "+f"(d[19]), "+f"(d[20]), "+f"(d[21]), "+f"(d[22]), "+f"(d[23]),
      "+f"(d[24]), "+f"(d[25]), "+f"(d[26]), "+f"(d[27]), "+f"(d[28]), "+f"(d[29]), "+f"(d[30]), "+f"(d[31]),
      "+f"(d[32]), "+f"(d[33]), "+f"(d[34]), "+f"(d[35]), "+f"(d[36]), "+f"(d[37]), "+f"(d[38]), "+f"(d[39]),
      "+f"(d[40]), "+f"(d[41]), "+f"(d[42]), "+f"(d[43]), "+f"(d[44]), "+f"(d[45]), "+f"(d[46]), "+f"(d[47]),
      "+f"(d[48]), "+f"(d[49]), "+f"(d[50]), "+f"(d[51]), "+f"(d[52]), "+f"(d[53]), "+f"(d[54]), "+f"(d[55]),
      "+f"(d[56]), "+f"(d[57]), "+f"(d[58]), "+f"(d[59]), "+f"(d[60]), "+f"(d[61]), "+f"(d[62]), "+f"(d[63])
    : "r"(da), "r"(db), "r"(scale_d), "n"(AHI), "n"(BHI));
}
template <uint32_t AHI, uint32_t BHI>
__device__ __forceinline__ void wgmma_ss_n192_t1(float (&d)[96], uint32_t da, uint32_t db, int scale_d) {
  asm volatile("{\n.reg .pred p;\n.reg .b64 da, db;\n"
    "mov.b64 da, {%96, %99};\nmov.b64 db, {%97, %100};\n"
    "setp.ne.b32 p, %98, 0;\n"
    "wgmma.mma_async.sync.aligned.m64n192k16.f32.bf16.bf16 "
    "{%0, %1, %2, %3, %4, %5, %6, %7, %8, %9, %10, %11, %12, %13, %14, %15, "
    "%16, %17, %18, %19, %20, %21, %22, %23, %24, %25, %26, %27, %28, %29, %30, %31, "
    "%32, %33, %34, %35, %36, %37, %38, %39, %40, %41, %42, %43, %44, %45, %46, %47, "
    "%48, %49, %50, %51, %52, %53, %54, %55, %56, %57, %58, %59, %60, %61, %62, %63, "
    "%64, %65, %66, %67, %68, %69, %70, %71, %72, %73, %74, %75, %76, %77, %78, %79, "
    "%80, %81, %82, %83, %84, %85, %86, %87, %88, %89, %90, %91, %92, %93, %94, %95}, "
    "da, db, p, 1, 1, 0, 1;\n}\n"
    : "+f"(d[0]), "+f"(d[1]), "+f"(d[2]), "+f"(d[3]), "+f"(d[4]), "+f"(d[5]), "+f"(d[6]), "+f"(d[7]),
      "+f"(d[8]), "+f"(d[9]), "+f"(d[10]), "+f"(d[11]), "+f"(d[12]), "+f"(d[13]), "+f"(d[14]), "+f"(d[15]),
      "+f"(d[16]), "+f"(d[17]), "+f"(d[18]), "+f"(d[19]), "+f"(d[20]), "+f"(d[21]), "+f"(d[22]), "+f"(d[23]),
      "+f"(d[24]), "+f"(d[25]), "+f"(d[26]), "+f"(d[27]), "+f"(d[28]), "+f"(d[29]), "+f"(d[30]), "+f"(d[31]),
      "+f"(d[32]), "+f"(d[33]), "+f"(d[34]), "+f"(d[35]), "+f"(d[36]), "+f"(d[37]), "+f"(d[38]), "+f"(d[39]),
      "+f"(d[40]), "+f"(d[41]), "+f"(d[42]), "+f"(d[43]), "+f"(d[44]), "+f"(d[45]), "+f"(d[46]), "+f"(d[47]),
      "+f"(d[48]), "+f"(d[49]), "+f"(d[50]), "+f"(d[51]), "+f"(d[52]), "+f"(d[53]), "+f"(d[54]), "+f"(d[55]),
      "+f"(d[56]), "+f"(d[57]), "+f"(d[58]), "+f"(d[59]), "+f"(d[60]), "+f"(d[61]), "+f"(d[62]), "+f"(d[63]),
      "+f"(d[64]), "+f"(d[65]), "+f"(d[66]), "+f"(d[67]), "+f"(d[68]), "+f"(d[69]), "+f"(d[70]), "+f"(d[71]),
      "+f"(d[72]), "+f"(d[73]), "+f"(d[74]), "+f"(d[75]), "+f"(d[76]), "+f"(d[77]), "+f"(d[78]), "+f"(d[79]),
      "+f"(d[80]), "+f"(d[81]), "+f"(d[82]), "+f"(d[83]), "+f"(d[84]), "+f"(d[85]), "+f"(d[86]), "+f"(d[87]),
      "+f"(d[88]), "+f"(d[89]), "+f"(d[90]), "+f"(d[91]), "+f"(d[92]), "+f"(d[93]), "+f"(d[94]), "+f"(d[95])
    : "r"(da), "r"(db), "r"(scale_d), "n"(AHI), "n"(BHI));
}
template <uint32_t AHI, uint32_t BHI>
__device__ __forceinline__ void wgmma_ss_n256_t1(float (&d)[128], uint32_t da, uint32_t db, int scale_d) {
  asm volatile("{\n.reg .pred p;\n.reg .b64 da, db;\n"
    "mov.b64 da, {%128, %131};\nmov.b64 db, {%129, %132};\n"
    "setp.ne.b32 p, %130, 0;\n"
    "wgmma.mma_async.sync.aligned.m64n256k16.f32.bf16.bf16 "
    "{%0, %1, %2, %3, %4, %5, %6, %7, %8, %9, %10, %11, %12, %13, %14, %15, "
    "%16, %17, %18, %19, %20, %21, %22, %23, %24, %25, %26, %27, %28, %29, %30, %31, "
    "%32, %33, %34, %35, %36, %37, %38, %39, %40, %41, %42, %43, %44, %45, %46, %47, "
    "%48, %49, %50, %51, %52, %53, %54, %55, %56, %57, %58, %59, %60, %61, %62, %63, "
    "%64, %65, %66, %67, %68, %69, %70, %71, %72, %73, %74, %75, %76, %77, %78, %79, "
    "%80, %81, %82, %83, %84, %85, %86, %87, %88, %89, %90, %91, %92, %93, %94, %95, "
    "%96, %97, %98, %99, %100, %101, %102, %103, %104, %105, %106, %107, %108, %109, %110, %111, "
    "%112, %113, %114, %115, %116, %117, %118, %119, %120, %121, %122, %123, %124, %125, %126, %127}, "
    "da, db, p, 1, 1, 0, 1;\n}\n"
    : "+f"(d[0]), "+f"(d[1]), "+f"(d[2]), "+f"(d[3]), "+f"(d[4]), "+f"(d[5]), "+f"(d[6]), "+f"(d[7]),
      "+f"(d[8]), "+f"(d[9]), "+f"(d[10]), "+f"(d[11]), "+f"(d[12]), "+f"(d[13]), "+f"(d[14]), "+f"(d[15]),
      "+f"(d[16]), "+f"(d[17]), "+f"(d[18]), "+f"(d[19]), "+f"(d[20]), "+f"(d[21]), "+f"(d[22]), "+f"(d[23]),
      "+f"(d[24]), "+f"(d[25]), "+f"(d[26]), "+f"(d[27]), "+f"(d[28]), "+f"(d[29]), "+f"(d[30]), "+f"(d[31]),
      "+f"(d[32]), "+f"(d[33]), "+f"(d[34]), "+f"(d[35]), "+f"(d[36]), "+f"(d[37]), "+f"(d[38]), "+f"(d[39]),
      "+f"(d[40]), "+f"(d[41]), "+f"(d[42]), "+f"(d[43]), "+f"(d[44]), "+f"(d[45]), "+f"(d[46]), "+f"(d[47]),
      "+f"(d[48]), "+f"(d[49]), "+f"(d[50]), "+f"(d[51]), "+f"(d[52]), "+f"(d[53]), "+f"(d[54]), "+f"(d[55]),
      "+f"(d[56]), "+f"(d[57]), "+f"(d[58]), "+f"(d[59]), "+f"(d[60]), "+f"(d[61]), "+f"(d[62]), "+f"(d[63]),
      "+f"(d[64]), "+f"(d[65]), "+f"(d[66]), "+f"(d[67]), "+f"(d[68]), "+f"(d[69]), "+f"(d[70]), "+f"(d[71]),
      "+f"(d[72]), "+f"(d[73]), "+f"(d[74]), "+f"(d[75]), "+f"(d[76]), "+f"(d[77]), "+f"(d[78]), "+f"(d[79]),
      "+f"(d[80]), "+f"(d[81]), "+f"(d[82]), "+f"(d[83]), "+f"(d[84]), "+f"(d[85]), "+f"(d[86]), "+f"(d[87]),
      "+f"(d[88]), "+f"(d[89]), "+f"(d[90]), "+f"(d[91]), "+f"(d[92]), "+f"(d[93]), "+f"(d[94]), "+f"(d[95]),
      "+f"(d[96]), "+f"(d[97]), "+f"(d[98]), "+f"(d[99]), "+f"(d[100]), "+f"(d[101]), "+f"(d[102]), "+f"(d[103]),
      "+f"(d[104]), "+f"(d[105]), "+f"(d[106]), "+f"(d[107]), "+f"(d[108]), "+f"(d[109]), "+f"(d[110]), "+f"(d[111]),
      "+f"(d[112]), "+f"(d[113]), "+f"(d[114]), "+f"(d[115]), "+f"(d[116]), "+f"(d[117]), "+f"(d[118]), "+f"(d[119]),
      "+f"(d[120]), "+f"(d[121]), "+f"(d[122]), "+f"(d[123]), "+f"(d[124]), "+f"(d[125]), "+f"(d[126]), "+f"(d[127])
    : "r"(da), "r"(db), "r"(scale_d), "n"(AHI), "n"(BHI));
}
__device__ __forceinline__ void wgmma6_rs_n24_t1(float (&d)[12], uint32_t a0, uint32_t a1, uint32_t a2, uint32_t a3, uint64_t db, int scale_d) {
  asm volatile("{\n.reg .pred p;\n"
    "setp.ne.b32 p, %17, 0;\n"
    "wgmma.mma_async.sync.aligned.m64n24k16.f32.bf16.bf16 "
    "{%0, %1, %2, %3, %4, %5, %6, %7, %8, %9, %10, %11}, "
    "{%12, %13, %14, %15}, %16, p, 1, 1, 1;\n}\n"
    : "+f"(d[0]), "+f"(d[1]), "+f"(d[2]), "+f"(d[3]), "+f"(d[4]), "+f"(d[5]), "+f"(d[6]), "+f"(d[7]),
      "+f"(d[8]), "+f"(d[9]), "+f"(d[10]), "+f"(d[11])
    : "r"(a0), "r"(a1), "r"(a2), "r"(a3), "l"(db), "r"(scale_d));
}
__device__ __forceinline__ void wgmma6_rs_n64_t0(float (&d)[32], uint32_t a0, uint32_t a1, uint32_t a2, uint32_t a3, uint64_t db, int scale_d) {
  asm volatile("{\n.reg .pred p;\n"
    "setp.ne.b32 p, %37, 0;\n"
    "wgmma.mma_async.sync.aligned.m64n64k16.f32.bf16.bf16 "
    "{%0, %1, %2, %3, %4, %5, %6, %7, %8, %9, %10, %11, %12, %13, %14, %15, "
    "%16, %17, %18, %19, %20, %21, %22, %23, %24, %25, %26, %27, %28, %29, %30, %31}, "
    "{%32, %33, %34, %35}, %36, p, 1, 1, 0;\n}\n"
    : "+f"(d[0]), "+f"(d[1]), "+f"(d[2]), "+f"(d[3]), "+f"(d[4]), "+f"(d[5]), "+f"(d[6]), "+f"(d[7]),
      "+f"(d[8]), "+f"(d[9]), "+f"(d[10]), "+f"(d[11]), "+f"(d[12]), "+f"(d[13]), "+f"(d[14]), "+f"(d[15]),
      "+f"(d[16]), "+f"(d[17]), "+f"(d[18]), "+f"(d[19]), "+f"(d[20]), "+f"(d[21]), "+f"(d[22]), "+f"(d[23]),
      "+f"(d[24]), "+f"(d[25]), "+f"(d[26]), "+f"(d[27]), "+f"(d[28]), "+f"(d[29]), "+f"(d[30]), "+f"(d[31])
    : "r"(a0), "r"(a1), "r"(a2), "r"(a3), "l"(db), "r"(scale_d));
}
__device__ __forceinline__ void wgmma6_ss_n80_t1(float (&d)[40], uint64_t da, uint64_t db, int scale_d) {
  asm volatile("{\n.reg .pred p;\n"
    "setp.ne.b32 p, %42, 0;\n"
    "wgmma.mma_async.sync.aligned.m64n80k16.f32.bf16.bf16 "
    "{%0, %1, %2, %3, %4, %5, %6, %7, %8, %9, %10, %11, %12, %13, %14, %15, "
    "%16, %17, %18, %19, %20, %21, %22, %23, %24, %25, %26, %27, %28, %29, %30, %31, "
    "%32, %33, %34, %35, %36, %37, %38, %39}, "
    "%40, %41, p, 1, 1, 0, 1;\n}\n"
    : "+f"(d[0]), "+f"(d[1]), "+f"(d[2]), "+f"(d[3]), "+f"(d[4]), "+f"(d[5]), "+f"(d[6]), "+f"(d[7]),
      "+f"(d[8]), "+f"(d[9]), "+f"(d[10]), "+f"(d[11]), "+f"(d[12]), "+f"(d[13]), "+f"(d[14]), "+f"(d[15]),
      "+f"(d[16]), "+f"(d[17]), "+f"(d[18]), "+f"(d[19]), "+f"(d[20]), "+f"(d[21]), "+f"(d[22]), "+f"(d[23]),
      "+f"(d[24]), "+f"(d[25]), "+f"(d[26]), "+f"(d[27]), "+f"(d[28]), "+f"(d[29]), "+f"(d[30]), "+f"(d[31]),
      "+f"(d[32]), "+f"(d[33]), "+f"(d[34]), "+f"(d[35]), "+f"(d[36]), "+f"(d[37]), "+f"(d[38]), "+f"(d[39])
    : "l"(da), "l"(db), "r"(scale_d));
}
__device__ __forceinline__ void wgmma6_ss_n144_t1(float (&d)[72], uint64_t da, uint64_t db, int scale_d) {
  asm volatile("{\n.reg .pred p;\n"
    "setp.ne.b32 p, %74, 0;\n"
    "wgmma.mma_async.sync.aligned.m64n144k16.f32.bf16.bf16 "
    "{%0, %1, %2, %3, %4, %5, %6, %7, %8, %9, %10, %11, %12, %13, %14, %15, "
    "%16, %17, %18, %19, %20, %21, %22, %23, %24, %25, %26, %27, %28, %29, %30, %31, "
    "%32, %33, %34, %35, %36, %37, %38, %39, %40, %41, %42, %43, %44, %45, %46, %47, "
    "%48, %49, %50, %51, %52, %53, %54, %55, %56, %57, %58, %59, %60, %61, %62, %63, "
    "%64, %65, %66, %67, %68, %69, %70, %71}, "
    "%72, %73, p, 1, 1, 0, 1;\n}\n"
    : "+f"(d[0]), "+f"(d[1]), "+f"(d[2]), "+f"(d[3]), "+f"(d[4]), "+f"(d[5]), "+f"(d[6]), "+f"(d[7]),
      "+f"(d[8]), "+f"(d[9]), "+f"(d[10]), "+f"(d[11]), "+f"(d[12]), "+f"(d[13]), "+f"(d[14]), "+f"(d[15]),
      "+f"(d[16]), "+f"(d[17]), "+f"(d[18]), "+f"(d[19]), "+f"(d[20]), "+f"(d[21]), "+f"(d[22]), "+f"(d[23]),
      "+f"(d[24]), "+f"(d[25]), "+f"(d[26]), "+f"(d[27]), "+f"(d[28]), "+f"(d[29]), "+f"(d[30]), "+f"(d[31]),
      "+f"(d[32]), "+f"(d[33]), "+f"(d[34]), "+f"(d[35]), "+f"(d[36]), "+f"(d[37]), "+f"(d[38]), "+f"(d[39]),
      "+f"(d[40]), "+f"(d[41]), "+f"(d[42]), "+f"(d[43]), "+f"(d[44]), "+f"(d[45]), "+f"(d[46]), "+f"(d[47]),
      "+f"(d[48]), "+f"(d[49]), "+f"(d[50]), "+f"(d[51]), "+f"(d[52]), "+f"(d[53]), "+f"(d[54]), "+f"(d[55]),
      "+f"(d[56]), "+f"(d[57]), "+f"(d[58]), "+f"(d[59]), "+f"(d[60]), "+f"(d[61]), "+f"(d[62]), "+f"(d[63]),
      "+f"(d[64]), "+f"(d[65]), "+f"(d[66]), "+f"(d[67]), "+f"(d[68]), "+f"(d[69]), "+f"(d[70]), "+f"(d[71])
    : "l"(da), "l"(db), "r"(scale_d));
}
__device__ __forceinline__ void wgmma6_ss_n256_t1(float (&d)[128], uint64_t da, uint64_t db, int scale_d) {
  asm volatile("{\n.reg .pred p;\n"
    "setp.ne.b32 p, %130, 0;\n"
    "wgmma.mma_async.sync.aligned.m64n256k16.f32.bf16.bf16 "
    "{%0, %1, %2, %3, %4, %5, %6, %7, %8, %9, %10, %11, %12, %13, %14, %15, "
    "%16, %17, %18, %19, %20, %21, %22, %23, %24, %25, %26, %27, %28, %29, %30, %31, "
    "%32, %33, %34, %35, %36, %37, %38, %39, %40, %41, %42, %43, %44, %45, %46, %47, "
    "%48, %49, %50, %51, %52, %53, %54, %55, %56, %57, %58, %59, %60, %61, %62, %63, "
    "%64, %65, %66, %67, %68, %69, %70, %71, %72, %73, %74, %75, %76, %77, %78, %79, "
    "%80, %81, %82, %83, %84, %85, %86, %87, %88, %89, %90, %91, %92, %93, %94, %95, "
    "%96, %97, %98, %99, %100, %101, %102, %103, %104, %105, %106, %107, %108, %109, %110, %111, "
    "%112, %113, %114, %115, %116, %117, %118, %119, %120, %121, %122, %123, %124, %125, %126, %127}, "
    "%128, %129, p, 1, 1, 0, 1;\n}\n"
    : "+f"(d[0]), "+f"(d[1]), "+f"(d[2]), "+f"(d[3]), "+f"(d[4]), "+f"(d[5]), "+f"(d[6]), "+f"(d[7]),
      "+f"(d[8]), "+f"(d[9]), "+f"(d[10]), "+f"(d[11]), "+f"(d[12]), "+f"(d[13]), "+f"(d[14]), "+f"(d[15]),
      "+f"(d[16]), "+f"(d[17]), "+f"(d[18]), "+f"(d[19]), "+f"(d[20]), "+f"(d[21]), "+f"(d[22]), "+f"(d[23]),
      "+f"(d[24]), "+f"(d[25]), "+f"(d[26]), "+f"(d[27]), "+f"(d[28]), "+f"(d[29]), "+f"(d[30]), "+f"(d[31]),
      "+f"(d[32]), "+f"(d[33]), "+f"(d[34]), "+f"(d[35]), "+f"(d[36]), "+f"(d[37]), "+f"(d[38]), "+f"(d[39]),
      "+f"(d[40]), "+f"(d[41]), "+f"(d[42]), "+f"(d[43]), "+f"(d[44]), "+f"(d[45]), "+f"(d[46]), "+f"(d[47]),
      "+f"(d[48]), "+f"(d[49]), "+f"(d[50]), "+f"(d[51]), "+f"(d[52]), "+f"(d[53]), "+f"(d[54]), "+f"(d[55]),
      "+f"(d[56]), "+f"(d[57]), "+f"(d[58]), "+f"(d[59]), "+f"(d[60]), "+f"(d[61]), "+f"(d[62]), "+f"(d[63]),
      "+f"(d[64]), "+f"(d[65]), "+f"(d[66]), "+f"(d[67]), "+f"(d[68]), "+f"(d[69]), "+f"(d[70]), "+f"(d[71]),
      "+f"(d[72]), "+f"(d[73]), "+f"(d[74]), "+f"(d[75]), "+f"(d[76]), "+f"(d[77]), "+f"(d[78]), "+f"(d[79]),
      "+f"(d[80]), "+f"(d[81]), "+f"(d[82]), "+f"(d[83]), "+f"(d[84]), "+f"(d[85]), "+f"(d[86]), "+f"(d[87]),
      "+f"(d[88]), "+f"(d[89]), "+f"(d[90]), "+f"(d[91]), "+f"(d[92]), "+f"(d[93]), "+f"(d[94]), "+f"(d[95]),
      "+f"(d[96]), "+f"(d[97]), "+f"(d[98]), "+f"(d[99]), "+f"(d[100]), "+f"(d[101]), "+f"(d[102]), "+f"(d[103]),
      "+f"(d[104]), "+f"(d[105]), "+f"(d[106]), "+f"(d[107]), "+f"(d[108]), "+f"(d[109]), "+f"(d[110]), "+f"(d[111]),
      "+f"(d[112]), "+f"(d[113]), "+f"(d[114]), "+f"(d[115]), "+f"(d[116]), "+f"(d[117]), "+f"(d[118]), "+f"(d[119]),
      "+f"(d[120]), "+f"(d[121]), "+f"(d[122]), "+f"(d[123]), "+f"(d[124]), "+f"(d[125]), "+f"(d[126]), "+f"(d[127])
    : "l"(da), "l"(db), "r"(scale_d));
}

__device__ __forceinline__ void wg_fence() { asm volatile("wgmma.fence.sync.aligned;" ::: "memory"); }
__device__ __forceinline__ void wg_commit() { asm volatile("wgmma.commit_group.sync.aligned;" ::: "memory"); }
template <int N> __device__ __forceinline__ void wg_wait() { asm volatile("wgmma.wait_group.sync.aligned %0;" ::"n"(N) : "memory"); }
__host__ __device__ constexpr uint32_t dlo(uint32_t off, uint32_t lbo) { return (off >> 4) | ((lbo >> 4) << 16); }
__host__ __device__ constexpr uint32_t dhi(uint32_t sbo, uint32_t swz) { return (sbo >> 4) | (swz << 30); }
constexpr uint32_t HI_X = dhi(512, 2), HI_W = dhi(1024, 1), HI_A2 = dhi(256, 0), HI_K = dhi(640, 0), HI_V = dhi(128, 0), HI_T = dhi(256, 0);
constexpr uint32_t QB0 = dlo(8192, 2048), QB1 = QB0 + 384, QT1 = 48;
__device__ __forceinline__ float ex2(float x) { float y; asm volatile("ex2.approx.ftz.f32 %0, %1;" : "=f"(y) : "f"(x)); return y; }
template <uint32_t HI> __device__ __forceinline__ uint64_t mkdesc(uint32_t lo) {
    uint64_t d;
    asm("mov.b64 %0, {%1, %2};" : "=l"(d) : "r"(lo), "n"(HI));
    return d;
}
__device__ __forceinline__ float rcp_fast(float x) { float y; asm("rcp.approx.ftz.f32 %0, %1;" : "=f"(y) : "f"(x)); return y; }
__device__ __forceinline__ float tanh_fast(float x) { float y; asm("tanh.approx.f32 %0, %1;" : "=f"(y) : "f"(x)); return y; }
__device__ __forceinline__ uint32_t pack(float lo, float hi) { uint32_t y; asm("cvt.rn.bf16x2.f32 %0, %1, %2;" : "=r"(y) : "f"(hi), "f"(lo)); return y; }
template <int N> __device__ __forceinline__ void fence_regs(float (&d)[N]) {
#pragma unroll
    for (int i = 0; i < N; i++) asm volatile("" : "+f"(d[i])::"memory");
}
template <int N> __device__ __forceinline__ void fence_regs(uint32_t (&d)[N]) {
#pragma unroll
    for (int i = 0; i < N; i++) asm volatile("" : "+r"(d[i])::"memory");
}
template <int N> __device__ __forceinline__ void undef_regs(float (&d)[N]) {
#pragma unroll
    for (int i = 0; i < N; i++) asm volatile("" : "=f"(d[i]));
}
__device__ __forceinline__ void mbar_init(uint32_t bar, uint32_t cnt) { asm volatile("mbarrier.init.shared::cta.b64 [%0], %1;" ::"r"(bar), "r"(cnt) : "memory"); }
__device__ __forceinline__ void mbar_expect_tx(uint32_t bar, uint32_t bytes) { asm volatile("mbarrier.arrive.expect_tx.shared::cta.b64 _, [%0], %1;" ::"r"(bar), "r"(bytes) : "memory"); }
__device__ __forceinline__ void mbar_arrive(uint32_t bar) { asm volatile("mbarrier.arrive.shared::cta.b64 _, [%0];" ::"r"(bar) : "memory"); }
__device__ __forceinline__ void mbar_arrive_cluster(uint32_t bar, uint32_t cta) {
    asm volatile("{\n.reg .b32 ra;\nmapa.shared::cluster.u32 ra, %0, %1;\nmbarrier.arrive.shared::cluster.b64 _, [ra];\n}" ::"r"(bar), "r"(cta) : "memory");
}
__device__ __forceinline__ void mbar_wait(uint32_t bar, uint32_t parity) {
    asm volatile(
        "{\n.reg .pred p;\n.reg .u32 n;\n"
        "mbarrier.try_wait.parity.shared::cta.b64 p, [%0], %1;\n"
        "@p bra.uni LAB_DONE;\n"
        "mov.u32 n, 0;\n"
        "LAB_WAIT:\n"
        "mbarrier.try_wait.parity.shared::cta.b64 p, [%0], %1, 1000;\n"
        "@p bra.uni LAB_DONE;\n"
        "add.u32 n, n, 1;\n"
        "setp.ge.u32 p, n, 0x400000;\n"
        "@p trap;\n"
        "bra.uni LAB_WAIT;\n"
        "LAB_DONE:\n}" ::"r"(bar), "r"(parity) : "memory");
}
__device__ __forceinline__ void flag_wait(const uint32_t* p, uint32_t target) {
    asm volatile(
        "{\n.reg .pred p;\n.reg .u32 n;\n.reg .s32 v;\n"
        "mov.u32 n, 0;\n"
        "LAB_WAIT:\n"
        "ld.acquire.gpu.global.s32 v, [%0];\n"
        "sub.s32 v, v, %1;\n"
        "setp.ge.s32 p, v, 0;\n"
        "@p bra.uni LAB_DONE;\n"
        "add.u32 n, n, 1;\n"
        "setp.ge.u32 p, n, 0x800000;\n"
        "@p trap;\n"
        "bra.uni LAB_WAIT;\n"
        "LAB_DONE:\n}" ::"l"(p), "r"(target) : "memory");
}
__device__ __forceinline__ uint32_t flag_wait_bits(const uint32_t* p, uint32_t base, uint32_t mask) {
    uint32_t v;
    asm volatile(
        "{\n.reg .pred p;\n.reg .u32 n, t;\n"
        "mov.u32 n, 0;\n"
        "LAB_WAIT:\n"
        "ld.acquire.gpu.global.u32 %0, [%1];\n"
        "sub.u32 %0, %0, %2;\n"
        "and.b32 t, %0, %3;\n"
        "setp.ne.u32 p, t, 0;\n"
        "@p bra.uni LAB_DONE;\n"
        "add.u32 n, n, 1;\n"
        "setp.ge.u32 p, n, 0x800000;\n"
        "@p trap;\n"
        "bra.uni LAB_WAIT;\n"
        "LAB_DONE:\n}" : "=&r"(v) : "l"(p), "r"(base), "r"(mask) : "memory");
    return v;
}
__device__ __forceinline__ void flag_add(uint32_t* p) { asm volatile("red.release.gpu.global.add.u32 [%0], 1;" ::"l"(p) : "memory"); }
__device__ __forceinline__ void flag_addv(uint32_t* p, uint32_t v) { asm volatile("red.release.gpu.global.add.u32 [%0], %1;" ::"l"(p), "r"(v) : "memory"); }
__device__ __forceinline__ void fence_async_global() { asm volatile("fence.proxy.async.global;" ::: "memory"); }
__device__ __forceinline__ void fence_async_shared() { asm volatile("fence.proxy.async.shared::cta;" ::: "memory"); }
__device__ __forceinline__ bool elect_one() {
    uint32_t p;
    asm volatile("{\n.reg .pred p;\nelect.sync _|p, 0xffffffff;\nselp.u32 %0, 1, 0, p;\n}" : "=r"(p));
    return p != 0;
}
__device__ __forceinline__ uint32_t mbar_test(uint32_t bar, uint32_t parity) {
    uint32_t p;
    asm volatile("{\n.reg .pred p;\nmbarrier.test_wait.parity.shared::cta.b64 p, [%1], %2;\nselp.u32 %0, 1, 0, p;\n}" : "=r"(p) : "r"(bar), "r"(parity) : "memory");
    return p;
}
__device__ __forceinline__ void mbar_wait_unless(uint32_t done, uint32_t bar, uint32_t parity) {
    asm volatile(
        "{\n.reg .pred p;\n.reg .u32 n;\n"
        "setp.ne.u32 p, %2, 0;\n"
        "@p bra.uni LAB_DONE;\n"
        "mov.u32 n, 0;\n"
        "LAB_WAIT:\n"
        "mbarrier.try_wait.parity.shared::cta.b64 p, [%0], %1, 1000;\n"
        "@p bra.uni LAB_DONE;\n"
        "add.u32 n, n, 1;\n"
        "setp.ge.u32 p, n, 0x400000;\n"
        "@p trap;\n"
        "bra.uni LAB_WAIT;\n"
        "LAB_DONE:\n}" ::"r"(bar), "r"(parity), "r"(done) : "memory");
}
__device__ __forceinline__ void bulk_s2g(void* dst, uint32_t src, uint32_t bytes) {
    asm volatile("cp.async.bulk.global.shared::cta.bulk_group [%0], [%1], %2;" ::"l"(dst), "r"(src), "r"(bytes) : "memory");
}
__device__ __forceinline__ void bulk_s2c(uint32_t addr, uint32_t bytes, uint32_t bar, uint32_t cta) {
    asm volatile("{\n.reg .b32 d, b;\nmapa.shared::cluster.u32 d, %0, %3;\nmapa.shared::cluster.u32 b, %2, %3;\n"
                 "cp.async.bulk.shared::cluster.shared::cta.mbarrier::complete_tx::bytes [d], [%0], %1, [b];\n}"
                 ::"r"(addr), "r"(bytes), "r"(bar), "r"(cta) : "memory");
}
__device__ __forceinline__ void sts32(uint32_t a, uint32_t v) { asm volatile("st.shared.u32 [%0], %1;" ::"r"(a), "r"(v) : "memory"); }
__device__ __forceinline__ void sts128(uint32_t a, uint32_t x, uint32_t y, uint32_t z, uint32_t w) { asm volatile("st.shared.v4.u32 [%0], {%1, %2, %3, %4};" ::"r"(a), "r"(x), "r"(y), "r"(z), "r"(w) : "memory"); }
__device__ __forceinline__ void stsm4(uint32_t a, uint32_t r0, uint32_t r1, uint32_t r2, uint32_t r3) {
    asm volatile("stmatrix.sync.aligned.m8n8.x4.shared.b16 [%0], {%1, %2, %3, %4};" ::"r"(a), "r"(r0), "r"(r1), "r"(r2), "r"(r3) : "memory");
}
__device__ __forceinline__ void ldsm4(uint32_t* r, uint32_t a) {
    asm volatile("ldmatrix.sync.aligned.m8n8.x4.shared.b16 {%0, %1, %2, %3}, [%4];" : "=r"(r[0]), "=r"(r[1]), "=r"(r[2]), "=r"(r[3]) : "r"(a) : "memory");
}
__device__ __forceinline__ uint32_t lds32(uint32_t a) { uint32_t v; asm volatile("ld.shared.u32 %0, [%1];" : "=r"(v) : "r"(a) : "memory"); return v; }
__device__ __forceinline__ void tma_2d(uint32_t dst, const CUtensorMap* tm, int c0, int c1, uint32_t bar) {
    asm volatile("cp.async.bulk.tensor.2d.shared::cluster.global.mbarrier::complete_tx::bytes [%0], [%1, {%3, %4}], [%2];"
                 ::"r"(dst), "l"(tm), "r"(bar), "r"(c0), "r"(c1) : "memory");
}
__device__ __forceinline__ void tma_2d_mc(uint32_t dst, const CUtensorMap* tm, int c0, int c1, uint32_t bar) {
    asm volatile("cp.async.bulk.tensor.2d.shared::cluster.global.mbarrier::complete_tx::bytes.multicast::cluster [%0], [%1, {%3, %4}], [%2], %5;"
                 ::"r"(dst), "l"(tm), "r"(bar), "r"(c0), "r"(c1), "h"((uint16_t)3) : "memory");
}
__device__ __forceinline__ void tma_3d_mc(uint32_t dst, const CUtensorMap* tm, int c0, int c1, int c2, uint32_t bar) {
    asm volatile("cp.async.bulk.tensor.3d.shared::cluster.global.mbarrier::complete_tx::bytes.multicast::cluster [%0], [%1, {%3, %4, %5}], [%2], %6;"
                 ::"r"(dst), "l"(tm), "r"(bar), "r"(c0), "r"(c1), "r"(c2), "h"((uint16_t)3) : "memory");
}
__device__ __forceinline__ void bulk_g2s(uint32_t dst, const void* src, uint32_t bytes, uint32_t bar) {
    asm volatile("cp.async.bulk.shared::cluster.global.mbarrier::complete_tx::bytes [%0], [%1], %2, [%3];"
                 ::"r"(dst), "l"(src), "r"(bytes), "r"(bar) : "memory");
}
__device__ __forceinline__ void bulk_g2s_mc(uint32_t dst, const void* src, uint32_t bytes, uint32_t bar) {
    asm volatile("cp.async.bulk.shared::cluster.global.mbarrier::complete_tx::bytes.multicast::cluster [%0], [%1], %2, [%3], %4;"
                 ::"r"(dst), "l"(src), "r"(bytes), "r"(bar), "h"((uint16_t)3) : "memory");
}
__device__ __forceinline__ void mma_16816(float* d, uint32_t a0, uint32_t a1, uint32_t a2, uint32_t a3, uint32_t b0, uint32_t b1) {
    asm volatile("mma.sync.aligned.m16n8k16.row.col.f32.bf16.bf16.f32 {%0,%1,%2,%3}, {%4,%5,%6,%7}, {%8,%9}, {%0,%1,%2,%3};"
                 : "+f"(d[0]), "+f"(d[1]), "+f"(d[2]), "+f"(d[3]) : "r"(a0), "r"(a1), "r"(a2), "r"(a3), "r"(b0), "r"(b1));
}
__device__ __forceinline__ uint32_t movm_t(uint32_t a) { uint32_t d; asm volatile("movmatrix.sync.aligned.m8n8.trans.b16 %0, %1;" : "=r"(d) : "r"(a)); return d; }
__device__ __forceinline__ uint32_t ldg32(const uint8_t* p) { uint32_t v; asm volatile("ld.global.u32 %0, [%1];" : "=r"(v) : "l"(p) : "memory"); return v; }
__device__ __forceinline__ void stg32(uint8_t* p, uint32_t v) { asm volatile("st.global.u32 [%0], %1;" ::"l"(p), "r"(v) : "memory"); }
#define PROF(i) do {} while (0)
#define TRACE() do {} while (0)
#define PROFX(w, i) do {} while (0)

struct Ring {
    uint32_t slot;
    uint32_t phase;
    __device__ __forceinline__ void next() { if (++slot == NSTAGE) { slot = 0; phase ^= 1; } }
};

__device__ __forceinline__ void load_q(uint32_t (&q)[8], uint32_t qa, int lane) {
    q[0] = lds32(qa + lane * 4);       q[1] = lds32(qa + lane * 4 + 256);
    q[2] = lds32(qa + lane * 4 + 128); q[3] = lds32(qa + lane * 4 + 384);
    const uint32_t t0 = lds32(qa + 512 + (lane & ~3)), t1 = lds32(qa + 544 + (lane & ~3));
    q[4] = (lane & 3) == 2 ? t0 : 0u;  q[5] = (lane & 3) == 2 ? t1 : 0u;
}

__device__ __forceinline__ bool norm_o(uint32_t (&w)[6], const float (&o)[12], int lane, uint32_t gaddr) {
    const float l0 = __shfl_sync(0xffffffffu, o[8], (lane & ~3) | 1);
    const float l1 = __shfl_sync(0xffffffffu, o[10], (lane & ~3) | 1);
    const float i0 = rcp_fast(l0) * __uint_as_float(lds32(gaddr)), i1 = rcp_fast(l1) * __uint_as_float(lds32(gaddr + 32));
    uint32_t big = 0;
#pragma unroll
    for (int b = 0; b < 3; b++) {
        w[2 * b] = pack(o[4 * b] * i0, o[4 * b + 1] * i0);
        w[2 * b + 1] = pack(o[4 * b + 2] * i1, o[4 * b + 3] * i1);
        if (b == 2 && (lane & 3) != 0) w[4] = w[5] = 0u;
        big |= ((w[2 * b] & 0x7F807F80u) + 0x00800080u) | ((w[2 * b + 1] & 0x7F807F80u) + 0x00800080u);
    }
    const bool ok = fminf(l0, l1) >= 0x1p-30f && l0 <= 0x1p100f && l1 <= 0x1p100f && (big & 0x80008000u) == 0;
    return !__all_sync(0xffffffffu, ok);
}

__device__ __forceinline__ void attn_true_max(float (&o)[12], const uint32_t (&q)[8], const uint8_t* kv) {
    float m0 = -INFINITY, m1 = -INFINITY;
#pragma unroll
    for (int i = 0; i < 12; i++) o[i] = 0.f;
#pragma unroll 1
    for (int kb = 0; kb < SEQ / 16; kb++) {
        uint32_t t[2][5];
#pragma unroll
        for (int g = 0; g < 2; g++)
#pragma unroll
            for (int ch = 0; ch < 5; ch++) t[g][ch] = ldg32(kv + (kb * 2 + g) * 640 + ch * 128);
        float s[2][4];
#pragma unroll
        for (int g = 0; g < 2; g++) {
            s[g][0] = s[g][1] = s[g][2] = s[g][3] = 0.f;
            mma_16816(s[g], q[0], q[1], q[2], q[3], t[g][0], t[g][1]);
            mma_16816(s[g], q[4], q[5], 0u, 0u, t[g][4], 0u);
        }
        float x0 = fmaxf(fmaxf(s[0][0], s[0][1]), fmaxf(s[1][0], s[1][1]));
        float x1 = fmaxf(fmaxf(s[0][2], s[0][3]), fmaxf(s[1][2], s[1][3]));
        x0 = fmaxf(x0, __shfl_xor_sync(0xffffffffu, x0, 1)); x0 = fmaxf(x0, __shfl_xor_sync(0xffffffffu, x0, 2));
        x1 = fmaxf(x1, __shfl_xor_sync(0xffffffffu, x1, 1)); x1 = fmaxf(x1, __shfl_xor_sync(0xffffffffu, x1, 2));
        const float n0 = fmaxf(m0, x0), n1 = fmaxf(m1, x1);
        const float u0 = (n0 == -INFINITY) ? 0.f : n0, u1 = (n1 == -INFINITY) ? 0.f : n1;
        const float c0 = ex2(m0 - u0), c1 = ex2(m1 - u1);
        m0 = n0; m1 = n1;
#pragma unroll
        for (int b = 0; b < 3; b++) { o[4 * b] *= c0; o[4 * b + 1] *= c0; o[4 * b + 2] *= c1; o[4 * b + 3] *= c1; }
        const uint32_t a0 = pack(ex2(s[0][0] - u0), ex2(s[0][1] - u0)), a1 = pack(ex2(s[0][2] - u1), ex2(s[0][3] - u1));
        const uint32_t a2 = pack(ex2(s[1][0] - u0), ex2(s[1][1] - u0)), a3 = pack(ex2(s[1][2] - u1), ex2(s[1][3] - u1));
#pragma unroll
        for (int b = 0; b < 3; b++) mma_16816(&o[4 * b], a0, a1, a2, a3, movm_t(t[0][2 + b]), movm_t(t[1][2 + b]));
    }
}

__device__ __forceinline__ float geglu2(float g, float u) {
    const float p = fmaf(g * g, 0.044715f * 0.7978845608028654f, 0.7978845608028654f);
    const float th = tanh_fast(g * p);
    const float y = g * u;
    return fmaf(y, th, y);
}

struct Attn {
    float s[32];
    float o[12];
    uint32_t p[16];
    uint32_t q[8];
};

__global__ void __cluster_dims__(2, 1, 1) __launch_bounds__(384, 1)
fused_kernel(__nv_bfloat16* __restrict__ out, const __nv_bfloat16* __restrict__ x, const __nv_bfloat16* __restrict__ gate_w,
             const uint8_t* __restrict__ wqkv, const uint8_t* __restrict__ wgt, const uint8_t* __restrict__ wu,
             const __grid_constant__ CUtensorMap tm_x, const __grid_constant__ CUtensorMap tm_qkv,
             const __grid_constant__ CUtensorMap tm_qkv8,
             const __grid_constant__ CUtensorMap tm_wg, const __grid_constant__ CUtensorMap tm_wu,
             const __grid_constant__ CUtensorMap tm_wd, const __grid_constant__ CUtensorMap tm_wo,
             const __grid_constant__ CUtensorMap tm_wd16, const __grid_constant__ CUtensorMap tm_wo16) {
    extern __shared__ uint8_t smem_raw[];
    const uint32_t sb = __shfl_sync(0xffffffffu, ((uint32_t)__cvta_generic_to_shared(smem_raw) + 1023) & ~1023u, 0);
    const uint32_t bars = sb + OFF_BAR;
    const uint32_t bar_full = bars, bar_empty = bars + 64;
    const uint32_t bar_ev = bars + 128;
    const uint32_t bar_rdy = bars + 256;
    const uint32_t bar_ep = bars + 320, bar_gate = bars + 328;
    const uint32_t bar_st = bars + 336;
    const uint32_t bar_late = bars + 408;
    const uint32_t bar_px = bars + 416;
    const uint32_t bar_free = bars + 424;
    const uint32_t s_epoch = bars + 448, s_zero = bars + 452, s_order = bars + 464, s_gate = bars + 512;

    const int cta = blockIdx.x >= NCTA ? blockIdx.x : ((blockIdx.x & 14) << 3) | ((blockIdx.x >> 4) << 1) | (blockIdx.x & 1);
    const int rank = cta & 1;
    const int j = (cta >> 1) & 7;
    const int m = (cta >> 4) * 2 + rank;
    const int hf = j >> 2, nt = j & 3;
    const int warp = __shfl_sync(0xffffffffu, threadIdx.x >> 5, 0);
    const int lane = threadIdx.x & 31;
    const int wg = warp >> 2;

    auto prefetch_stages = [&](int n) {
        const int t = threadIdx.x;
        const int row = (t >> 3) * 16 + m, sel = t & 7;
        const uint8_t* p = sel < 6 ? wqkv + (size_t)row * (3 * DM * 2) + (sel >> 1) * (DM * 2) + j * 128 + (sel & 1) * 128
                                   : (sel == 7 ? wu : wgt) + (size_t)row * (FF * 2) + (j * 576 + 512) * 2;
        if (t < n * 16) asm volatile("prefetch.global.L2 [%0];" ::"l"(p));
        p = (const uint8_t*)x + (size_t)(m * 128 + j * 16 + (t & 15)) * (DM * 2) + (t >> 4) * 128;
        if (t < n * 8) asm volatile("prefetch.global.L2 [%0];" ::"l"(p));
    };
    const bool leader = elect_one();
    if (leader) {
        mbar_init(warp < 6 ? bar_full + warp * 8 : bar_empty + (warp - 6) * 8, warp < 6 ? 2 : 4);
        asm volatile("fence.mbarrier_init.release.cluster;" ::: "memory");
    }
    asm volatile("barrier.cluster.arrive.relaxed.aligned;" ::: "memory");
    if (cta < NCTA && wg < 2) prefetch_stages(4);
    if (warp != 8) {
        if (leader && warp < 8) {
            const uint32_t lo = (warp >= 4 && warp <= 6) ? 1 : 4, hi = warp == 6 ? 4 : lo;
            mbar_init(bar_ev + warp * 32, lo); mbar_init(bar_ev + warp * 32 + 8, lo);
            mbar_init(bar_ev + warp * 32 + 16, hi); mbar_init(bar_ev + warp * 32 + 24, hi);
            if (warp < 4) mbar_init(bar_late + warp * 8, 1);
            sts32(s_zero, 0u); sts32(s_zero + 4, 0u);
            asm volatile("fence.mbarrier_init.release.cluster;" ::: "memory");
        }
        asm volatile("bar.sync 1, 352;" ::: "memory");
    }
    asm volatile("barrier.cluster.wait.acquire.aligned;" ::: "memory");

    if (wg == 2) {
        asm volatile("setmaxnreg.dec.sync.aligned.u32 24;");
        if (cta >= NCTA) {
            if (warp == 9 && elect_one()) {
                const uint32_t ep = g_flags[FL_E + cta * 32] + 1;
                g_flags[FL_E + cta * 32] = ep;
                mbar_wait(bar_ev + 2 * 8, 0);
                mbar_wait(bar_ev + 10 * 8, 0);
                flag_add(&g_flags[FL_G + (cta - NCTA) * 32]);
#pragma unroll 1
                for (int i = 0; i < 2; i++) {
                    const int jx = (cta - NCTA) * 2 + i;
                    flag_wait(&g_flags[FL_KV + jx * 32 + 1], ep * 32);
                    fence_async_global();
                    mbar_expect_tx(bar_rdy + i * 8, 20480 + 16 * 4608);
#pragma unroll 1
                    for (int p = 0; p < 8; p++) bulk_g2s(sb + 40960 + (i * 8 + p) * 9216, g_q3 + (p * 16 + jx * 2) * 4608, 9216, bar_rdy + i * 8);
                    bulk_g2s(sb + i * 20480, g_kv + (size_t)(jx * 4 + 3) * HEAD_BYTES + 28 * 5120, 20480, bar_rdy + i * 8);
                }
#pragma unroll 1
                for (int i = 0; i < 2; i++) {
                    mbar_wait(bar_ev + i * 8, 0);
                    mbar_wait(bar_ev + (8 + i) * 8, 0);
                    flag_add(&g_flags[FL_KV + ((cta - NCTA) * 2 + i) * 32 + 2]);
                }
            }
        } else if (warp == 8) {
            if (elect_one()) {
                Ring r{0, 1};
                const int row0 = m * 128;
                const CUtensorMap* tw = rank ? &tm_wu : &tm_wg;
                PROFX(0, 40); PROFX(1, 40);
#pragma unroll 1
                for (int kk = 0; kk < 18; kk++) {
                    if (kk == 1) { PROFX(0, 41); PROFX(1, 41); }
                    if (kk == 6) { PROFX(0, 42); PROFX(1, 42); }
                    const uint32_t st = sb + r.slot * SLOT, fb = bar_full + r.slot * 8;
                    mbar_wait(bar_empty + r.slot * 8, r.phase);
                    mbar_arrive(fb);
                    mbar_expect_tx(fb, 8192 + 12288 + 8192 + 1536);
                    tma_2d(st + OFF_AX, &tm_x, kk * 32, row0, fb);
                    tma_3d_mc(st + 8192 + rank * 6144, &tm_qkv, j * 72, kk * 32 + rank * 16, 0, fb);
                    tma_3d_mc(st + OFF_TL + rank * 768, &tm_qkv8, j * 72 + 64, kk * 32 + rank * 16, 0, fb);
                    tma_2d_mc(st + rank * 4096, tw, j * 576 + 512, kk * 32, fb);
                    r.next();
                }
                int k0 = DM - NSTAGE * 32;
#pragma unroll 1
                for (int t = 0; t < 4; t++)
#pragma unroll 1
                    for (int kk = 0; kk < 18; kk++) {
                        const uint32_t st = sb + r.slot * SLOT, fb = bar_full + r.slot * 8;
                        mbar_wait(bar_empty + r.slot * 8, r.phase);
                        if (t == 0 && kk < 2) mbar_arrive(fb);
                        const bool have_x = kk < NSTAGE;
                        mbar_expect_tx(fb, have_x ? 16384 : 8192 + 16384);
                        tma_2d_mc(st + rank * 8192, tw, j * 576 + t * 128, k0, fb);
                        tma_2d_mc(st + rank * 8192 + 4096, tw, j * 576 + t * 128 + 64, k0, fb);
                        if (!have_x) tma_2d(st + OFF_AX, &tm_x, k0, row0, fb);
                        k0 += kk == 17 ? DM + 32 - NSTAGE * 32 : 32;
                        if (k0 >= DM) k0 -= DM;
                        r.next();
                    }
                const uint8_t* a2 = g_a2 + (size_t)m * A2_TILE;
                mbar_wait(bar_rdy + 4 * 8, 0);
#pragma unroll 1
                for (int n = 0; n < 48; n++) {
                    const int u = n >> 2, jj = n & 3;
                    const uint32_t st = sb + r.slot * SLOT, fb = bar_full + r.slot * 8;
                    mbar_wait(bar_empty + r.slot * 8, r.phase);
                    mbar_expect_tx(fb, 12288 + 12288 + STRIPB);
                    const int ks = (hf * 4 + jj) * 36 + u * 3;
#pragma unroll
                    for (int b = 0; b < 2; b++) tma_2d_mc(st + b * 6144 + rank * 3072, &tm_wd, nt * 128 + (b ^ hf) * 64, ks * 16 + rank * 24, fb);
                    tma_2d_mc(st + 12288 + rank * 3072, &tm_wd16, 512 + nt * 16, ks * 16 + rank * 24, fb);
                    if (jj == 0) { mbar_wait(bar_rdy + ((3 * u + 2) >> 3) * 8, 0); fence_async_global(); }
                    bulk_g2s(st + OFF_A2, a2 + ks * 4096, 12288, fb);
                    r.next();
                }
#pragma unroll 1
                for (int n = 0; n < 4; n++) {
                    const uint32_t st = sb + r.slot * SLOT, fb = bar_full + r.slot * 8;
                    mbar_wait(bar_empty + r.slot * 8, r.phase);
                    mbar_expect_tx(fb, 12288 + 12288 + STRIPB);
                    const int pr = hf * 2 + (n & 1), head = (pr * 2 + rank) * 4 + (n >> 1);
#pragma unroll
                    for (int b = 0; b < 2; b++) tma_2d_mc(st + b * 6144 + rank * 3072, &tm_wo, nt * 128 + (b ^ hf) * 64, head * 18, fb);
                    tma_2d_mc(st + 12288 + rank * 3072, &tm_wo16, 512 + nt * 16, head * 18, fb);
                    if (n == 0) { mbar_wait(bar_rdy + 5 * 8, 0); fence_async_global(); }
                    bulk_g2s(st + OFF_A2, a2 + (288 + ((n >> 1) * 4 + pr) * 3) * 4096, 12288, fb);
                    r.next();
                }
                mbar_expect_tx(bar_late, 4 * (6144 + STRIPB));
#pragma unroll 1
                for (int n = 0; n < 8; n++) {
                    const uint32_t st = sb + r.slot * SLOT, fb = bar_full + r.slot * 8;
                    mbar_wait(bar_empty + r.slot * 8, r.phase);
                    if (n >= 2) mbar_arrive(fb);
                    if (n < 4) mbar_expect_tx(fb, 12288 + 6144 + STRIPB);
                    const int head = ((n & 3) * 2 + rank) * 4 + 2 + (n >> 2);
                    tma_2d_mc(st + rank * 3072, &tm_wo, nt * 128 + hf * 64, head * 18, n < 4 ? fb : bar_late);
                    tma_2d_mc(st + 6144 + rank * 3072, &tm_wo16, 512 + nt * 16, head * 18, n < 4 ? fb : bar_late);
                    if (n < 4) bulk_g2s(st + OFF_A2, a2 + (288 + (8 + n) * 3) * 4096, 12288, fb);
                    r.next();
                }
                mbar_wait(bar_ep, 0);
                const uint32_t base = (lds32(s_epoch) - 1) * 0x04040404u;
                uint32_t todo = 0x04040404u, k = 2;
#pragma unroll 1
                while (todo) {
                    const uint32_t got = flag_wait_bits(&g_flags[FL_M + m * 64 + FM_LATE], base, todo) & todo;
                    fence_async_global();
#pragma unroll 1
                    for (int pr = 0; pr < 4; pr++)
                        if ((got >> (pr * 8)) & 4) {
                            sts32(s_order + k * 4, (2 + pr) * (SLOT >> 4));
                            mbar_expect_tx(bar_full + k * 8, 12288);
                            bulk_g2s(sb + k * SLOT + OFF_A2, a2 + (288 + (12 + pr) * 3) * 4096, 12288, bar_full + k * 8);
                            k++;
                        }
                    todo &= ~got;
                }
                PROFX(0, 50); PROFX(1, 50);
            }
        } else if (warp == 9) {
            if (elect_one()) {
                const uint32_t ep = g_flags[FL_E + cta * 32] + 1;
                g_flags[FL_E + cta * 32] = ep;
                sts32(s_epoch, ep);
                mbar_arrive(bar_ep);
                Ring r{0, 1};
                const uint8_t* kv = g_kv + (size_t)(j * 4) * HEAD_BYTES + rank * 2560;
                const int rot = (cta >> 4) * 4;
                uint32_t have = flag_wait_bits(&g_flags[FL_KV + j * 32], (ep - 1) * 0x44444444u, 4u << rot);
                fence_async_global();
#pragma unroll 1
                for (int it = 4; it < 124; it++) {
                    const uint32_t fb = bar_full + r.slot * 8;
                    if (it < 32 && !((have >> ((it + rot) & 28)) & 4)) {
                        have = flag_wait_bits(&g_flags[FL_KV + j * 32], (ep - 1) * 0x44444444u, 4u << ((it + rot) & 28));
                        fence_async_global();
                    }
                    if (it == 4) { PROFX(0, 37); PROFX(1, 37); }
                    if (it == 24) { flag_wait(&g_flags[FL_KV + j * 32 + 1], ep * 32); fence_async_global(); }
                    mbar_wait(bar_empty + r.slot * 8, r.phase);
                    mbar_expect_tx(fb, 5120);
                    bulk_g2s_mc(sb + r.slot * SLOT + OFF_KV + rank * 2560, kv + (it < 32 ? (it + rot) & 31 : it) * 5120, 2560, fb);
                    r.next();
                }
                flag_wait(&g_flags[FL_KV + j * 32 + 2], ep);
                mbar_arrive(bar_px);
                uint32_t* fr = &g_flags[FL_M + m * 64 + FM_R];
                mbar_wait(bar_ev + 6 * 8, 0);
                mbar_wait(bar_ev + 14 * 8, 0);
                PROFX(0, 51); PROFX(1, 51);
                flag_add(fr + j);
                PROFX(0, 52); PROFX(1, 52);
                flag_wait(fr + (j ^ 4), ep);
                PROFX(0, 53); PROFX(1, 53);
                mbar_arrive(bar_rdy + 6 * 8);
            }
        } else {
            const int w = warp - 10;
            if (elect_one()) {
                const uint32_t mine = 2 + rank * 2 + w, other = 2 + (rank ^ 1) * 2 + w;
                mbar_wait(bar_st + w * 8, 0);
                PROFX(w, 32);
                bulk_s2g(g_kv + (size_t)(j * 4) * HEAD_BYTES + (m * 16 + w * 8) * 640, sb + mine * SLOT + OFF_KV, 5120);
                asm volatile("cp.async.bulk.commit_group;" ::: "memory");
                mbar_arrive(bar_full + mine * 8);
                mbar_expect_tx(bar_full + other * 8, 5120);
#pragma unroll 1
                for (int i = 0; i < 2; i++) {
                    if (i == rank) {
                        mbar_wait(bar_empty + mine * 8, 0);
                        bulk_s2c(sb + mine * SLOT + OFF_KV, 5120, bar_full + mine * 8, rank ^ 1);
                    } else {
                        asm volatile("cp.async.bulk.wait_group 0;" ::: "memory");
                        flag_addv(&g_flags[FL_KV + j * 32], 1u << ((cta >> 4) * 4));
                    }
                }
                PROFX(w, 34);
                mbar_wait(bar_st + (2 + w) * 8, 0);
                __nanosleep(1500);
                bulk_s2g(g_q3 + cta * 4608 + w * 2304, sb + OFF_Q + 3 * 4608 + w * 2304, 2304);
#pragma unroll 1
                for (int h = 1; h < 4; h++) {
                    __nanosleep(200);
                    bulk_s2g(g_kv + (size_t)(j * 4 + h) * HEAD_BYTES + (m * 16 + w * 8) * 640, sb + (w * 3 + h - 1) * SLOT + OFF_GAP, 5120);
                    asm volatile("cp.async.bulk.commit_group;\ncp.async.bulk.wait_group 0;" ::: "memory");
                }
                mbar_arrive(bar_free + w * 8);
                flag_add(&g_flags[FL_KV + j * 32 + 1]);
                PROFX(w, 35);
            }
            __syncwarp();
            uint32_t* fm = &g_flags[FL_M + m * 64];
            mbar_wait(bar_ep, 0);
            const uint32_t ep = lds32(s_epoch);
            if (w == 1) {
                flag_wait(&g_flags[FL_G + (m >> 2) * 32], ep);
                const uint4 gv = __ldcg((const uint4*)(g_gate + m * 128) + lane);
                sts128(s_gate + lane * 16, gv.x, gv.y, gv.z, gv.w);
                __syncwarp();
                if (lane == 0) mbar_arrive(bar_gate);
            }
            if (elect_one()) {
#pragma unroll 1
                for (int i = 0; i < 6; i++) {
                    const int e = i == 0 ? 4 : i == 5 ? 5 : i - 1;
                    mbar_wait(bar_ev + (w * 8 + e) * 8, 0);
                    if (e < 3) {
                        uint8_t* hp = g_a2 + (size_t)m * A2_TILE + (j * 36 + e * 8) * 4096 + w * 2048;
#pragma unroll 1
                        for (int k = 0; k < 8; k++) {
                            const int g = (k * 11) >> 5;
                            bulk_s2g(hp + k * 4096, sb + (w * 3 + g) * SLOT + OFF_GAP + (k - g * 3) * 2048, 2048);
                        }
                        asm volatile("cp.async.bulk.commit_group;\ncp.async.bulk.wait_group 0;" ::: "memory");
                    }
                    uint32_t* fl = fm + FM_H + (e == 5 ? 5 : hf * 8 + e);
                    flag_add(fl);
                    if (w == 0) { flag_wait(fl, ep * (e == 5 ? 16 : 8)); mbar_arrive(bar_rdy + e * 8); }
                }
                mbar_wait(bar_ev + (w * 8 + 7) * 8, 0);
                PROFX(w, 48);
                flag_addv(fm + FM_LATE, 1u << ((j >> 1) * 8));
                PROFX(w, 49);
            }
        }
    } else {
        asm volatile("setmaxnreg.inc.sync.aligned.u32 240;");
        const int wq = warp & 3;
        const int c = lane & 3;
        const int tid = threadIdx.x & 127;
        const int grp = wg * 8 + wq * 2;
        const uint32_t sbd = (sb & 0x3FFFF) >> 4;
        uint32_t sd = sbd, pd = sbd, fb = bar_full, pb = bar_full, ph = 0;
#define STAGE_NEXT do { pd = sd; sd = (sd == sbd + (NSTAGE - 1) * (SLOT >> 4)) ? sbd : sd + (SLOT >> 4);           \
                        pb = fb; fb += 8; if (fb == bar_full + NSTAGE * 8) { fb = bar_full; ph ^= 1; } } while (0)
        auto release = [&]() { if (tid < 2) mbar_arrive_cluster(pb + 64, tid); };
        auto signal = [&](int e) { __syncwarp(); if (lane == 0) mbar_arrive(bar_ev + (wg * 8 + e) * 8); };
        if (cta >= NCTA) {
            PROF(0);
            {
                float wv[72];
#pragma unroll
                for (int i = 0; i < 9; i++) {
                    const uint4 t = __ldg((const uint4*)gate_w + (lane & 7) + i * 8);
                    const uint32_t u[4] = {t.x, t.y, t.z, t.w};
#pragma unroll
                    for (int e = 0; e < 4; e++) { wv[8 * i + 2 * e] = __uint_as_float(u[e] << 16); wv[8 * i + 2 * e + 1] = __uint_as_float(u[e] & 0xffff0000u); }
                }
                __nanosleep(1500);
#pragma unroll 1
                for (int b = 0; b < 8; b++) {
                    const int row = (cta - NCTA) * 512 + warp * 64 + b * 8 + (lane >> 3);
                    uint4 xa[2][9];
#pragma unroll
                    for (int r = 0; r < 2; r++)
#pragma unroll
                        for (int i = 0; i < 9; i++) xa[r][i] = __ldg((const uint4*)(x + (size_t)(row + r * 4) * DM) + (lane & 7) + i * 8);
#pragma unroll
                    for (int r = 0; r < 2; r++) {
                        float z = 0.f, y = 0.f;
#pragma unroll
                        for (int i = 0; i < 9; i++) {
                            const uint32_t u[4] = {xa[r][i].x, xa[r][i].y, xa[r][i].z, xa[r][i].w};
#pragma unroll
                            for (int e = 0; e < 4; e++) {
                                z = fmaf(__uint_as_float(u[e] << 16), wv[8 * i + 2 * e], z);
                                y = fmaf(__uint_as_float(u[e] & 0xffff0000u), wv[8 * i + 2 * e + 1], y);
                            }
                        }
                        z += y;
#pragma unroll
                        for (int d = 1; d < 8; d <<= 1) z += __shfl_xor_sync(0xffffffffu, z, d);
                        if ((lane & 7) == 0) g_gate[row + r * 4] = rcp_fast(1.f + ex2(-1.4426950408889634f * z));
                    }
                }
                signal(2);
                PROF(2);
            }
            float s0[64], s1[64], o[12];
            uint32_t p0[32], p1[32], q[8];
            q[6] = lds32(s_zero); q[7] = lds32(s_zero + 4);
#pragma unroll
            for (int i = 0; i < 12; i++) o[i] = 0.f;
            auto store_px = [&](int u) {
                const int src = ((u & 15) >> 1) * 16 + ((cta - NCTA) * 2 + (u >> 4)) * 2 + (u & 1);
                float4* dst = g_px + (size_t)(src * 2 + wg) * 3 * 128 + tid;
#pragma unroll
                for (int i = 0; i < 3; i++) __stcg(dst + i * 128, make_float4(o[4 * i], o[4 * i + 1], o[4 * i + 2], o[4 * i + 3]));
            };
            mbar_wait(bar_rdy, 0);
            PROF(1);
            load_q(q, sb + 40960 + warp * 576, lane);
            fence_regs(q); fence_regs(o);
            wg_fence();
            wgmma_rs_n128_t0<HI_K>(s0, q[0], q[1], q[2], q[3], sbd + dlo(0, 128), 0);
            wgmma_rs_n128_t0<HI_K>(s0, q[4], q[5], q[6], q[7], sbd + dlo(512, 0), 1);
            wg_commit();
            wg_wait<0>();
            fence_regs(s0);
#pragma unroll 1
            for (int u = 0; u < 32; u++) {
                const uint32_t kb = sbd + (u >> 4) * 1280;
                wg_fence();
                wgmma_rs_n128_t0<HI_K>(s1, q[0], q[1], q[2], q[3], kb + dlo(10240, 128), 0);
                wgmma_rs_n128_t0<HI_K>(s1, q[4], q[5], q[6], q[7], kb + dlo(10240 + 512, 0), 1);
                wg_commit();
#pragma unroll
                for (int i = 0; i < 32; i++) p0[i] = pack(ex2(s0[2 * i]), ex2(s0[2 * i + 1]));
                fence_regs(p0);
                wg_wait<0>();
                fence_regs(o); fence_regs(s1); fence_regs(q);
                store_px(u > 0 ? u - 1 : 0);
                if (u == 16) signal(0);
                if (u == 15) mbar_wait(bar_rdy + 8, 0);
                const int un = u < 31 ? u + 1 : u;
                load_q(q, sb + 40960 + un * 4608 + warp * 576, lane);
                fence_regs(q);
                const uint32_t kn = sbd + (un >> 4) * 1280;
                wg_fence();
#pragma unroll
                for (int i = 0; i < 8; i++) wgmma_rs_n24_t1<HI_V>(o, p0[4 * i], p0[4 * i + 1], p0[4 * i + 2], p0[4 * i + 3], kb + dlo(256, 640) + 80 * i, i != 0);
                wgmma_rs_n128_t0<HI_K>(s0, q[0], q[1], q[2], q[3], kn + dlo(0, 128), 0);
                wgmma_rs_n128_t0<HI_K>(s0, q[4], q[5], q[6], q[7], kn + dlo(512, 0), 1);
                wg_commit();
#pragma unroll
                for (int i = 0; i < 32; i++) p1[i] = pack(ex2(s1[2 * i]), ex2(s1[2 * i + 1]));
                fence_regs(p1);
                wg_fence();
#pragma unroll
                for (int i = 0; i < 8; i++) wgmma_rs_n24_t1<HI_V>(o, p1[4 * i], p1[4 * i + 1], p1[4 * i + 2], p1[4 * i + 3], kb + dlo(10240 + 256, 640) + 80 * i, 1);
                wg_commit();
                wg_wait<1>();
                fence_regs(s0); fence_regs(p0);
            }
            wg_wait<0>();
            fence_regs(o);
            store_px(31);
            signal(1);
            PROF(20);
            return;
        }
        Attn at;
        PROF(0);

        uint8_t* a2w = g_a2 + (size_t)m * A2_TILE + grp * 256 + lane * 4;
        const uint32_t qa = sb + OFF_Q + warp * 576;
        float acc[128];
        {
            float qkv[96], tl[12], gu[64];
            const uint32_t xrow = wg * 64 + wq * 16 + (lane & 15);
            const uint32_t xa0 = (sb & ~0x3FFFFu) + OFF_AX + xrow * 64 + (((lane >> 4) ^ ((xrow >> 1) & 3)) << 4);
            uint32_t xf[2][8];
#pragma unroll 1
            for (int k2 = 0; k2 < 18 - DEFER; k2 += 2) {
#pragma unroll
                for (int h = 0; h < 2; h++) {
                    const int kk = k2 + h;
                    mbar_wait(fb, ph);
                    if (kk == 0) PROF(21);
                    if (kk == 6) PROF(22);
                    if (kk == 12) PROF(23);
                    ldsm4(&xf[h][0], xa0 + sd * 16);
                    ldsm4(&xf[h][4], (xa0 ^ 32) + sd * 16);
                    fence_regs(xf[h]);
                    const uint32_t db = sd + dlo(0, 4096), dt = sd + dlo(OFF_TL, 128);
                    wg_fence();
                    wgmma_rs_n192_t1<HI_W>(qkv, xf[h][0], xf[h][1], xf[h][2], xf[h][3], sd + QB0, kk != 0);
                    wgmma_rs_n24_t1<HI_T>(tl, xf[h][0], xf[h][1], xf[h][2], xf[h][3], dt, kk != 0);
                    wgmma_rs_n128_t1<HI_W>(gu, xf[h][0], xf[h][1], xf[h][2], xf[h][3], db, kk != 0);
                    wgmma_rs_n192_t1<HI_W>(qkv, xf[h][4], xf[h][5], xf[h][6], xf[h][7], sd + QB1, 1);
                    wgmma_rs_n24_t1<HI_T>(tl, xf[h][4], xf[h][5], xf[h][6], xf[h][7], dt + QT1, 1);
                    wgmma_rs_n128_t1<HI_W>(gu, xf[h][4], xf[h][5], xf[h][6], xf[h][7], db + 128, 1);
                    wg_commit();
                    wg_wait<1>();
                    if (kk > 0) release();
                    STAGE_NEXT;
                }
            }
#pragma unroll
            for (int kk = 0; kk < DEFER; kk++) {
                mbar_wait(fb + kk * 8, ph);
                const uint32_t st = sd + kk * (SLOT >> 4);
                const uint32_t da = st + wg * 256 + dlo(OFF_AX, 16), dt = st + dlo(OFF_TL, 128);
                wg_fence();
                wgmma_ss_n192_t1<HI_X, HI_W>(qkv, da, st + QB0, 1);
                wgmma_ss_n24_t1<HI_X, HI_T>(tl, da, dt, 1);
                wgmma_ss_n192_t1<HI_X, HI_W>(qkv, da + 2, st + QB1, 1);
                wgmma_ss_n24_t1<HI_X, HI_T>(tl, da + 2, dt + QT1, 1);
                wg_commit();
                if (kk == 0) { wg_wait<1>(); release(); }
            }
#pragma unroll
            for (int kk = 0; kk < DEFER; kk++) {
                const uint32_t st = sd + kk * (SLOT >> 4);
                const uint32_t da = st + wg * 256 + dlo(OFF_AX, 16), db = st + dlo(0, 4096);
                wgmma_ss_n128_t1<HI_X, HI_W>(gu, da, db, 1);
                wgmma_ss_n128_t1<HI_X, HI_W>(gu, da + 2, db + 128, 1);
            }
            wg_commit();
            wg_wait<1>();
            fence_regs(qkv); fence_regs(tl);
            PROF(1);
            constexpr float QS = 0.23570226039551584f * 1.4426950408889634f;
            uint32_t kp[9][2], vp[9][2];
#pragma unroll
            for (int i = 0; i < 9; i++) {
                const float* k4 = i < 8 ? &qkv[32 + 4 * i] : &tl[4];
                const float* v4 = i < 8 ? &qkv[64 + 4 * i] : &tl[8];
                kp[i][0] = pack(k4[0], k4[1]); kp[i][1] = pack(k4[2], k4[3]);
                vp[i][0] = pack(v4[0], v4[1]); vp[i][1] = pack(v4[2], v4[3]);
            }
            const int quad = lane & ~3;
            const uint32_t cst = c == 1 ? 0x3F80u : 0u;
            {
                const uint32_t a = sb + (2 + rank * 2 + wg) * SLOT + OFF_KV + wq * 1280 + lane * 4;
#pragma unroll
                for (int r = 0; r < 2; r++) {
                    const uint32_t kt = __shfl_sync(0xffffffffu, kp[2][r], quad);
                    sts32(a + r * 640, kp[0][r]);       sts32(a + r * 640 + 128, kp[1][r]);
                    sts32(a + r * 640 + 256, vp[0][r]); sts32(a + r * 640 + 384, vp[1][r]);
                    sts32(a + r * 640 + 512, c == 0 ? vp[2][r] : c == 2 ? kt : cst);
                }
                fence_async_shared();
                __syncwarp();
                if (lane == 0) mbar_arrive(bar_st + wg * 8);
            }
            PROF(2);
#pragma unroll
            for (int i = 0; i < 9; i++) {
                const float* q4 = i < 8 ? &qkv[4 * i] : &tl[0];
                const uint32_t q0 = pack(q4[0] * QS, q4[1] * QS), q1 = pack(q4[2] * QS, q4[3] * QS);
                if (i < 2) { at.q[2 * i] = q0; at.q[2 * i + 1] = q1; }
                else {
                    if (i == 2) {
                        const uint32_t t0 = __shfl_sync(0xffffffffu, q0, quad), t1 = __shfl_sync(0xffffffffu, q1, quad);
                        at.q[4] = c == 2 ? t0 : 0u; at.q[5] = c == 2 ? t1 : 0u;
                    }
                    const int lc = 8 * i + 2 * c;
                    const int hd = (lc * 3641) >> 16;
                    const int d = lc - hd * 18;
                    const bool last = (i & 1) == 0 && c == i / 2 - 1;
                    const uint32_t aq = qa + hd * 4608 + (last ? 512 + (lane >> 2) * 4 : (d >> 3) * 128 + (d & 7) * 2 + (lane >> 2) * 16);
                    if (i > 2 || c > 0) { sts32(aq, q0); sts32(aq + (last ? 32 : 256), q1); }
                }
            }
            mbar_wait(bar_st, 0);
            mbar_wait(bar_st + 8, 0);
#pragma unroll
            for (int i = 2; i < 9; i++) {
                const int lc = 8 * i + 2 * c;
                const int hd = (lc * 3641) >> 16;
                const int d = lc - hd * 18;
                const uint32_t ak = sb + (wg * 3 - 1 + hd) * SLOT + OFF_GAP + wq * 1280 + (lane >> 2) * 16;
                const uint32_t off = (d >> 3) * 128 + (d & 7) * 2;
                if ((i & 1) == 0 && c == i / 2 - 1) {
                    if (i > 2) { sts128(ak + 512, vp[i][0], 0x3F80u, kp[i][0], 0u); sts128(ak + 512 + 640, vp[i][1], 0x3F80u, kp[i][1], 0u); }
                } else {
                    sts32(ak + off, kp[i][0]); sts32(ak + off + 640, kp[i][1]); sts32(ak + off + 256, vp[i][0]); sts32(ak + off + 256 + 640, vp[i][1]);
                }
            }
            fence_async_shared();
            __syncwarp();
            if (lane == 0) mbar_arrive(bar_st + (2 + wg) * 8);
            PROF(39);
            wg_wait<0>();
            fence_regs(gu);
            if (tid < 2 * DEFER) mbar_arrive_cluster(fb + 64 + (tid >> 1) * 8, tid & 1);
#pragma unroll
            for (int kk = 0; kk < 2; kk++) {
                mbar_wait(bar_full + kk * 8, 1);
                const uint32_t st = sbd + kk * (SLOT >> 4);
                const uint32_t da = st + wg * 256 + dlo(OFF_AX, 16), db = st + dlo(0, 4096);
                wg_fence();
                wgmma_ss_n256_t1<HI_X, HI_W>(acc, da, db, kk);
                wgmma_ss_n256_t1<HI_X, HI_W>(acc, da + 2, db + 128, 1);
                wg_commit();
            }
            sd = sbd + 2 * (SLOT >> 4); fb = bar_full + 16; pb = bar_full; ph = 1;
            uint8_t* hp = a2w + (j * 36 + 32) * 4096;
#pragma unroll
            for (int i = 0; i < 16; i++)
                stg32(hp + (i >> 2) * 4096 + ((i >> 1) & 1) * 128 + (i & 1) * 256, pack(geglu2(gu[2 * i], gu[32 + 2 * i]), geglu2(gu[2 * i + 1], gu[32 + 2 * i + 1])));
            signal(4);
            PROF(3);
            wg_wait<1>();
            release();
            mbar_wait(fb, ph);
            PROF(38);
        }

        const uint32_t gaddr = s_gate + (grp * 8 + (lane >> 2)) * 4;
        at.q[6] = lds32(s_zero); at.q[7] = lds32(s_zero + 4);
#pragma unroll
        for (int i = 0; i < 16; i++) at.p[i] = 0u;
#pragma unroll
        for (int i = 0; i < 12; i++) at.o[i] = 0.f;
        fence_regs(at.q); fence_regs(at.p); fence_regs(at.o);
        pd = sd;
        uint32_t rel = bar_empty + 8;
        asm volatile("mapa.shared::cluster.u32 %0, %0, %1;" : "+r"(rel) : "r"(tid & 1));
        const uint32_t rel_off = rel - (bar_full + 8);

#define ISSUE_PV() do {                                                                                            \
            const uint32_t dv = pd + dlo(OFF_KV + 256, 640);                                                       \
            wgmma_rs_n24_t1<HI_V>(at.o, at.p[0], at.p[1], at.p[2], at.p[3], dv, 1);                                \
            wgmma_rs_n24_t1<HI_V>(at.o, at.p[4], at.p[5], at.p[6], at.p[7], dv + 80, 1);                           \
            wgmma_rs_n24_t1<HI_V>(at.o, at.p[8], at.p[9], at.p[10], at.p[11], dv + 160, 1);                        \
            wgmma_rs_n24_t1<HI_V>(at.o, at.p[12], at.p[13], at.p[14], at.p[15], dv + 240, 1);                      \
        } while (0)
#define EXPS() do {                                                                                                \
            _Pragma("unroll") for (int i = 0; i < 16; i++) at.p[i] = pack(ex2(at.s[2 * i]), ex2(at.s[2 * i + 1])); \
            fence_regs(at.p);                                                                                      \
        } while (0)
#define FUSED_STEP(DV, DK, NB, NPH, REL, GEMM_CODE) do {                                                           \
            wg_fence();                                                                                            \
            wgmma6_rs_n24_t1(at.o, at.p[0], at.p[1], at.p[2], at.p[3], (DV), 1);                                   \
            wgmma6_rs_n24_t1(at.o, at.p[4], at.p[5], at.p[6], at.p[7], (DV) + 80, 1);                              \
            wgmma6_rs_n24_t1(at.o, at.p[8], at.p[9], at.p[10], at.p[11], (DV) + 160, 1);                           \
            wgmma6_rs_n24_t1(at.o, at.p[12], at.p[13], at.p[14], at.p[15], (DV) + 240, 1);                         \
            wgmma6_rs_n64_t0(at.s, at.q[0], at.q[1], at.q[2], at.q[3], (DK) + dlo(0, 128), 0);                     \
            wgmma6_rs_n64_t0(at.s, at.q[4], at.q[5], at.q[6], at.q[7], (DK) + 32, 1);                              \
            wg_commit();                                                                                           \
            GEMM_CODE;                                                                                             \
            wg_commit();                                                                                           \
            const uint32_t rdy = mbar_test(NB, NPH);                                                               \
            wg_wait<1>();                                                                                          \
            fence_regs(at.s); fence_regs(at.p);                                                                    \
            if (tid < 2) asm volatile("mbarrier.arrive.shared::cluster.b64 _, [%0];" ::"r"(REL) : "memory");       \
            EXPS();                                                                                                \
            mbar_wait_unless(rdy, NB, NPH);                                                                        \
        } while (0)
#define FUSED_PAIR(HIA, LOA, LOB, STEP0, GEMM) do {                                                                \
            const uint64_t dv0 = mkdesc<HI_V>(pd + dlo(OFF_KV + 256, 640));                                        \
            const uint64_t dv1 = mkdesc<HI_V>(sd + dlo(OFF_KV + 256, 640));                                        \
            const uint64_t dk = mkdesc<HI_K>(sd + dlo(OFF_KV, 0));                                                 \
            const uint64_t da = mkdesc<HIA>(sd + (LOA)), db = mkdesc<HI_W>(sd + (LOB));                            \
            STEP0(dv0, dk, fb + 8, ph, rel, GEMM(da, db, first));                                                  \
            const uint32_t r1 = fb + rel_off;                                                                      \
            rel = r1 + 8;                                                                                          \
            pd = sd + (SLOT >> 4); pb = fb + 8;                                                                    \
            if (fb == bar_full + (NSTAGE - 2) * 8) { fb = bar_full; ph ^= 1; } else fb += 16;                      \
            sd = (sd == sbd + (NSTAGE - 2) * (SLOT >> 4)) ? sbd : sd + 2 * (SLOT >> 4);                            \
            FUSED_STEP(dv1, dk + (SLOT >> 4), fb, ph, r1, GEMM(da + (SLOT >> 4), db + (SLOT >> 4), 1));            \
            first = 1;                                                                                             \
            TRACE();                                                                                               \
        } while (0)
#define GEMM_256(A, B, SC) do { wgmma6_ss_n256_t1(acc, A, B, SC); wgmma6_ss_n256_t1(acc, (A) + 2, (B) + 128, 1); } while (0)
#define GEMM_80(A, B, SC) do { wgmma6_ss_n80_t1(keep, A, B, SC); wgmma6_ss_n80_t1(keep, (A) + 256, (B) + 128, 1); wgmma6_ss_n80_t1(keep, (A) + 512, (B) + 256, 1); } while (0)
#define GEMM_144(A, B, SC) do { wgmma6_ss_n144_t1(ah, A, B, SC); wgmma6_ss_n144_t1(ah, (A) + 256, (B) + 128, 1); wgmma6_ss_n144_t1(ah, (A) + 512, (B) + 256, 1); } while (0)
#define NORM_ITEM(item) do {                                                                                       \
            if (norm_o(ow, at.o, lane, gaddr)) {                                                                   \
                attn_true_max(at.o, at.q, g_kv + (size_t)(j * 4 + (item)) * HEAD_BYTES + lane * 4);                \
                norm_o(ow, at.o, lane, gaddr);                                                                     \
            }                                                                                                      \
        } while (0)
#define STORE_ITEM(item) do { uint32_t ow[6]; NORM_ITEM(item); PUT_ITEM(item); } while (0)
#define PUT_ITEM(item) do {                                                                                        \
            uint8_t* op = a2w + (288 + ((item) * 4 + (j >> 1)) * 3) * 4096 + (j & 1) * 4224;                       \
            const int step = (j & 1) ? 3968 : 128;                                                                 \
            stg32(op, ow[0]);        stg32(op + 256, ow[1]);                                                       \
            stg32(op + step, ow[2]); stg32(op + step + 256, ow[3]);                                                \
            stg32(op + 4096, ow[4]); stg32(op + 4096 + 256, ow[5]);                                                \
        } while (0)
#define ITEM_STEP(DV, DK, NB, NPH, REL, GEMM_CODE) do {                                                            \
            uint32_t qo[8];                                                                                        \
            _Pragma("unroll") for (int i = 0; i < 6; i++) asm volatile("mov.b32 %0, %1;" : "=r"(qo[i]) : "r"(at.q[i])); \
            load_q(at.q, qa + (item + 1) * 4608, lane);                                                            \
            fence_regs(at.q);                                                                                      \
            wg_fence();                                                                                            \
            wgmma6_rs_n24_t1(at.o, at.p[0], at.p[1], at.p[2], at.p[3], (DV), 1);                                   \
            wgmma6_rs_n24_t1(at.o, at.p[4], at.p[5], at.p[6], at.p[7], (DV) + 80, 1);                              \
            wgmma6_rs_n24_t1(at.o, at.p[8], at.p[9], at.p[10], at.p[11], (DV) + 160, 1);                           \
            wgmma6_rs_n24_t1(at.o, at.p[12], at.p[13], at.p[14], at.p[15], (DV) + 240, 1);                         \
            wgmma6_rs_n64_t0(at.s, at.q[0], at.q[1], at.q[2], at.q[3], (DK) + dlo(0, 128), 0);                     \
            wgmma6_rs_n64_t0(at.s, at.q[4], at.q[5], at.q[6], at.q[7], (DK) + 32, 1);                              \
            wg_commit();                                                                                           \
            GEMM_CODE;                                                                                             \
            wg_commit();                                                                                           \
            wg_wait<1>();                                                                                          \
            fence_regs(at.o); fence_regs(at.p); fence_regs(at.s);                                                  \
            if (tid < 2) asm volatile("mbarrier.arrive.shared::cluster.b64 _, [%0];" ::"r"(REL) : "memory");       \
            uint32_t ow[6];                                                                                        \
            const bool bad = norm_o(ow, at.o, lane, gaddr);                                                        \
            EXPS();                                                                                                \
            if (bad) {                                                                                             \
                attn_true_max(at.o, qo, g_kv + (size_t)(j * 4 + (item)) * HEAD_BYTES + lane * 4);                  \
                norm_o(ow, at.o, lane, gaddr);                                                                     \
            }                                                                                                      \
            PUT_ITEM(item);                                                                                        \
            _Pragma("unroll") for (int i = 0; i < 12; i++) at.o[i] = 0.f;                                          \
            fence_regs(at.o);                                                                                      \
            mbar_wait(NB, NPH);                                                                                    \
        } while (0)
#define H2(i) pack(geglu2(acc[i], acc[64 + (i)]), geglu2(acc[(i) + 1], acc[65 + (i)]))
        float keep[40];
        float4 px[3];
        {
            float ah[72];
            int first = 1;
            {
#pragma unroll 1
                for (int t = 0; t < 5; t++) {
                    int n = 0x26988 >> (t * 4) & 15;
#pragma unroll 1
                    do { FUSED_PAIR(HI_X, wg * 256 + dlo(OFF_AX, 16), dlo(0, 4096), FUSED_STEP, GEMM_256); } while (--n);
                    if (t & 1) {
                        const int item = t >> 1;
                        mbar_wait(t == 1 ? bar_gate : bar_rdy + 2 * 8, 0);
                        FUSED_PAIR(HI_X, wg * 256 + dlo(OFF_AX, 16), dlo(0, 4096), ITEM_STEP, GEMM_256);
                    }
                    if (t < 3) {
                        mbar_wait(t > 0 ? bar_rdy + (t - 1) * 8 : bar_free + wg * 8, 0);
                        wg_wait<0>();
                        fence_regs(acc);
                        first = 0;
                        PROF(4 + 2 * t);
                        const uint32_t ha = sb + wg * 3 * SLOT + OFF_GAP + wq * 512 + lane * 16;
#pragma unroll
                        for (int k = 0; k < 8; k++) stsm4(ha + (k / 3) * SLOT + (k % 3) * 2048, H2(8 * k), H2(8 * k + 4), H2(8 * k + 2), H2(8 * k + 6));
                        fence_async_shared();
                        undef_regs(acc);
                        signal(t);
                        PROF(5 + 2 * t);
                    }
                }
                wg_wait<0>();
                fence_regs(acc);
                first = 0;
                PROF(10);
                uint8_t* hp = a2w + (j * 36 + 24) * 4096;
#pragma unroll
                for (int b = 0; b < 2; b++)
                    if (cta != 1000 + b) {
#pragma unroll
                        for (int k = b * 4; k < b * 4 + 4; k++) {
                            stg32(hp + k * 4096, H2(8 * k));           stg32(hp + k * 4096 + 256, H2(8 * k + 2));
                            stg32(hp + k * 4096 + 128, H2(8 * k + 4)); stg32(hp + k * 4096 + 384, H2(8 * k + 6));
                        }
                    }
                signal(3);
                PROF(11);
            }
#pragma unroll 1
            for (int seg = 0; seg < 3; seg++) {
                int n = 0x2AD >> (seg * 4) & 15;
#pragma unroll 1
                do { FUSED_PAIR(HI_A2, wg * 128 + dlo(OFF_A2, 128), dlo(0, 6144), FUSED_STEP, GEMM_144); } while (--n);
                if (seg == 0) {
                    constexpr int item = 2;
                    FUSED_PAIR(HI_A2, wg * 128 + dlo(OFF_A2, 128), dlo(0, 6144), ITEM_STEP, GEMM_144);
                    signal(5);
                } else if (seg == 1) {
                    wg_wait<0>();
                    fence_regs(ah);
                    PROF(12);
                    const float w0 = 0.5f - 0.5f * __uint_as_float(lds32(gaddr)), w1 = 0.5f - 0.5f * __uint_as_float(lds32(gaddr + 32));
#pragma unroll
                    for (int i = 0; i < 72; i++) ah[i] *= (i & 2) ? w1 : w0;
                    fence_regs(ah);
                }
            }
            wg_wait<0>();
            fence_regs(ah);
            PROF(17);
            mbar_wait(bar_px, 0);
#pragma unroll
            for (int i = 0; i < 3; i++) px[i] = __ldcg(g_px + (size_t)(cta * 2 + wg) * 3 * 128 + tid + i * 128);
            uint4* mine = g_part + (size_t)(cta * 2 + wg) * 5 * 128 + tid;
#pragma unroll
            for (int i = 0; i < 5; i++) {
                const float* v = &ah[32 + 8 * i];
                __stcg(mine + i * 128, make_uint4(pack(v[0], v[1]), pack(v[2], v[3]), pack(v[4], v[5]), pack(v[6], v[7])));
            }
#pragma unroll
            for (int i = 0; i < 40; i++) keep[i] = ah[i < 32 ? i : 32 + i] + __uint_as_float(at.q[6]);
            signal(6);
            fence_regs(keep);
        }
        {
            int first = 1;
            FUSED_PAIR(HI_A2, wg * 128 + dlo(OFF_A2, 128), dlo(0, 6144), FUSED_STEP, GEMM_80);
        }
        PROF(13);
        wg_fence();
        ISSUE_PV();
        wg_commit();
        wg_wait<0>();
        fence_regs(at.o); fence_regs(at.p); fence_regs(at.q);
#pragma unroll
        for (int i = 0; i < 3; i++) { at.o[4 * i] += px[i].x; at.o[4 * i + 1] += px[i].y; at.o[4 * i + 2] += px[i].z; at.o[4 * i + 3] += px[i].w; }
        STORE_ITEM(3);
        signal(7);
        fence_regs(keep);
        PROF(14);
#pragma unroll 1
        for (int kk = 0; kk < 2; kk++) {
            mbar_wait(fb, ph);
            const uint64_t da = mkdesc<HI_A2>(sd + wg * 128 + dlo(OFF_A2, 128)), db = mkdesc<HI_W>(sd + dlo(0, 6144));
            wg_fence();
            GEMM_80(da, db, 1);
            wg_commit();
            wg_wait<1>();
            if (kk < 1) release();
            STAGE_NEXT;
        }
        {
            mbar_wait(bar_rdy + 6 * 8, 0);
            const uint4* theirs = g_part + (size_t)((cta ^ 8) * 2 + wg) * 5 * 128 + tid;
            uint4 pv[5];
#pragma unroll
            for (int i = 0; i < 5; i++) pv[i] = __ldcg(theirs + i * 128);
            wg_wait<0>();
            fence_regs(keep);
#pragma unroll
            for (int i = 0; i < 5; i++) {
                const uint32_t u[4] = {pv[i].x, pv[i].y, pv[i].z, pv[i].w};
#pragma unroll
                for (int e = 0; e < 4; e++) { keep[8 * i + 2 * e] += __uint_as_float(u[e] << 16); keep[8 * i + 2 * e + 1] += __uint_as_float(u[e] & 0xffff0000u); }
            }
            fence_regs(keep);
        }
        mbar_wait(bar_late, 0);
#pragma unroll 1
        for (int k = 2; k < 6; k++) {
            mbar_wait(bar_full + k * 8, 0);
            if (k == 2) PROF(15);
            const uint32_t bo = __shfl_sync(0xffffffffu, lds32(s_order + k * 4), 0);
            const uint64_t da = mkdesc<HI_A2>(sbd + k * (SLOT >> 4) + wg * 128 + dlo(OFF_A2, 128)), db = mkdesc<HI_W>(sbd + bo + dlo(0, 6144));
            wg_fence();
            GEMM_80(da, db, 1);
            wg_commit();
        }
        asm volatile("barrier.cluster.arrive.relaxed.aligned;" ::: "memory");
        const uint32_t tb = sb + (warp >> 1) * SLOT + OFF_KV + (warp & 1) * 2560;
        const uint32_t trow = ((lane >> 3) & 1) * 8 + (lane & 7);
        uint8_t* op = (uint8_t*)(out + (size_t)(m * 128 + grp * 8) * DM);
        wg_wait<0>();
        fence_regs(keep);
        PROF(16);
#pragma unroll
        for (int i = 0; i < 5; i++) {
            const uint32_t a = i < 4 ? tb + trow * 128 + (((2 * i + (lane >> 4)) ^ (lane & 7)) << 4) : tb + 2048 + trow * 32 + (lane >> 4) * 16;
            stsm4(a, pack(keep[8 * i], keep[8 * i + 1]), pack(keep[8 * i + 2], keep[8 * i + 3]), pack(keep[8 * i + 4], keep[8 * i + 5]), pack(keep[8 * i + 6], keep[8 * i + 7]));
        }
        __syncwarp();
        uint4 v[5];
#pragma unroll
        for (int i = 0; i < 5; i++) {
            const uint32_t r = 4 * i + (lane >> 3);
            const uint32_t a = i < 4 ? tb + r * 128 + (((lane & 7) ^ (r & 7)) << 4) : tb + 2048 + lane * 16;
            asm volatile("ld.shared.v4.u32 {%0, %1, %2, %3}, [%4];" : "=r"(v[i].x), "=r"(v[i].y), "=r"(v[i].z), "=r"(v[i].w) : "r"(a) : "memory");
        }
#pragma unroll
        for (int i = 0; i < 4; i++) *(uint4*)(op + (4 * i + (lane >> 3)) * (DM * 2) + nt * 256 + hf * 128 + (lane & 7) * 16) = v[i];
        if (wg == hf) *(uint4*)(op + (lane >> 1) * (DM * 2) + 1024 + nt * 32 + (lane & 1) * 16) = v[4];
        PROF(20);
        asm volatile("barrier.cluster.wait.aligned;" ::: "memory");
    }
}

typedef CUresult (*EncodeFn)(CUtensorMap*, CUtensorMapDataType, cuuint32_t, void*, const cuuint64_t*, const cuuint64_t*,
                             const cuuint32_t*, const cuuint32_t*, CUtensorMapInterleave, CUtensorMapSwizzle,
                             CUtensorMapL2promotion, CUtensorMapFloatOOBfill);

CUtensorMap make_map(EncodeFn enc, const void* ptr, uint64_t inner, uint64_t outer, uint32_t box_inner, uint32_t box_outer, CUtensorMapSwizzle swz) {
    CUtensorMap t;
    cuuint64_t dims[2] = {inner, outer};
    cuuint64_t strides[1] = {inner * 2};
    cuuint32_t box[2] = {box_inner, box_outer};
    cuuint32_t es[2] = {1, 1};
    enc(&t, CU_TENSOR_MAP_DATA_TYPE_BFLOAT16, 2, const_cast<void*>(ptr), dims, strides, box, es, CU_TENSOR_MAP_INTERLEAVE_NONE, swz,
        CU_TENSOR_MAP_L2_PROMOTION_L2_128B, CU_TENSOR_MAP_FLOAT_OOB_FILL_NONE);
    return t;
}

CUtensorMap make_qkv_map(EncodeFn enc, const void* ptr, uint32_t width, CUtensorMapSwizzle swz) {
    CUtensorMap t;
    cuuint64_t dims[3] = {DM, DM, 3};
    cuuint64_t strides[2] = {3 * DM * 2, DM * 2};
    cuuint32_t box[3] = {width, 16, 3};
    cuuint32_t es[3] = {1, 1, 1};
    enc(&t, CU_TENSOR_MAP_DATA_TYPE_BFLOAT16, 3, const_cast<void*>(ptr), dims, strides, box, es, CU_TENSOR_MAP_INTERLEAVE_NONE, swz,
        CU_TENSOR_MAP_L2_PROMOTION_L2_128B, CU_TENSOR_MAP_FLOAT_OOB_FILL_NONE);
    return t;
}

}

extern "C" void kernel_launch(void* const* d_in, const int* in_sizes, int n_in, void* d_out, int out_size) {
    (void)in_sizes; (void)n_in; (void)out_size;
    void* fn = nullptr;
    cudaDriverEntryPointQueryResult qr;
    cudaGetDriverEntryPoint("cuTensorMapEncodeTiled", &fn, cudaEnableDefault, &qr);
    EncodeFn enc = (EncodeFn)fn;
    const CUtensorMap tm_x = make_map(enc, d_in[0], DM, SEQ, 32, 128, CU_TENSOR_MAP_SWIZZLE_64B);
    const CUtensorMap tm_qkv = make_qkv_map(enc, d_in[1], 64, CU_TENSOR_MAP_SWIZZLE_128B);
    const CUtensorMap tm_qkv8 = make_qkv_map(enc, d_in[1], 8, CU_TENSOR_MAP_SWIZZLE_NONE);
    const CUtensorMap tm_wo = make_map(enc, d_in[2], DM, DM, 64, 24, CU_TENSOR_MAP_SWIZZLE_128B);
    const CUtensorMap tm_wg = make_map(enc, d_in[4], FF, DM, 64, 32, CU_TENSOR_MAP_SWIZZLE_128B);
    const CUtensorMap tm_wu = make_map(enc, d_in[5], FF, DM, 64, 32, CU_TENSOR_MAP_SWIZZLE_128B);
    const CUtensorMap tm_wd = make_map(enc, d_in[6], DM, FF, 64, 24, CU_TENSOR_MAP_SWIZZLE_128B);
    const CUtensorMap tm_wd16 = make_map(enc, d_in[6], DM, FF, 16, 24, CU_TENSOR_MAP_SWIZZLE_128B);
    const CUtensorMap tm_wo16 = make_map(enc, d_in[2], DM, DM, 16, 24, CU_TENSOR_MAP_SWIZZLE_128B);
    cudaFuncSetAttribute(fused_kernel, cudaFuncAttributeMaxDynamicSharedMemorySize, SMEM_BYTES);
    fused_kernel<<<NCTA + 4, 384, SMEM_BYTES>>>((__nv_bfloat16*)d_out, (const __nv_bfloat16*)d_in[0], (const __nv_bfloat16*)d_in[7],
                                               (const uint8_t*)d_in[1], (const uint8_t*)d_in[4], (const uint8_t*)d_in[5],
                                               tm_x, tm_qkv, tm_qkv8, tm_wg, tm_wu, tm_wd, tm_wo, tm_wd16, tm_wo16);
}
```

```cpp
#include <cuda_runtime.h>
#include <cuda.h>
#include <cuda_bf16.h>
#include <stdint.h>


namespace {

constexpr int SEQ = 2048, DM = 576, FF = 4608;
constexpr int NCTA = 128;
constexpr int NSTAGE = 6;
constexpr int E0 = 2;
constexpr int DEFER = 2;
constexpr int SLOT = 35 * 1024;
constexpr int OFF_AX = 22528;
constexpr int OFF_A2 = 18432;
constexpr int OFF_TL = 20480;
constexpr int OFF_GAP = 16384;
constexpr int OFF_KV = 30720;
constexpr int OFF_Q = NSTAGE * SLOT - 4608;
constexpr int OFF_BAR = NSTAGE * SLOT + 3 * 4608;
constexpr int SMEM_BYTES = OFF_BAR + 1024 + 1024;

constexpr int STRIPB = 48 * 32;
constexpr int HEAD_BYTES = 256 * 640;
constexpr int A2_TILE = 336 * 4096;

constexpr int FL_KV = 0;
constexpr int FL_M = FL_KV + 8 * 32;
constexpr int FM_H = 0;
constexpr int FM_LATE = 7;
constexpr int FM_R = 16;
constexpr int FL_G = FL_M + 16 * 64;
constexpr int FL_E = FL_G + 4 * 32;
constexpr int FL_N = FL_E + (NCTA + 4) * 32;

__device__ __align__(1024) uint8_t g_kv[32 * HEAD_BYTES];
__device__ __align__(1024) uint8_t g_a2[16 * A2_TILE];
__device__ __align__(1024) uint4 g_part[NCTA * 2 * 5 * 128];
__device__ __align__(1024) uint8_t g_q3[NCTA * 4608];
__device__ __align__(1024) float4 g_px[NCTA * 2 * 3 * 128];
__device__ float g_gate[SEQ];
__device__ __align__(256) uint32_t g_flags[FL_N];

template <uint32_t BHI>
__device__ __forceinline__ void wgmma_rs_n24_t1(float (&d)[12], uint32_t a0, uint32_t a1, uint32_t a2, uint32_t a3, uint32_t db, int scale_d) {
  asm volatile("{\n.reg .pred p;\n.reg .b64 da, db;\n"
    "mov.b64 db, {%16, %18};\n"
    "setp.ne.b32 p, %17, 0;\n"
    "wgmma.mma_async.sync.aligned.m64n24k16.f32.bf16.bf16 "
    "{%0, %1, %2, %3, %4, %5, %6, %7, %8, %9, %10, %11}, "
    "{%12, %13, %14, %15}, db, p, 1, 1, 1;\n}\n"
    : "+f"(d[0]), "+f"(d[1]), "+f"(d[2]), "+f"(d[3]), "+f"(d[4]), "+f"(d[5]), "+f"(d[6]), "+f"(d[7]),
      "+f"(d[8]), "+f"(d[9]), "+f"(d[10]), "+f"(d[11])
    : "r"(a0), "r"(a1), "r"(a2), "r"(a3), "r"(db), "r"(scale_d), "n"(BHI));
}
template <uint32_t BHI>
__device__ __forceinline__ void wgmma_rs_n128_t0(float (&d)[64], uint32_t a0, uint32_t a1, uint32_t a2, uint32_t a3, uint32_t db, int scale_d) {
  asm volatile("{\n.reg .pred p;\n.reg .b64 da, db;\n"
    "mov.b64 db, {%68, %70};\n"
    "setp.ne.b32 p, %69, 0;\n"
    "wgmma.mma_async.sync.aligned.m64n128k16.f32.bf16.bf16 "
    "{%0, %1, %2, %3, %4, %5, %6, %7, %8, %9, %10, %11, %12, %13, %14, %15, "
    "%16, %17, %18, %19, %20, %21, %22, %23, %24, %25, %26, %27, %28, %29, %30, %31, "
    "%32, %33, %34, %35, %36, %37, %38, %39, %40, %41, %42, %43, %44, %45, %46, %47, "
    "%48, %49, %50, %51, %52, %53, %54, %55, %56, %57, %58, %59, %60, %61, %62, %63}, "
    "{%64, %65, %66, %67}, db, p, 1, 1, 0;\n}\n"
    : "+f"(d[0]), "+f"(d[1]), "+f"(d[2]), "+f"(d[3]), "+f"(d[4]), "+f"(d[5]), "+f"(d[6]), "+f"(d[7]),
      "+f"(d[8]), "+f"(d[9]), "+f"(d[10]), "+f"(d[11]), "+f"(d[12]), "+f"(d[13]), "+f"(d[14]), "+f"(d[15]),
      "+f"(d[16]), "+f"(d[17]), "+f"(d[18]), "+f"(d[19]), "+f"(d[20]), "+f"(d[21]), "+f"(d[22]), "+f"(d[23]),
      "+f"(d[24]), "+f"(d[25]), "+f"(d[26]), "+f"(d[27]), "+f"(d[28]), "+f"(d[29]), "+f"(d[30]), "+f"(d[31]),
      "+f"(d[32]), "+f"(d[33]), "+f"(d[34]), "+f"(d[35]), "+f"(d[36]), "+f"(d[37]), "+f"(d[38]), "+f"(d[39]),
      "+f"(d[40]), "+f"(d[41]), "+f"(d[42]), "+f"(d[43]), "+f"(d[44]), "+f"(d[45]), "+f"(d[46]), "+f"(d[47]),
      "+f"(d[48]), "+f"(d[49]), "+f"(d[50]), "+f"(d[51]), "+f"(d[52]), "+f"(d[53]), "+f"(d[54]), "+f"(d[55]),
      "+f"(d[56]), "+f"(d[57]), "+f"(d[58]), "+f"(d[59]), "+f"(d[60]), "+f"(d[61]), "+f"(d[62]), "+f"(d[63])
    : "r"(a0), "r"(a1), "r"(a2), "r"(a3), "r"(db), "r"(scale_d), "n"(BHI));
}
template <uint32_t BHI>
__device__ __forceinline__ void wgmma_rs_n128_t1(float (&d)[64], uint32_t a0, uint32_t a1, uint32_t a2, uint32_t a3, uint32_t db, int scale_d) {
  asm volatile("{\n.reg .pred p;\n.reg .b64 da, db;\n"
    "mov.b64 db, {%68, %70};\n"
    "setp.ne.b32 p, %69, 0;\n"
    "wgmma.mma_async.sync.aligned.m64n128k16.f32.bf16.bf16 "
    "{%0, %1, %2, %3, %4, %5, %6, %7, %8, %9, %10, %11, %12, %13, %14, %15, "
    "%16, %17, %18, %19, %20, %21, %22, %23, %24, %25, %26, %27, %28, %29, %30, %31, "
    "%32, %33, %34, %35, %36, %37, %38, %39, %40, %41, %42, %43, %44, %45, %46, %47, "
    "%48, %49, %50, %51, %52, %53, %54, %55, %56, %57, %58, %59, %60, %61, %62, %63}, "
    "{%64, %65, %66, %67}, db, p, 1, 1, 1;\n}\n"
    : "+f"(d[0]), "+f"(d[1]), "+f"(d[2]), "+f"(d[3]), "+f"(d[4]), "+f"(d[5]), "+f"(d[6]), "+f"(d[7]),
      "+f"(d[8]), "+f"(d[9]), "+f"(d[10]), "+f"(d[11]), "+f"(d[12]), "+f"(d[13]), "+f"(d[14]), "+f"(d[15]),
      "+f"(d[16]), "+f"(d[17]), "+f"(d[18]), "+f"(d[19]), "+f"(d[20]), "+f"(d[21]), "+f"(d[22]), "+f"(d[23]),
      "+f"(d[24]), "+f"(d[25]), "+f"(d[26]), "+f"(d[27]), "+f"(d[28]), "+f"(d[29]), "+f"(d[30]), "+f"(d[31]),
      "+f"(d[32]), "+f"(d[33]), "+f"(d[34]), "+f"(d[35]), "+f"(d[36]), "+f"(d[37]), "+f"(d[38]), "+f"(d[39]),
      "+f"(d[40]), "+f"(d[41]), "+f"(d[42]), "+f"(d[43]), "+f"(d[44]), "+f"(d[45]), "+f"(d[46]), "+f"(d[47]),
      "+f"(d[48]), "+f"(d[49]), "+f"(d[50]), "+f"(d[51]), "+f"(d[52]), "+f"(d[53]), "+f"(d[54]), "+f"(d[55]),
      "+f"(d[56]), "+f"(d[57]), "+f"(d[58]), "+f"(d[59]), "+f"(d[60]), "+f"(d[61]), "+f"(d[62]), "+f"(d[63])
    : "r"(a0), "r"(a1), "r"(a2), "r"(a3), "r"(db), "r"(scale_d), "n"(BHI));
}
template <uint32_t BHI>
__device__ __forceinline__ void wgmma_rs_n192_t1(float (&d)[96], uint32_t a0, uint32_t a1, uint32_t a2, uint32_t a3, uint32_t db, int scale_d) {
  asm volatile("{\n.reg .pred p;\n.reg .b64 da, db;\n"
    "mov.b64 db, {%100, %102};\n"
    "setp.ne.b32 p, %101, 0;\n"
    "wgmma.mma_async.sync.aligned.m64n192k16.f32.bf16.bf16 "
    "{%0, %1, %2, %3, %4, %5, %6, %7, %8, %9, %10, %11, %12, %13, %14, %15, "
    "%16, %17, %18, %19, %20, %21, %22, %23, %24, %25, %26, %27, %28, %29, %30, %31, "
    "%32, %33, %34, %35, %36, %37, %38, %39, %40, %41, %42, %43, %44, %45, %46, %47, "
    "%48, %49, %50, %51, %52, %53, %54, %55, %56, %57, %58, %59, %60, %61, %62, %63, "
    "%64, %65, %66, %67, %68, %69, %70, %71, %72, %73, %74, %75, %76, %77, %78, %79, "
    "%80, %81, %82, %83, %84, %85, %86, %87, %88, %89, %90, %91, %92, %93, %94, %95}, "
    "{%96, %97, %98, %99}, db, p, 1, 1, 1;\n}\n"
    : "+f"(d[0]), "+f"(d[1]), "+f"(d[2]), "+f"(d[3]), "+f"(d[4]), "+f"(d[5]), "+f"(d[6]), "+f"(d[7]),
      "+f"(d[8]), "+f"(d[9]), "+f"(d[10]), "+f"(d[11]), "+f"(d[12]), "+f"(d[13]), "+f"(d[14]), "+f"(d[15]),
      "+f"(d[16]), "+f"(d[17]), "+f"(d[18]), "+f"(d[19]), "+f"(d[20]), "+f"(d[21]), "+f"(d[22]), "+f"(d[23]),
      "+f"(d[24]), "+f"(d[25]), "+f"(d[26]), "+f"(d[27]), "+f"(d[28]), "+f"(d[29]), "+f"(d[30]), "+f"(d[31]),
      "+f"(d[32]), "+f"(d[33]), "+f"(d[34]), "+f"(d[35]), "+f"(d[36]), "+f"(d[37]), "+f"(d[38]), "+f"(d[39]),
      "+f"(d[40]), "+f"(d[41]), "+f"(d[42]), "+f"(d[43]), "+f"(d[44]), "+f"(d[45]), "+f"(d[46]), "+f"(d[47]),
      "+f"(d[48]), "+f"(d[49]), "+f"(d[50]), "+f"(d[51]), "+f"(d[52]), "+f"(d[53]), "+f"(d[54]), "+f"(d[55]),
      "+f"(d[56]), "+f"(d[57]), "+f"(d[58]), "+f"(d[59]), "+f"(d[60]), "+f"(d[61]), "+f"(d[62]), "+f"(d[63]),
      "+f"(d[64]), "+f"(d[65]), "+f"(d[66]), "+f"(d[67]), "+f"(d[68]), "+f"(d[69]), "+f"(d[70]), "+f"(d[71]),
      "+f"(d[72]), "+f"(d[73]), "+f"(d[74]), "+f"(d[75]), "+f"(d[76]), "+f"(d[77]), "+f"(d[78]), "+f"(d[79]),
      "+f"(d[80]), "+f"(d[81]), "+f"(d[82]), "+f"(d[83]), "+f"(d[84]), "+f"(d[85]), "+f"(d[86]), "+f"(d[87]),
      "+f"(d[88]), "+f"(d[89]), "+f"(d[90]), "+f"(d[91]), "+f"(d[92]), "+f"(d[93]), "+f"(d[94]), "+f"(d[95])
    : "r"(a0), "r"(a1), "r"(a2), "r"(a3), "r"(db), "r"(scale_d), "n"(BHI));
}
template <uint32_t AHI, uint32_t BHI>
__device__ __forceinline__ void wgmma_ss_n24_t1(float (&d)[12], uint32_t da, uint32_t db, int scale_d) {
  asm volatile("{\n.reg .pred p;\n.reg .b64 da, db;\n"
    "mov.b64 da, {%12, %15};\nmov.b64 db, {%13, %16};\n"
    "setp.ne.b32 p, %14, 0;\n"
    "wgmma.mma_async.sync.aligned.m64n24k16.f32.bf16.bf16 "
    "{%0, %1, %2, %3, %4, %5, %6, %7, %8, %9, %10, %11}, "
    "da, db, p, 1, 1, 0, 1;\n}\n"
    : "+f"(d[0]), "+f"(d[1]), "+f"(d[2]), "+f"(d[3]), "+f"(d[4]), "+f"(d[5]), "+f"(d[6]), "+f"(d[7]),
      "+f"(d[8]), "+f"(d[9]), "+f"(d[10]), "+f"(d[11])
    : "r"(da), "r"(db), "r"(scale_d), "n"(AHI), "n"(BHI));
}
template <uint32_t AHI, uint32_t BHI>
__device__ __forceinline__ void wgmma_ss_n128_t1(float (&d)[64], uint32_t da, uint32_t db, int scale_d) {
  asm volatile("{\n.reg .pred p;\n.reg .b64 da, db;\n"
    "mov.b64 da, {%64, %67};\nmov.b64 db, {%65, %68};\n"
    "setp.ne.b32 p, %66, 0;\n"
    "wgmma.mma_async.sync.aligned.m64n128k16.f32.bf16.bf16 "
    "{%0, %1, %2, %3, %4, %5, %6, %7, %8, %9, %10, %11, %12, %13, %14, %15, "
    "%16, %17, %18, %19, %20, %21, %22, %23, %24, %25, %26, %27, %28, %29, %30, %31, "
    "%32, %33, %34, %35, %36, %37, %38, %39, %40, %41, %42, %43, %44, %45, %46, %47, "
    "%48, %49, %50, %51, %52, %53, %54, %55, %56, %57, %58, %59, %60, %61, %62, %63}, "
    "da, db, p, 1, 1, 0, 1;\n}\n"
    : "+f"(d[0]), "+f"(d[1]), "+f"(d[2]), "+f"(d[3]), "+f"(d[4]), "+f"(d[5]), "+f"(d[6]), "+f"(d[7]),
      "+f"(d[8]), "+f"(d[9]), "+f"(d[10]), "+f"(d[11]), "+f"(d[12]), "+f"(d[13]), "+f"(d[14]), "+f"(d[15]),
      "+f"(d[16]), "+f"(d[17]), "+f"(d[18]), "+f"(d[19]), "+f"(d[20]), "+f"(d[21]), "+f"(d[22]), "+f"(d[23]),
      "+f"(d[24]), "+f"(d[25]), "+f"(d[26]), "+f"(d[27]), "+f"(d[28]), "+f"(d[29]), "+f"(d[30]), "+f"(d[31]),
      "+f"(d[32]), "+f"(d[33]), "+f"(d[34]), "+f"(d[35]), "+f"(d[36]), "+f"(d[37]), "+f"(d[38]), "+f"(d[39]),
      "+f"(d[40]), "+f"(d[41]), "+f"(d[42]), "+f"(d[43]), "+f"(d[44]), "+f"(d[45]), "+f"(d[46]), "+f"(d[47]),
      "+f"(d[48]), "+f"(d[49]), "+f"(d[50]), "+f"(d[51]), "+f"(d[52]), "+f"(d[53]), "+f"(d[54]), "+f"(d[55]),
      "+f"(d[56]), "+f"(d[57]), "+f"(d[58]), "+f"(d[59]), "+f"(d[60]), "+f"(d[61]), "+f"(d[62]), "+f"(d[63])
    : "r"(da), "r"(db), "r"(scale_d), "n"(AHI), "n"(BHI));
}
template <uint32_t AHI, uint32_t BHI>
__device__ __forceinline__ void wgmma_ss_n192_t1(float (&d)[96], uint32_t da, uint32_t db, int scale_d) {
  asm volatile("{\n.reg .pred p;\n.reg .b64 da, db;\n"
    "mov.b64 da, {%96, %99};\nmov.b64 db, {%97, %100};\n"
    "setp.ne.b32 p, %98, 0;\n"
    "wgmma.mma_async.sync.aligned.m64n192k16.f32.bf16.bf16 "
    "{%0, %1, %2, %3, %4, %5, %6, %7, %8, %9, %10, %11, %12, %13, %14, %15, "
    "%16, %17, %18, %19, %20, %21, %22, %23, %24, %25, %26, %27, %28, %29, %30, %31, "
    "%32, %33, %34, %35, %36, %37, %38, %39, %40, %41, %42, %43, %44, %45, %46, %47, "
    "%48, %49, %50, %51, %52, %53, %54, %55, %56, %57, %58, %59, %60, %61, %62, %63, "
    "%64, %65, %66, %67, %68, %69, %70, %71, %72, %73, %74, %75, %76, %77, %78, %79, "
    "%80, %81, %82, %83, %84, %85, %86, %87, %88, %89, %90, %91, %92, %93, %94, %95}, "
    "da, db, p, 1, 1, 0, 1;\n}\n"
    : "+f"(d[0]), "+f"(d[1]), "+f"(d[2]), "+f"(d[3]), "+f"(d[4]), "+f"(d[5]), "+f"(d[6]), "+f"(d[7]),
      "+f"(d[8]), "+f"(d[9]), "+f"(d[10]), "+f"(d[11]), "+f"(d[12]), "+f"(d[13]), "+f"(d[14]), "+f"(d[15]),
      "+f"(d[16]), "+f"(d[17]), "+f"(d[18]), "+f"(d[19]), "+f"(d[20]), "+f"(d[21]), "+f"(d[22]), "+f"(d[23]),
      "+f"(d[24]), "+f"(d[25]), "+f"(d[26]), "+f"(d[27]), "+f"(d[28]), "+f"(d[29]), "+f"(d[30]), "+f"(d[31]),
      "+f"(d[32]), "+f"(d[33]), "+f"(d[34]), "+f"(d[35]), "+f"(d[36]), "+f"(d[37]), "+f"(d[38]), "+f"(d[39]),
      "+f"(d[40]), "+f"(d[41]), "+f"(d[42]), "+f"(d[43]), "+f"(d[44]), "+f"(d[45]), "+f"(d[46]), "+f"(d[47]),
      "+f"(d[48]), "+f"(d[49]), "+f"(d[50]), "+f"(d[51]), "+f"(d[52]), "+f"(d[53]), "+f"(d[54]), "+f"(d[55]),
      "+f"(d[56]), "+f"(d[57]), "+f"(d[58]), "+f"(d[59]), "+f"(d[60]), "+f"(d[61]), "+f"(d[62]), "+f"(d[63]),
      "+f"(d[64]), "+f"(d[65]), "+f"(d[66]), "+f"(d[67]), "+f"(d[68]), "+f"(d[69]), "+f"(d[70]), "+f"(d[71]),
      "+f"(d[72]), "+f"(d[73]), "+f"(d[74]), "+f"(d[75]), "+f"(d[76]), "+f"(d[77]), "+f"(d[78]), "+f"(d[79]),
      "+f"(d[80]), "+f"(d[81]), "+f"(d[82]), "+f"(d[83]), "+f"(d[84]), "+f"(d[85]), "+f"(d[86]), "+f"(d[87]),
      "+f"(d[88]), "+f"(d[89]), "+f"(d[90]), "+f"(d[91]), "+f"(d[92]), "+f"(d[93]), "+f"(d[94]), "+f"(d[95])
    : "r"(da), "r"(db), "r"(scale_d), "n"(AHI), "n"(BHI));
}
template <uint32_t AHI, uint32_t BHI>
__device__ __forceinline__ void wgmma_ss_n256_t1(float (&d)[128], uint32_t da, uint32_t db, int scale_d) {
  asm volatile("{\n.reg .pred p;\n.reg .b64 da, db;\n"
    "mov.b64 da, {%128, %131};\nmov.b64 db, {%129, %132};\n"
    "setp.ne.b32 p, %130, 0;\n"
    "wgmma.mma_async.sync.aligned.m64n256k16.f32.bf16.bf16 "
    "{%0, %1, %2, %3, %4, %5, %6, %7, %8, %9, %10, %11, %12, %13, %14, %15, "
    "%16, %17, %18, %19, %20, %21, %22, %23, %24, %25, %26, %27, %28, %29, %30, %31, "
    "%32, %33, %34, %35, %36, %37, %38, %39, %40, %41, %42, %43, %44, %45, %46, %47, "
    "%48, %49, %50, %51, %52, %53, %54, %55, %56, %57, %58, %59, %60, %61, %62, %63, "
    "%64, %65, %66, %67, %68, %69, %70, %71, %72, %73, %74, %75, %76, %77, %78, %79, "
    "%80, %81, %82, %83, %84, %85, %86, %87, %88, %89, %90, %91, %92, %93, %94, %95, "
    "%96, %97, %98, %99, %100, %101, %102, %103, %104, %105, %106, %107, %108, %109, %110, %111, "
    "%112, %113, %114, %115, %116, %117, %118, %119, %120, %121, %122, %123, %124, %125, %126, %127}, "
    "da, db, p, 1, 1, 0, 1;\n}\n"
    : "+f"(d[0]), "+f"(d[1]), "+f"(d[2]), "+f"(d[3]), "+f"(d[4]), "+f"(d[5]), "+f"(d[6]), "+f"(d[7]),
      "+f"(d[8]), "+f"(d[9]), "+f"(d[10]), "+f"(d[11]), "+f"(d[12]), "+f"(d[13]), "+f"(d[14]), "+f"(d[15]),
      "+f"(d[16]), "+f"(d[17]), "+f"(d[18]), "+f"(d[19]), "+f"(d[20]), "+f"(d[21]), "+f"(d[22]), "+f"(d[23]),
      "+f"(d[24]), "+f"(d[25]), "+f"(d[26]), "+f"(d[27]), "+f"(d[28]), "+f"(d[29]), "+f"(d[30]), "+f"(d[31]),
      "+f"(d[32]), "+f"(d[33]), "+f"(d[34]), "+f"(d[35]), "+f"(d[36]), "+f"(d[37]), "+f"(d[38]), "+f"(d[39]),
      "+f"(d[40]), "+f"(d[41]), "+f"(d[42]), "+f"(d[43]), "+f"(d[44]), "+f"(d[45]), "+f"(d[46]), "+f"(d[47]),
      "+f"(d[48]), "+f"(d[49]), "+f"(d[50]), "+f"(d[51]), "+f"(d[52]), "+f"(d[53]), "+f"(d[54]), "+f"(d[55]),
      "+f"(d[56]), "+f"(d[57]), "+f"(d[58]), "+f"(d[59]), "+f"(d[60]), "+f"(d[61]), "+f"(d[62]), "+f"(d[63]),
      "+f"(d[64]), "+f"(d[65]), "+f"(d[66]), "+f"(d[67]), "+f"(d[68]), "+f"(d[69]), "+f"(d[70]), "+f"(d[71]),
      "+f"(d[72]), "+f"(d[73]), "+f"(d[74]), "+f"(d[75]), "+f"(d[76]), "+f"(d[77]), "+f"(d[78]), "+f"(d[79]),
      "+f"(d[80]), "+f"(d[81]), "+f"(d[82]), "+f"(d[83]), "+f"(d[84]), "+f"(d[85]), "+f"(d[86]), "+f"(d[87]),
      "+f"(d[88]), "+f"(d[89]), "+f"(d[90]), "+f"(d[91]), "+f"(d[92]), "+f"(d[93]), "+f"(d[94]), "+f"(d[95]),
      "+f"(d[96]), "+f"(d[97]), "+f"(d[98]), "+f"(d[99]), "+f"(d[100]), "+f"(d[101]), "+f"(d[102]), "+f"(d[103]),
      "+f"(d[104]), "+f"(d[105]), "+f"(d[106]), "+f"(d[107]), "+f"(d[108]), "+f"(d[109]), "+f"(d[110]), "+f"(d[111]),
      "+f"(d[112]), "+f"(d[113]), "+f"(d[114]), "+f"(d[115]), "+f"(d[116]), "+f"(d[117]), "+f"(d[118]), "+f"(d[119]),
      "+f"(d[120]), "+f"(d[121]), "+f"(d[122]), "+f"(d[123]), "+f"(d[124]), "+f"(d[125]), "+f"(d[126]), "+f"(d[127])
    : "r"(da), "r"(db), "r"(scale_d), "n"(AHI), "n"(BHI));
}
__device__ __forceinline__ void wgmma6_rs_n24_t1(float (&d)[12], uint32_t a0, uint32_t a1, uint32_t a2, uint32_t a3, uint64_t db, int scale_d) {
  asm volatile("{\n.reg .pred p;\n"
    "setp.ne.b32 p, %17, 0;\n"
    "wgmma.mma_async.sync.aligned.m64n24k16.f32.bf16.bf16 "
    "{%0, %1, %2, %3, %4, %5, %6, %7, %8, %9, %10, %11}, "
    "{%12, %13, %14, %15}, %16, p, 1, 1, 1;\n}\n"
    : "+f"(d[0]), "+f"(d[1]), "+f"(d[2]), "+f"(d[3]), "+f"(d[4]), "+f"(d[5]), "+f"(d[6]), "+f"(d[7]),
      "+f"(d[8]), "+f"(d[9]), "+f"(d[10]), "+f"(d[11])
    : "r"(a0), "r"(a1), "r"(a2), "r"(a3), "l"(db), "r"(scale_d));
}
__device__ __forceinline__ void wgmma6_rs_n64_t0(float (&d)[32], uint32_t a0, uint32_t a1, uint32_t a2, uint32_t a3, uint64_t db, int scale_d) {
  asm volatile("{\n.reg .pred p;\n"
    "setp.ne.b32 p, %37, 0;\n"
    "wgmma.mma_async.sync.aligned.m64n64k16.f32.bf16.bf16 "
    "{%0, %1, %2, %3, %4, %5, %6, %7, %8, %9, %10, %11, %12, %13, %14, %15, "
    "%16, %17, %18, %19, %20, %21, %22, %23, %24, %25, %26, %27, %28, %29, %30, %31}, "
    "{%32, %33, %34, %35}, %36, p, 1, 1, 0;\n}\n"
    : "+f"(d[0]), "+f"(d[1]), "+f"(d[2]), "+f"(d[3]), "+f"(d[4]), "+f"(d[5]), "+f"(d[6]), "+f"(d[7]),
      "+f"(d[8]), "+f"(d[9]), "+f"(d[10]), "+f"(d[11]), "+f"(d[12]), "+f"(d[13]), "+f"(d[14]), "+f"(d[15]),
      "+f"(d[16]), "+f"(d[17]), "+f"(d[18]), "+f"(d[19]), "+f"(d[20]), "+f"(d[21]), "+f"(d[22]), "+f"(d[23]),
      "+f"(d[24]), "+f"(d[25]), "+f"(d[26]), "+f"(d[27]), "+f"(d[28]), "+f"(d[29]), "+f"(d[30]), "+f"(d[31])
    : "r"(a0), "r"(a1), "r"(a2), "r"(a3), "l"(db), "r"(scale_d));
}
__device__ __forceinline__ void wgmma6_ss_n80_t1(float (&d)[40], uint64_t da, uint64_t db, int scale_d) {
  asm volatile("{\n.reg .pred p;\n"
    "setp.ne.b32 p, %42, 0;\n"
    "wgmma.mma_async.sync.aligned.m64n80k16.f32.bf16.bf16 "
    "{%0, %1, %2, %3, %4, %5, %6, %7, %8, %9, %10, %11, %12, %13, %14, %15, "
    "%16, %17, %18, %19, %20, %21, %22, %23, %24, %25, %26, %27, %28, %29, %30, %31, "
    "%32, %33, %34, %35, %36, %37, %38, %39}, "
    "%40, %41, p, 1, 1, 0, 1;\n}\n"
    : "+f"(d[0]), "+f"(d[1]), "+f"(d[2]), "+f"(d[3]), "+f"(d[4]), "+f"(d[5]), "+f"(d[6]), "+f"(d[7]),
      "+f"(d[8]), "+f"(d[9]), "+f"(d[10]), "+f"(d[11]), "+f"(d[12]), "+f"(d[13]), "+f"(d[14]), "+f"(d[15]),
      "+f"(d[16]), "+f"(d[17]), "+f"(d[18]), "+f"(d[19]), "+f"(d[20]), "+f"(d[21]), "+f"(d[22]), "+f"(d[23]),
      "+f"(d[24]), "+f"(d[25]), "+f"(d[26]), "+f"(d[27]), "+f"(d[28]), "+f"(d[29]), "+f"(d[30]), "+f"(d[31]),
      "+f"(d[32]), "+f"(d[33]), "+f"(d[34]), "+f"(d[35]), "+f"(d[36]), "+f"(d[37]), "+f"(d[38]), "+f"(d[39])
    : "l"(da), "l"(db), "r"(scale_d));
}
__device__ __forceinline__ void wgmma6_ss_n144_t1(float (&d)[72], uint64_t da, uint64_t db, int scale_d) {
  asm volatile("{\n.reg .pred p;\n"
    "setp.ne.b32 p, %74, 0;\n"
    "wgmma.mma_async.sync.aligned.m64n144k16.f32.bf16.bf16 "
    "{%0, %1, %2, %3, %4, %5, %6, %7, %8, %9, %10, %11, %12, %13, %14, %15, "
    "%16, %17, %18, %19, %20, %21, %22, %23, %24, %25, %26, %27, %28, %29, %30, %31, "
    "%32, %33, %34, %35, %36, %37, %38, %39, %40, %41, %42, %43, %44, %45, %46, %47, "
    "%48, %49, %50, %51, %52, %53, %54, %55, %56, %57, %58, %59, %60, %61, %62, %63, "
    "%64, %65, %66, %67, %68, %69, %70, %71}, "
    "%72, %73, p, 1, 1, 0, 1;\n}\n"
    : "+f"(d[0]), "+f"(d[1]), "+f"(d[2]), "+f"(d[3]), "+f"(d[4]), "+f"(d[5]), "+f"(d[6]), "+f"(d[7]),
      "+f"(d[8]), "+f"(d[9]), "+f"(d[10]), "+f"(d[11]), "+f"(d[12]), "+f"(d[13]), "+f"(d[14]), "+f"(d[15]),
      "+f"(d[16]), "+f"(d[17]), "+f"(d[18]), "+f"(d[19]), "+f"(d[20]), "+f"(d[21]), "+f"(d[22]), "+f"(d[23]),
      "+f"(d[24]), "+f"(d[25]), "+f"(d[26]), "+f"(d[27]), "+f"(d[28]), "+f"(d[29]), "+f"(d[30]), "+f"(d[31]),
      "+f"(d[32]), "+f"(d[33]), "+f"(d[34]), "+f"(d[35]), "+f"(d[36]), "+f"(d[37]), "+f"(d[38]), "+f"(d[39]),
      "+f"(d[40]), "+f"(d[41]), "+f"(d[42]), "+f"(d[43]), "+f"(d[44]), "+f"(d[45]), "+f"(d[46]), "+f"(d[47]),
      "+f"(d[48]), "+f"(d[49]), "+f"(d[50]), "+f"(d[51]), "+f"(d[52]), "+f"(d[53]), "+f"(d[54]), "+f"(d[55]),
      "+f"(d[56]), "+f"(d[57]), "+f"(d[58]), "+f"(d[59]), "+f"(d[60]), "+f"(d[61]), "+f"(d[62]), "+f"(d[63]),
      "+f"(d[64]), "+f"(d[65]), "+f"(d[66]), "+f"(d[67]), "+f"(d[68]), "+f"(d[69]), "+f"(d[70]), "+f"(d[71])
    : "l"(da), "l"(db), "r"(scale_d));
}
__device__ __forceinline__ void wgmma6_ss_n256_t1(float (&d)[128], uint64_t da, uint64_t db, int scale_d) {
  asm volatile("{\n.reg .pred p;\n"
    "setp.ne.b32 p, %130, 0;\n"
    "wgmma.mma_async.sync.aligned.m64n256k16.f32.bf16.bf16 "
    "{%0, %1, %2, %3, %4, %5, %6, %7, %8, %9, %10, %11, %12, %13, %14, %15, "
    "%16, %17, %18, %19, %20, %21, %22, %23, %24, %25, %26, %27, %28, %29, %30, %31, "
    "%32, %33, %34, %35, %36, %37, %38, %39, %40, %41, %42, %43, %44, %45, %46, %47, "
    "%48, %49, %50, %51, %52, %53, %54, %55, %56, %57, %58, %59, %60, %61, %62, %63, "
    "%64, %65, %66, %67, %68, %69, %70, %71, %72, %73, %74, %75, %76, %77, %78, %79, "
    "%80, %81, %82, %83, %84, %85, %86, %87, %88, %89, %90, %91, %92, %93, %94, %95, "
    "%96, %97, %98, %99, %100, %101, %102, %103, %104, %105, %106, %107, %108, %109, %110, %111, "
    "%112, %113, %114, %115, %116, %117, %118, %119, %120, %121, %122, %123, %124, %125, %126, %127}, "
    "%128, %129, p, 1, 1, 0, 1;\n}\n"
    : "+f"(d[0]), "+f"(d[1]), "+f"(d[2]), "+f"(d[3]), "+f"(d[4]), "+f"(d[5]), "+f"(d[6]), "+f"(d[7]),
      "+f"(d[8]), "+f"(d[9]), "+f"(d[10]), "+f"(d[11]), "+f"(d[12]), "+f"(d[13]), "+f"(d[14]), "+f"(d[15]),
      "+f"(d[16]), "+f"(d[17]), "+f"(d[18]), "+f"(d[19]), "+f"(d[20]), "+f"(d[21]), "+f"(d[22]), "+f"(d[23]),
      "+f"(d[24]), "+f"(d[25]), "+f"(d[26]), "+f"(d[27]), "+f"(d[28]), "+f"(d[29]), "+f"(d[30]), "+f"(d[31]),
      "+f"(d[32]), "+f"(d[33]), "+f"(d[34]), "+f"(d[35]), "+f"(d[36]), "+f"(d[37]), "+f"(d[38]), "+f"(d[39]),
      "+f"(d[40]), "+f"(d[41]), "+f"(d[42]), "+f"(d[43]), "+f"(d[44]), "+f"(d[45]), "+f"(d[46]), "+f"(d[47]),
      "+f"(d[48]), "+f"(d[49]), "+f"(d[50]), "+f"(d[51]), "+f"(d[52]), "+f"(d[53]), "+f"(d[54]), "+f"(d[55]),
      "+f"(d[56]), "+f"(d[57]), "+f"(d[58]), "+f"(d[59]), "+f"(d[60]), "+f"(d[61]), "+f"(d[62]), "+f"(d[63]),
      "+f"(d[64]), "+f"(d[65]), "+f"(d[66]), "+f"(d[67]), "+f"(d[68]), "+f"(d[69]), "+f"(d[70]), "+f"(d[71]),
      "+f"(d[72]), "+f"(d[73]), "+f"(d[74]), "+f"(d[75]), "+f"(d[76]), "+f"(d[77]), "+f"(d[78]), "+f"(d[79]),
      "+f"(d[80]), "+f"(d[81]), "+f"(d[82]), "+f"(d[83]), "+f"(d[84]), "+f"(d[85]), "+f"(d[86]), "+f"(d[87]),
      "+f"(d[88]), "+f"(d[89]), "+f"(d[90]), "+f"(d[91]), "+f"(d[92]), "+f"(d[93]), "+f"(d[94]), "+f"(d[95]),
      "+f"(d[96]), "+f"(d[97]), "+f"(d[98]), "+f"(d[99]), "+f"(d[100]), "+f"(d[101]), "+f"(d[102]), "+f"(d[103]),
      "+f"(d[104]), "+f"(d[105]), "+f"(d[106]), "+f"(d[107]), "+f"(d[108]), "+f"(d[109]), "+f"(d[110]), "+f"(d[111]),
      "+f"(d[112]), "+f"(d[113]), "+f"(d[114]), "+f"(d[115]), "+f"(d[116]), "+f"(d[117]), "+f"(d[118]), "+f"(d[119]),
      "+f"(d[120]), "+f"(d[121]), "+f"(d[122]), "+f"(d[123]), "+f"(d[124]), "+f"(d[125]), "+f"(d[126]), "+f"(d[127])
    : "l"(da), "l"(db), "r"(scale_d));
}

__device__ __forceinline__ void wg_fence() { asm volatile("wgmma.fence.sync.aligned;" ::: "memory"); }
__device__ __forceinline__ void wg_commit() { asm volatile("wgmma.commit_group.sync.aligned;" ::: "memory"); }
template <int N> __device__ __forceinline__ void wg_wait() { asm volatile("wgmma.wait_group.sync.aligned %0;" ::"n"(N) : "memory"); }
__host__ __device__ constexpr uint32_t dlo(uint32_t off, uint32_t lbo) { return (off >> 4) | ((lbo >> 4) << 16); }
__host__ __device__ constexpr uint32_t dhi(uint32_t sbo, uint32_t swz) { return (sbo >> 4) | (swz << 30); }
constexpr uint32_t HI_X = dhi(512, 2), HI_W = dhi(1024, 1), HI_A2 = dhi(256, 0), HI_K = dhi(640, 0), HI_V = dhi(128, 0), HI_T = dhi(256, 0);
constexpr uint32_t QB0 = dlo(8192, 2048), QB1 = QB0 + 384, QT1 = 48;
__device__ __forceinline__ float ex2(float x) { float y; asm volatile("ex2.approx.ftz.f32 %0, %1;" : "=f"(y) : "f"(x)); return y; }
template <uint32_t HI> __device__ __forceinline__ uint64_t mkdesc(uint32_t lo) {
    uint64_t d;
    asm("mov.b64 %0, {%1, %2};" : "=l"(d) : "r"(lo), "n"(HI));
    return d;
}
__device__ __forceinline__ float rcp_fast(float x) { float y; asm("rcp.approx.ftz.f32 %0, %1;" : "=f"(y) : "f"(x)); return y; }
__device__ __forceinline__ float tanh_fast(float x) { float y; asm("tanh.approx.f32 %0, %1;" : "=f"(y) : "f"(x)); return y; }
__device__ __forceinline__ uint32_t pack(float lo, float hi) { uint32_t y; asm("cvt.rn.bf16x2.f32 %0, %1, %2;" : "=r"(y) : "f"(hi), "f"(lo)); return y; }
template <int N> __device__ __forceinline__ void fence_regs(float (&d)[N]) {
#pragma unroll
    for (int i = 0; i < N; i++) asm volatile("" : "+f"(d[i])::"memory");
}
template <int N> __device__ __forceinline__ void fence_regs(uint32_t (&d)[N]) {
#pragma unroll
    for (int i = 0; i < N; i++) asm volatile("" : "+r"(d[i])::"memory");
}
template <int N> __device__ __forceinline__ void undef_regs(float (&d)[N]) {
#pragma unroll
    for (int i = 0; i < N; i++) asm volatile("" : "=f"(d[i]));
}
__device__ __forceinline__ void mbar_init(uint32_t bar, uint32_t cnt) { asm volatile("mbarrier.init.shared::cta.b64 [%0], %1;" ::"r"(bar), "r"(cnt) : "memory"); }
__device__ __forceinline__ void mbar_expect_tx(uint32_t bar, uint32_t bytes) { asm volatile("mbarrier.arrive.expect_tx.shared::cta.b64 _, [%0], %1;" ::"r"(bar), "r"(bytes) : "memory"); }
__device__ __forceinline__ void mbar_arrive(uint32_t bar) { asm volatile("mbarrier.arrive.shared::cta.b64 _, [%0];" ::"r"(bar) : "memory"); }
__device__ __forceinline__ void mbar_arrive_cluster(uint32_t bar, uint32_t cta) {
    asm volatile("{\n.reg .b32 ra;\nmapa.shared::cluster.u32 ra, %0, %1;\nmbarrier.arrive.shared::cluster.b64 _, [ra];\n}" ::"r"(bar), "r"(cta) : "memory");
}
__device__ __forceinline__ void mbar_wait(uint32_t bar, uint32_t parity) {
    asm volatile(
        "{\n.reg .pred p;\n.reg .u32 n;\n"
        "mbarrier.try_wait.parity.shared::cta.b64 p, [%0], %1;\n"
        "@p bra.uni LAB_DONE;\n"
        "mov.u32 n, 0;\n"
        "LAB_WAIT:\n"
        "mbarrier.try_wait.parity.shared::cta.b64 p, [%0], %1, 1000;\n"
        "@p bra.uni LAB_DONE;\n"
        "add.u32 n, n, 1;\n"
        "setp.ge.u32 p, n, 0x400000;\n"
        "@p trap;\n"
        "bra.uni LAB_WAIT;\n"
        "LAB_DONE:\n}" ::"r"(bar), "r"(parity) : "memory");
}
__device__ __forceinline__ void flag_wait(const uint32_t* p, uint32_t target) {
    asm volatile(
        "{\n.reg .pred p;\n.reg .u32 n;\n.reg .s32 v;\n"
        "mov.u32 n, 0;\n"
        "LAB_WAIT:\n"
        "ld.acquire.gpu.global.s32 v, [%0];\n"
        "sub.s32 v, v, %1;\n"
        "setp.ge.s32 p, v, 0;\n"
        "@p bra.uni LAB_DONE;\n"
        "add.u32 n, n, 1;\n"
        "setp.ge.u32 p, n, 0x800000;\n"
        "@p trap;\n"
        "bra.uni LAB_WAIT;\n"
        "LAB_DONE:\n}" ::"l"(p), "r"(target) : "memory");
}
__device__ __forceinline__ uint32_t flag_wait_bits(const uint32_t* p, uint32_t base, uint32_t mask) {
    uint32_t v;
    asm volatile(
        "{\n.reg .pred p;\n.reg .u32 n, t;\n"
        "mov.u32 n, 0;\n"
        "LAB_WAIT:\n"
        "ld.acquire.gpu.global.u32 %0, [%1];\n"
        "sub.u32 %0, %0, %2;\n"
        "and.b32 t, %0, %3;\n"
        "setp.ne.u32 p, t, 0;\n"
        "@p bra.uni LAB_DONE;\n"
        "add.u32 n, n, 1;\n"
        "setp.ge.u32 p, n, 0x800000;\n"
        "@p trap;\n"
        "bra.uni LAB_WAIT;\n"
        "LAB_DONE:\n}" : "=&r"(v) : "l"(p), "r"(base), "r"(mask) : "memory");
    return v;
}
__device__ __forceinline__ void flag_add(uint32_t* p) { asm volatile("red.release.gpu.global.add.u32 [%0], 1;" ::"l"(p) : "memory"); }
__device__ __forceinline__ void flag_addv(uint32_t* p, uint32_t v) { asm volatile("red.release.gpu.global.add.u32 [%0], %1;" ::"l"(p), "r"(v) : "memory"); }
__device__ __forceinline__ void fence_async_global() { asm volatile("fence.proxy.async.global;" ::: "memory"); }
__device__ __forceinline__ void fence_async_shared() { asm volatile("fence.proxy.async.shared::cta;" ::: "memory"); }
__device__ __forceinline__ bool elect_one() {
    uint32_t p;
    asm volatile("{\n.reg .pred p;\nelect.sync _|p, 0xffffffff;\nselp.u32 %0, 1, 0, p;\n}" : "=r"(p));
    return p != 0;
}
__device__ __forceinline__ uint32_t mbar_test(uint32_t bar, uint32_t parity) {
    uint32_t p;
    asm volatile("{\n.reg .pred p;\nmbarrier.test_wait.parity.shared::cta.b64 p, [%1], %2;\nselp.u32 %0, 1, 0, p;\n}" : "=r"(p) : "r"(bar), "r"(parity) : "memory");
    return p;
}
__device__ __forceinline__ void mbar_wait_unless(uint32_t done, uint32_t bar, uint32_t parity) {
    asm volatile(
        "{\n.reg .pred p;\n.reg .u32 n;\n"
        "setp.ne.u32 p, %2, 0;\n"
        "@p bra.uni LAB_DONE;\n"
        "mov.u32 n, 0;\n"
        "LAB_WAIT:\n"
        "mbarrier.try_wait.parity.shared::cta.b64 p, [%0], %1, 1000;\n"
        "@p bra.uni LAB_DONE;\n"
        "add.u32 n, n, 1;\n"
        "setp.ge.u32 p, n, 0x400000;\n"
        "@p trap;\n"
        "bra.uni LAB_WAIT;\n"
        "LAB_DONE:\n}" ::"r"(bar), "r"(parity), "r"(done) : "memory");
}
__device__ __forceinline__ void bulk_s2g(void* dst, uint32_t src, uint32_t bytes) {
    asm volatile("cp.async.bulk.global.shared::cta.bulk_group [%0], [%1], %2;" ::"l"(dst), "r"(src), "r"(bytes) : "memory");
}
__device__ __forceinline__ void bulk_s2c(uint32_t addr, uint32_t bytes, uint32_t bar, uint32_t cta) {
    asm volatile("{\n.reg .b32 d, b;\nmapa.shared::cluster.u32 d, %0, %3;\nmapa.shared::cluster.u32 b, %2, %3;\n"
                 "cp.async.bulk.shared::cluster.shared::cta.mbarrier::complete_tx::bytes [d], [%0], %1, [b];\n}"
                 ::"r"(addr), "r"(bytes), "r"(bar), "r"(cta) : "memory");
}
__device__ __forceinline__ void sts32(uint32_t a, uint32_t v) { asm volatile("st.shared.u32 [%0], %1;" ::"r"(a), "r"(v) : "memory"); }
__device__ __forceinline__ void sts128(uint32_t a, uint32_t x, uint32_t y, uint32_t z, uint32_t w) { asm volatile("st.shared.v4.u32 [%0], {%1, %2, %3, %4};" ::"r"(a), "r"(x), "r"(y), "r"(z), "r"(w) : "memory"); }
__device__ __forceinline__ void stsm4(uint32_t a, uint32_t r0, uint32_t r1, uint32_t r2, uint32_t r3) {
    asm volatile("stmatrix.sync.aligned.m8n8.x4.shared.b16 [%0], {%1, %2, %3, %4};" ::"r"(a), "r"(r0), "r"(r1), "r"(r2), "r"(r3) : "memory");
}
__device__ __forceinline__ void ldsm4(uint32_t* r, uint32_t a) {
    asm volatile("ldmatrix.sync.aligned.m8n8.x4.shared.b16 {%0, %1, %2, %3}, [%4];" : "=r"(r[0]), "=r"(r[1]), "=r"(r[2]), "=r"(r[3]) : "r"(a) : "memory");
}
__device__ __forceinline__ uint32_t lds32(uint32_t a) { uint32_t v; asm volatile("ld.shared.u32 %0, [%1];" : "=r"(v) : "r"(a) : "memory"); return v; }
__device__ __forceinline__ void tma_2d(uint32_t dst, const CUtensorMap* tm, int c0, int c1, uint32_t bar) {
    asm volatile("cp.async.bulk.tensor.2d.shared::cluster.global.mbarrier::complete_tx::bytes [%0], [%1, {%3, %4}], [%2];"
                 ::"r"(dst), "l"(tm), "r"(bar), "r"(c0), "r"(c1) : "memory");
}
__device__ __forceinline__ void tma_2d_mc(uint32_t dst, const CUtensorMap* tm, int c0, int c1, uint32_t bar) {
    asm volatile("cp.async.bulk.tensor.2d.shared::cluster.global.mbarrier::complete_tx::bytes.multicast::cluster [%0], [%1, {%3, %4}], [%2], %5;"
                 ::"r"(dst), "l"(tm), "r"(bar), "r"(c0), "r"(c1), "h"((uint16_t)3) : "memory");
}
__device__ __forceinline__ void tma_3d(uint32_t dst, const CUtensorMap* tm, int c0, int c1, int c2, uint32_t bar) {
    asm volatile("cp.async.bulk.tensor.3d.shared::cluster.global.mbarrier::complete_tx::bytes [%0], [%1, {%3, %4, %5}], [%2];"
                 ::"r"(dst), "l"(tm), "r"(bar), "r"(c0), "r"(c1), "r"(c2) : "memory");
}
__device__ __forceinline__ void tma_3d_mc(uint32_t dst, const CUtensorMap* tm, int c0, int c1, int c2, uint32_t bar) {
    asm volatile("cp.async.bulk.tensor.3d.shared::cluster.global.mbarrier::complete_tx::bytes.multicast::cluster [%0], [%1, {%3, %4, %5}], [%2], %6;"
                 ::"r"(dst), "l"(tm), "r"(bar), "r"(c0), "r"(c1), "r"(c2), "h"((uint16_t)3) : "memory");
}
__device__ __forceinline__ void bulk_g2s(uint32_t dst, const void* src, uint32_t bytes, uint32_t bar) {
    asm volatile("cp.async.bulk.shared::cluster.global.mbarrier::complete_tx::bytes [%0], [%1], %2, [%3];"
                 ::"r"(dst), "l"(src), "r"(bytes), "r"(bar) : "memory");
}
__device__ __forceinline__ void bulk_g2s_mc(uint32_t dst, const void* src, uint32_t bytes, uint32_t bar) {
    asm volatile("cp.async.bulk.shared::cluster.global.mbarrier::complete_tx::bytes.multicast::cluster [%0], [%1], %2, [%3], %4;"
                 ::"r"(dst), "l"(src), "r"(bytes), "r"(bar), "h"((uint16_t)3) : "memory");
}
__device__ __forceinline__ void mma_16816(float* d, uint32_t a0, uint32_t a1, uint32_t a2, uint32_t a3, uint32_t b0, uint32_t b1) {
    asm volatile("mma.sync.aligned.m16n8k16.row.col.f32.bf16.bf16.f32 {%0,%1,%2,%3}, {%4,%5,%6,%7}, {%8,%9}, {%0,%1,%2,%3};"
                 : "+f"(d[0]), "+f"(d[1]), "+f"(d[2]), "+f"(d[3]) : "r"(a0), "r"(a1), "r"(a2), "r"(a3), "r"(b0), "r"(b1));
}
__device__ __forceinline__ uint32_t movm_t(uint32_t a) { uint32_t d; asm volatile("movmatrix.sync.aligned.m8n8.trans.b16 %0, %1;" : "=r"(d) : "r"(a)); return d; }
__device__ __forceinline__ uint32_t ldg32(const uint8_t* p) { uint32_t v; asm volatile("ld.global.u32 %0, [%1];" : "=r"(v) : "l"(p) : "memory"); return v; }
__device__ __forceinline__ void stg32(uint8_t* p, uint32_t v) { asm volatile("st.global.u32 [%0], %1;" ::"l"(p), "r"(v) : "memory"); }

struct Ring {
    uint32_t slot;
    uint32_t phase;
    __device__ __forceinline__ void next() { if (++slot == NSTAGE) { slot = 0; phase ^= 1; } }
};

__device__ __forceinline__ void load_q(uint32_t (&q)[8], uint32_t qa, int lane) {
    q[0] = lds32(qa + lane * 4);       q[1] = lds32(qa + lane * 4 + 256);
    q[2] = lds32(qa + lane * 4 + 128); q[3] = lds32(qa + lane * 4 + 384);
    const uint32_t t0 = lds32(qa + 512 + (lane & ~3)), t1 = lds32(qa + 544 + (lane & ~3));
    q[4] = (lane & 3) == 2 ? t0 : 0u;  q[5] = (lane & 3) == 2 ? t1 : 0u;
}

__device__ __forceinline__ bool norm_o(uint32_t (&w)[6], const float (&o)[12], int lane, uint32_t gaddr) {
    const float l0 = __shfl_sync(0xffffffffu, o[8], (lane & ~3) | 1);
    const float l1 = __shfl_sync(0xffffffffu, o[10], (lane & ~3) | 1);
    const float i0 = rcp_fast(l0) * __uint_as_float(lds32(gaddr)), i1 = rcp_fast(l1) * __uint_as_float(lds32(gaddr + 32));
    uint32_t big = 0;
#pragma unroll
    for (int b = 0; b < 3; b++) {
        w[2 * b] = pack(o[4 * b] * i0, o[4 * b + 1] * i0);
        w[2 * b + 1] = pack(o[4 * b + 2] * i1, o[4 * b + 3] * i1);
        if (b == 2 && (lane & 3) != 0) w[4] = w[5] = 0u;
        big |= ((w[2 * b] & 0x7F807F80u) + 0x00800080u) | ((w[2 * b + 1] & 0x7F807F80u) + 0x00800080u);
    }
    const bool ok = fminf(l0, l1) >= 0x1p-30f && l0 <= 0x1p100f && l1 <= 0x1p100f && (big & 0x80008000u) == 0;
    return !__all_sync(0xffffffffu, ok);
}

__device__ __forceinline__ void attn_true_max(float (&o)[12], const uint32_t (&q)[8], const uint8_t* kv) {
    float m0 = -INFINITY, m1 = -INFINITY;
#pragma unroll
    for (int i = 0; i < 12; i++) o[i] = 0.f;
#pragma unroll 1
    for (int kb = 0; kb < SEQ / 16; kb++) {
        uint32_t t[2][5];
#pragma unroll
        for (int g = 0; g < 2; g++)
#pragma unroll
            for (int ch = 0; ch < 5; ch++) t[g][ch] = ldg32(kv + (kb * 2 + g) * 640 + ch * 128);
        float s[2][4];
#pragma unroll
        for (int g = 0; g < 2; g++) {
            s[g][0] = s[g][1] = s[g][2] = s[g][3] = 0.f;
            mma_16816(s[g], q[0], q[1], q[2], q[3], t[g][0], t[g][1]);
            mma_16816(s[g], q[4], q[5], 0u, 0u, t[g][4], 0u);
        }
        float x0 = fmaxf(fmaxf(s[0][0], s[0][1]), fmaxf(s[1][0], s[1][1]));
        float x1 = fmaxf(fmaxf(s[0][2], s[0][3]), fmaxf(s[1][2], s[1][3]));
        x0 = fmaxf(x0, __shfl_xor_sync(0xffffffffu, x0, 1)); x0 = fmaxf(x0, __shfl_xor_sync(0xffffffffu, x0, 2));
        x1 = fmaxf(x1, __shfl_xor_sync(0xffffffffu, x1, 1)); x1 = fmaxf(x1, __shfl_xor_sync(0xffffffffu, x1, 2));
        const float n0 = fmaxf(m0, x0), n1 = fmaxf(m1, x1);
        const float u0 = (n0 == -INFINITY) ? 0.f : n0, u1 = (n1 == -INFINITY) ? 0.f : n1;
        const float c0 = ex2(m0 - u0), c1 = ex2(m1 - u1);
        m0 = n0; m1 = n1;
#pragma unroll
        for (int b = 0; b < 3; b++) { o[4 * b] *= c0; o[4 * b + 1] *= c0; o[4 * b + 2] *= c1; o[4 * b + 3] *= c1; }
        const uint32_t a0 = pack(ex2(s[0][0] - u0), ex2(s[0][1] - u0)), a1 = pack(ex2(s[0][2] - u1), ex2(s[0][3] - u1));
        const uint32_t a2 = pack(ex2(s[1][0] - u0), ex2(s[1][1] - u0)), a3 = pack(ex2(s[1][2] - u1), ex2(s[1][3] - u1));
#pragma unroll
        for (int b = 0; b < 3; b++) mma_16816(&o[4 * b], a0, a1, a2, a3, movm_t(t[0][2 + b]), movm_t(t[1][2 + b]));
    }
}

__device__ __forceinline__ float geglu2(float g, float u) {
    const float p = fmaf(g * g, 0.044715f * 0.7978845608028654f, 0.7978845608028654f);
    const float th = tanh_fast(g * p);
    const float y = g * u;
    return fmaf(y, th, y);
}

struct Attn {
    float s[32];
    float o[12];
    uint32_t p[16];
    uint32_t q[8];
};

__global__ void __cluster_dims__(2, 1, 1) __launch_bounds__(384, 1)
fused_kernel(__nv_bfloat16* __restrict__ out, const __nv_bfloat16* __restrict__ x, const __nv_bfloat16* __restrict__ gate_w,
             const __grid_constant__ CUtensorMap tm_x, const __grid_constant__ CUtensorMap tm_qkv,
             const __grid_constant__ CUtensorMap tm_qkv8,
             const __grid_constant__ CUtensorMap tm_wg, const __grid_constant__ CUtensorMap tm_wu,
             const __grid_constant__ CUtensorMap tm_wd, const __grid_constant__ CUtensorMap tm_wo,
             const __grid_constant__ CUtensorMap tm_wd16, const __grid_constant__ CUtensorMap tm_wo16) {
    extern __shared__ uint8_t smem_raw[];
    const uint32_t sb = __shfl_sync(0xffffffffu, ((uint32_t)__cvta_generic_to_shared(smem_raw) + 1023) & ~1023u, 0);
    const uint32_t bars = sb + OFF_BAR;
    const uint32_t bar_full = bars, bar_empty = bars + 64;
    const uint32_t bar_ev = bars + 128;
    const uint32_t bar_rdy = bars + 256;
    const uint32_t bar_ep = bars + 320, bar_gate = bars + 328;
    const uint32_t bar_st = bars + 336;
    const uint32_t bar_late = bars + 408;
    const uint32_t bar_px = bars + 416;
    const uint32_t bar_free = bars + 424;
    const uint32_t s_epoch = bars + 448, s_zero = bars + 452, s_order = bars + 464, s_gate = bars + 512;

    const int cta = blockIdx.x >= NCTA ? blockIdx.x : ((blockIdx.x & 14) << 3) | ((blockIdx.x >> 4) << 1) | (blockIdx.x & 1);
    const int rank = cta & 1;
    const int j = (cta >> 1) & 7;
    const int m = (cta >> 4) * 2 + rank;
    const int hf = j >> 2, nt = j & 3;
    const int warp = __shfl_sync(0xffffffffu, threadIdx.x >> 5, 0);
    const int lane = threadIdx.x & 31;
    const int wg = warp >> 2;

    const bool leader = elect_one();
    if (leader) {
        if (warp == 8) {
#pragma unroll
            for (int e = 0; e < E0; e++) mbar_init(bar_full + e * 8, 2);
        } else if (warp < NSTAGE) {
            if (warp >= E0) mbar_init(bar_full + warp * 8, 2);
            mbar_init(bar_empty + warp * 8, 4);
        }
        asm volatile("fence.mbarrier_init.release.cluster;" ::: "memory");
    }
    asm volatile("barrier.cluster.arrive.relaxed.aligned;" ::: "memory");
    if (cta < NCTA && warp == 8 && leader) {
#pragma unroll 1
        for (int e = 0; e < E0; e++) {
            const uint32_t st = sb + e * SLOT, fb = bar_full + e * 8;
            mbar_arrive(fb);
            mbar_expect_tx(fb, 8192 + 12288 + 8192 + 1536);
            tma_2d(st + OFF_AX, &tm_x, e * 32, m * 128, fb);
#pragma unroll
            for (int r = 0; r < 2; r++) {
                tma_3d(st + 8192 + r * 6144, &tm_qkv, j * 72, e * 32 + r * 16, 0, fb);
                tma_3d(st + OFF_TL + r * 768, &tm_qkv8, j * 72 + 64, e * 32 + r * 16, 0, fb);
                tma_2d(st + r * 4096, r ? &tm_wu : &tm_wg, j * 576 + 512, e * 32, fb);
            }
        }
    }
    if (warp != 8) {
        if (leader && warp < 8) {
            const uint32_t lo = (warp >= 4 && warp <= 6) ? 1 : 4, hi = warp == 6 ? 4 : lo;
            mbar_init(bar_ev + warp * 32, lo); mbar_init(bar_ev + warp * 32 + 8, lo);
            mbar_init(bar_ev + warp * 32 + 16, hi); mbar_init(bar_ev + warp * 32 + 24, hi);
            if (warp < 4) mbar_init(bar_late + warp * 8, 1);
            sts32(s_zero, 0u); sts32(s_zero + 4, 0u);
            asm volatile("fence.mbarrier_init.release.cluster;" ::: "memory");
        }
        asm volatile("bar.sync 1, 352;" ::: "memory");
    }
    asm volatile("barrier.cluster.wait.acquire.aligned;" ::: "memory");

    if (wg == 2) {
        asm volatile("setmaxnreg.dec.sync.aligned.u32 24;");
        if (cta >= NCTA) {
            if (warp == 9 && elect_one()) {
                const uint32_t ep = g_flags[FL_E + cta * 32] + 1;
                g_flags[FL_E + cta * 32] = ep;
                mbar_wait(bar_ev + 2 * 8, 0);
                mbar_wait(bar_ev + 10 * 8, 0);
                flag_add(&g_flags[FL_G + (cta - NCTA) * 32]);
#pragma unroll 1
                for (int i = 0; i < 2; i++) {
                    const int jx = (cta - NCTA) * 2 + i;
                    flag_wait(&g_flags[FL_KV + jx * 32 + 1], ep * 32);
                    fence_async_global();
                    mbar_expect_tx(bar_rdy + i * 8, 20480 + 16 * 4608);
#pragma unroll 1
                    for (int p = 0; p < 8; p++) bulk_g2s(sb + 40960 + (i * 8 + p) * 9216, g_q3 + (p * 16 + jx * 2) * 4608, 9216, bar_rdy + i * 8);
                    bulk_g2s(sb + i * 20480, g_kv + (size_t)(jx * 4 + 3) * HEAD_BYTES + 28 * 5120, 20480, bar_rdy + i * 8);
                }
#pragma unroll 1
                for (int i = 0; i < 2; i++) {
                    mbar_wait(bar_ev + i * 8, 0);
                    mbar_wait(bar_ev + (8 + i) * 8, 0);
                    flag_add(&g_flags[FL_KV + ((cta - NCTA) * 2 + i) * 32 + 2]);
                }
            }
        } else if (warp == 8) {
            if (elect_one()) {
                Ring r{E0, 1};
                const int row0 = m * 128;
                const CUtensorMap* tw = rank ? &tm_wu : &tm_wg;
#pragma unroll 1
                for (int kk = E0; kk < 18; kk++) {
                    const uint32_t st = sb + r.slot * SLOT, fb = bar_full + r.slot * 8;
                    mbar_wait(bar_empty + r.slot * 8, r.phase);
                    mbar_arrive(fb);
                    mbar_expect_tx(fb, 8192 + 12288 + 8192 + 1536);
                    tma_2d(st + OFF_AX, &tm_x, kk * 32, row0, fb);
                    tma_3d_mc(st + 8192 + rank * 6144, &tm_qkv, j * 72, kk * 32 + rank * 16, 0, fb);
                    tma_3d_mc(st + OFF_TL + rank * 768, &tm_qkv8, j * 72 + 64, kk * 32 + rank * 16, 0, fb);
                    tma_2d_mc(st + rank * 4096, tw, j * 576 + 512, kk * 32, fb);
                    r.next();
                }
                int k0 = DM - NSTAGE * 32;
#pragma unroll 1
                for (int t = 0; t < 4; t++)
#pragma unroll 1
                    for (int kk = 0; kk < 18; kk++) {
                        const uint32_t st = sb + r.slot * SLOT, fb = bar_full + r.slot * 8;
                        mbar_wait(bar_empty + r.slot * 8, r.phase);
                        if (t == 0 && kk < 2) mbar_arrive(fb);
                        const bool have_x = kk < NSTAGE;
                        mbar_expect_tx(fb, have_x ? 16384 : 8192 + 16384);
                        tma_2d_mc(st + rank * 8192, tw, j * 576 + t * 128, k0, fb);
                        tma_2d_mc(st + rank * 8192 + 4096, tw, j * 576 + t * 128 + 64, k0, fb);
                        if (!have_x) tma_2d(st + OFF_AX, &tm_x, k0, row0, fb);
                        k0 += kk == 17 ? DM + 32 - NSTAGE * 32 : 32;
                        if (k0 >= DM) k0 -= DM;
                        r.next();
                    }
                const uint8_t* a2 = g_a2 + (size_t)m * A2_TILE;
                mbar_wait(bar_rdy + 4 * 8, 0);
#pragma unroll 1
                for (int n = 0; n < 48; n++) {
                    const int u = n >> 2, jj = n & 3;
                    const uint32_t st = sb + r.slot * SLOT, fb = bar_full + r.slot * 8;
                    mbar_wait(bar_empty + r.slot * 8, r.phase);
                    mbar_expect_tx(fb, 12288 + 12288 + STRIPB);
                    const int ks = (hf * 4 + jj) * 36 + u * 3;
#pragma unroll
                    for (int b = 0; b < 2; b++) tma_2d_mc(st + b * 6144 + rank * 3072, &tm_wd, nt * 128 + (b ^ hf) * 64, ks * 16 + rank * 24, fb);
                    tma_2d_mc(st + 12288 + rank * 3072, &tm_wd16, 512 + nt * 16, ks * 16 + rank * 24, fb);
                    if (jj == 0) { mbar_wait(bar_rdy + ((3 * u + 2) >> 3) * 8, 0); fence_async_global(); }
                    bulk_g2s(st + OFF_A2, a2 + ks * 4096, 12288, fb);
                    r.next();
                }
#pragma unroll 1
                for (int n = 0; n < 4; n++) {
                    const uint32_t st = sb + r.slot * SLOT, fb = bar_full + r.slot * 8;
                    mbar_wait(bar_empty + r.slot * 8, r.phase);
                    mbar_expect_tx(fb, 12288 + 12288 + STRIPB);
                    const int pr = hf * 2 + (n & 1), head = (pr * 2 + rank) * 4 + (n >> 1);
#pragma unroll
                    for (int b = 0; b < 2; b++) tma_2d_mc(st + b * 6144 + rank * 3072, &tm_wo, nt * 128 + (b ^ hf) * 64, head * 18, fb);
                    tma_2d_mc(st + 12288 + rank * 3072, &tm_wo16, 512 + nt * 16, head * 18, fb);
                    if (n == 0) { mbar_wait(bar_rdy + 5 * 8, 0); fence_async_global(); }
                    bulk_g2s(st + OFF_A2, a2 + (288 + ((n >> 1) * 4 + pr) * 3) * 4096, 12288, fb);
                    r.next();
                }
                mbar_expect_tx(bar_late, 4 * (6144 + STRIPB));
#pragma unroll 1
                for (int n = 0; n < 8; n++) {
                    const uint32_t st = sb + r.slot * SLOT, fb = bar_full + r.slot * 8;
                    mbar_wait(bar_empty + r.slot * 8, r.phase);
                    if (n >= 2) mbar_arrive(fb);
                    if (n < 4) mbar_expect_tx(fb, 12288 + 6144 + STRIPB);
                    const int head = ((n & 3) * 2 + rank) * 4 + 2 + (n >> 2);
                    tma_2d_mc(st + rank * 3072, &tm_wo, nt * 128 + hf * 64, head * 18, n < 4 ? fb : bar_late);
                    tma_2d_mc(st + 6144 + rank * 3072, &tm_wo16, 512 + nt * 16, head * 18, n < 4 ? fb : bar_late);
                    if (n < 4) bulk_g2s(st + OFF_A2, a2 + (288 + (8 + n) * 3) * 4096, 12288, fb);
                    r.next();
                }
                mbar_wait(bar_ep, 0);
                const uint32_t base = (lds32(s_epoch) - 1) * 0x04040404u;
                uint32_t todo = 0x04040404u, k = 2;
#pragma unroll 1
                while (todo) {
                    const uint32_t got = flag_wait_bits(&g_flags[FL_M + m * 64 + FM_LATE], base, todo) & todo;
                    fence_async_global();
#pragma unroll 1
                    for (int pr = 0; pr < 4; pr++)
                        if ((got >> (pr * 8)) & 4) {
                            sts32(s_order + k * 4, (2 + pr) * (SLOT >> 4));
                            mbar_expect_tx(bar_full + k * 8, 12288);
                            bulk_g2s(sb + k * SLOT + OFF_A2, a2 + (288 + (12 + pr) * 3) * 4096, 12288, bar_full + k * 8);
                            k++;
                        }
                    todo &= ~got;
                }
            }
        } else if (warp == 9) {
            if (elect_one()) {
                const uint32_t ep = g_flags[FL_E + cta * 32] + 1;
                g_flags[FL_E + cta * 32] = ep;
                sts32(s_epoch, ep);
                mbar_arrive(bar_ep);
                Ring r{0, 1};
                const uint8_t* kv = g_kv + (size_t)(j * 4) * HEAD_BYTES + rank * 2560;
                const int rot = (cta >> 4) * 4;
                uint32_t have = flag_wait_bits(&g_flags[FL_KV + j * 32], (ep - 1) * 0x44444444u, 4u << rot);
                fence_async_global();
#pragma unroll 1
                for (int it = 4; it < 124; it++) {
                    const uint32_t fb = bar_full + r.slot * 8;
                    if (it < 32 && !((have >> ((it + rot) & 28)) & 4)) {
                        have = flag_wait_bits(&g_flags[FL_KV + j * 32], (ep - 1) * 0x44444444u, 4u << ((it + rot) & 28));
                        fence_async_global();
                    }
                    if (it == 24) { flag_wait(&g_flags[FL_KV + j * 32 + 1], ep * 32); fence_async_global(); }
                    mbar_wait(bar_empty + r.slot * 8, r.phase);
                    mbar_expect_tx(fb, 5120);
                    bulk_g2s_mc(sb + r.slot * SLOT + OFF_KV + rank * 2560, kv + (it < 32 ? (it + rot) & 31 : it) * 5120, 2560, fb);
                    r.next();
                }
                flag_wait(&g_flags[FL_KV + j * 32 + 2], ep);
                mbar_arrive(bar_px);
                uint32_t* fr = &g_flags[FL_M + m * 64 + FM_R];
                mbar_wait(bar_ev + 6 * 8, 0);
                mbar_wait(bar_ev + 14 * 8, 0);
                flag_add(fr + j);
                flag_wait(fr + (j ^ 4), ep);
                mbar_arrive(bar_rdy + 6 * 8);
            }
        } else {
            const int w = warp - 10;
            if (elect_one()) {
                const uint32_t mine = 2 + rank * 2 + w, other = 2 + (rank ^ 1) * 2 + w;
                mbar_wait(bar_st + w * 8, 0);
                bulk_s2g(g_kv + (size_t)(j * 4) * HEAD_BYTES + (m * 16 + w * 8) * 640, sb + mine * SLOT + OFF_KV, 5120);
                asm volatile("cp.async.bulk.commit_group;" ::: "memory");
                mbar_arrive(bar_full + mine * 8);
                mbar_expect_tx(bar_full + other * 8, 5120);
#pragma unroll 1
                for (int i = 0; i < 2; i++) {
                    if (i == rank) {
                        mbar_wait(bar_empty + mine * 8, 0);
                        bulk_s2c(sb + mine * SLOT + OFF_KV, 5120, bar_full + mine * 8, rank ^ 1);
                    } else {
                        asm volatile("cp.async.bulk.wait_group 0;" ::: "memory");
                        flag_addv(&g_flags[FL_KV + j * 32], 1u << ((cta >> 4) * 4));
                    }
                }
                mbar_wait(bar_st + (2 + w) * 8, 0);
                __nanosleep(1500);
                bulk_s2g(g_q3 + cta * 4608 + w * 2304, sb + OFF_Q + 3 * 4608 + w * 2304, 2304);
#pragma unroll 1
                for (int h = 1; h < 4; h++) {
                    __nanosleep(200);
                    bulk_s2g(g_kv + (size_t)(j * 4 + h) * HEAD_BYTES + (m * 16 + w * 8) * 640, sb + (w * 3 + h - 1) * SLOT + OFF_GAP, 5120);
                    asm volatile("cp.async.bulk.commit_group;\ncp.async.bulk.wait_group 0;" ::: "memory");
                }
                mbar_arrive(bar_free + w * 8);
                flag_add(&g_flags[FL_KV + j * 32 + 1]);
            }
            __syncwarp();
            uint32_t* fm = &g_flags[FL_M + m * 64];
            mbar_wait(bar_ep, 0);
            const uint32_t ep = lds32(s_epoch);
            if (w == 1) {
                flag_wait(&g_flags[FL_G + (m >> 2) * 32], ep);
                const uint4 gv = __ldcg((const uint4*)(g_gate + m * 128) + lane);
                sts128(s_gate + lane * 16, gv.x, gv.y, gv.z, gv.w);
                __syncwarp();
                if (lane == 0) mbar_arrive(bar_gate);
            }
            if (elect_one()) {
#pragma unroll 1
                for (int i = 0; i < 6; i++) {
                    const int e = i == 0 ? 4 : i == 5 ? 5 : i - 1;
                    mbar_wait(bar_ev + (w * 8 + e) * 8, 0);
                    if (e < 3) {
                        uint8_t* hp = g_a2 + (size_t)m * A2_TILE + (j * 36 + e * 8) * 4096 + w * 2048;
#pragma unroll 1
                        for (int k = 0; k < 8; k++) {
                            const int g = (k * 11) >> 5;
                            bulk_s2g(hp + k * 4096, sb + (w * 3 + g) * SLOT + OFF_GAP + (k - g * 3) * 2048, 2048);
                        }
                        asm volatile("cp.async.bulk.commit_group;\ncp.async.bulk.wait_group 0;" ::: "memory");
                    }
                    uint32_t* fl = fm + FM_H + (e == 5 ? 5 : hf * 8 + e);
                    flag_add(fl);
                    if (w == 0) { flag_wait(fl, ep * (e == 5 ? 16 : 8)); mbar_arrive(bar_rdy + e * 8); }
                }
                mbar_wait(bar_ev + (w * 8 + 7) * 8, 0);
                flag_addv(fm + FM_LATE, 1u << ((j >> 1) * 8));
            }
        }
    } else {
        asm volatile("setmaxnreg.inc.sync.aligned.u32 240;");
        const int wq = warp & 3;
        const int c = lane & 3;
        const int tid = threadIdx.x & 127;
        const int grp = wg * 8 + wq * 2;
        const uint32_t sbd = (sb & 0x3FFFF) >> 4;
        uint32_t sd = sbd, pd = sbd, fb = bar_full, pb = bar_full, ph = 0;
#define STAGE_NEXT do { pd = sd; sd = (sd == sbd + (NSTAGE - 1) * (SLOT >> 4)) ? sbd : sd + (SLOT >> 4);           \
                        pb = fb; fb += 8; if (fb == bar_full + NSTAGE * 8) { fb = bar_full; ph ^= 1; } } while (0)
        auto release = [&]() { if (tid < 2) mbar_arrive_cluster(pb + 64, tid); };
        auto signal = [&](int e) { __syncwarp(); if (lane == 0) mbar_arrive(bar_ev + (wg * 8 + e) * 8); };
        if (cta >= NCTA) {
            {
                float wv[72];
#pragma unroll
                for (int i = 0; i < 9; i++) {
                    const uint4 t = __ldg((const uint4*)gate_w + (lane & 7) + i * 8);
                    const uint32_t u[4] = {t.x, t.y, t.z, t.w};
#pragma unroll
                    for (int e = 0; e < 4; e++) { wv[8 * i + 2 * e] = __uint_as_float(u[e] << 16); wv[8 * i + 2 * e + 1] = __uint_as_float(u[e] & 0xffff0000u); }
                }
                __nanosleep(1500);
#pragma unroll 1
                for (int b = 0; b < 8; b++) {
                    const int row = (cta - NCTA) * 512 + warp * 64 + b * 8 + (lane >> 3);
                    uint4 xa[2][9];
#pragma unroll
                    for (int r = 0; r < 2; r++)
#pragma unroll
                        for (int i = 0; i < 9; i++) xa[r][i] = __ldg((const uint4*)(x + (size_t)(row + r * 4) * DM) + (lane & 7) + i * 8);
#pragma unroll
                    for (int r = 0; r < 2; r++) {
                        float z = 0.f, y = 0.f;
#pragma unroll
                        for (int i = 0; i < 9; i++) {
                            const uint32_t u[4] = {xa[r][i].x, xa[r][i].y, xa[r][i].z, xa[r][i].w};
#pragma unroll
                            for (int e = 0; e < 4; e++) {
                                z = fmaf(__uint_as_float(u[e] << 16), wv[8 * i + 2 * e], z);
                                y = fmaf(__uint_as_float(u[e] & 0xffff0000u), wv[8 * i + 2 * e + 1], y);
                            }
                        }
                        z += y;
#pragma unroll
                        for (int d = 1; d < 8; d <<= 1) z += __shfl_xor_sync(0xffffffffu, z, d);
                        if ((lane & 7) == 0) g_gate[row + r * 4] = rcp_fast(1.f + ex2(-1.4426950408889634f * z));
                    }
                }
                signal(2);
            }
            float s0[64], s1[64], o[12];
            uint32_t p0[32], p1[32], q[8];
            q[6] = lds32(s_zero); q[7] = lds32(s_zero + 4);
#pragma unroll
            for (int i = 0; i < 12; i++) o[i] = 0.f;
            auto store_px = [&](int u) {
                const int src = ((u & 15) >> 1) * 16 + ((cta - NCTA) * 2 + (u >> 4)) * 2 + (u & 1);
                float4* dst = g_px + (size_t)(src * 2 + wg) * 3 * 128 + tid;
#pragma unroll
                for (int i = 0; i < 3; i++) __stcg(dst + i * 128, make_float4(o[4 * i], o[4 * i + 1], o[4 * i + 2], o[4 * i + 3]));
            };
            mbar_wait(bar_rdy, 0);
            load_q(q, sb + 40960 + warp * 576, lane);
            fence_regs(q); fence_regs(o);
            wg_fence();
            wgmma_rs_n128_t0<HI_K>(s0, q[0], q[1], q[2], q[3], sbd + dlo(0, 128), 0);
            wgmma_rs_n128_t0<HI_K>(s0, q[4], q[5], q[6], q[7], sbd + dlo(512, 0), 1);
            wg_commit();
            wg_wait<0>();
            fence_regs(s0);
#pragma unroll 1
            for (int u = 0; u < 32; u++) {
                const uint32_t kb = sbd + (u >> 4) * 1280;
                wg_fence();
                wgmma_rs_n128_t0<HI_K>(s1, q[0], q[1], q[2], q[3], kb + dlo(10240, 128), 0);
                wgmma_rs_n128_t0<HI_K>(s1, q[4], q[5], q[6], q[7], kb + dlo(10240 + 512, 0), 1);
                wg_commit();
#pragma unroll
                for (int i = 0; i < 32; i++) p0[i] = pack(ex2(s0[2 * i]), ex2(s0[2 * i + 1]));
                fence_regs(p0);
                wg_wait<0>();
                fence_regs(o); fence_regs(s1); fence_regs(q);
                store_px(u > 0 ? u - 1 : 0);
                if (u == 16) signal(0);
                if (u == 15) mbar_wait(bar_rdy + 8, 0);
                const int un = u < 31 ? u + 1 : u;
                load_q(q, sb + 40960 + un * 4608 + warp * 576, lane);
                fence_regs(q);
                const uint32_t kn = sbd + (un >> 4) * 1280;
                wg_fence();
#pragma unroll
                for (int i = 0; i < 8; i++) wgmma_rs_n24_t1<HI_V>(o, p0[4 * i], p0[4 * i + 1], p0[4 * i + 2], p0[4 * i + 3], kb + dlo(256, 640) + 80 * i, i != 0);
                wgmma_rs_n128_t0<HI_K>(s0, q[0], q[1], q[2], q[3], kn + dlo(0, 128), 0);
                wgmma_rs_n128_t0<HI_K>(s0, q[4], q[5], q[6], q[7], kn + dlo(512, 0), 1);
                wg_commit();
#pragma unroll
                for (int i = 0; i < 32; i++) p1[i] = pack(ex2(s1[2 * i]), ex2(s1[2 * i + 1]));
                fence_regs(p1);
                wg_fence();
#pragma unroll
                for (int i = 0; i < 8; i++) wgmma_rs_n24_t1<HI_V>(o, p1[4 * i], p1[4 * i + 1], p1[4 * i + 2], p1[4 * i + 3], kb + dlo(10240 + 256, 640) + 80 * i, 1);
                wg_commit();
                wg_wait<1>();
                fence_regs(s0); fence_regs(p0);
            }
            wg_wait<0>();
            fence_regs(o);
            store_px(31);
            signal(1);
            return;
        }
        Attn at;

        uint8_t* a2w = g_a2 + (size_t)m * A2_TILE + grp * 256 + lane * 4;
        const uint32_t qa = sb + OFF_Q + warp * 576;
        float acc[128];
        {
            float qkv[96], tl[12], gu[64];
            const uint32_t xrow = wg * 64 + wq * 16 + (lane & 15);
            const uint32_t xa0 = (sb & ~0x3FFFFu) + OFF_AX + xrow * 64 + (((lane >> 4) ^ ((xrow >> 1) & 3)) << 4);
            uint32_t xf[2][8];
#pragma unroll 1
            for (int k2 = 0; k2 < 18 - DEFER; k2 += 2) {
#pragma unroll
                for (int h = 0; h < 2; h++) {
                    const int kk = k2 + h;
                    mbar_wait(fb, ph);
                    ldsm4(&xf[h][0], xa0 + sd * 16);
                    ldsm4(&xf[h][4], (xa0 ^ 32) + sd * 16);
                    fence_regs(xf[h]);
                    const uint32_t db = sd + dlo(0, 4096), dt = sd + dlo(OFF_TL, 128);
                    wg_fence();
                    wgmma_rs_n192_t1<HI_W>(qkv, xf[h][0], xf[h][1], xf[h][2], xf[h][3], sd + QB0, kk != 0);
                    wgmma_rs_n24_t1<HI_T>(tl, xf[h][0], xf[h][1], xf[h][2], xf[h][3], dt, kk != 0);
                    wgmma_rs_n128_t1<HI_W>(gu, xf[h][0], xf[h][1], xf[h][2], xf[h][3], db, kk != 0);
                    wgmma_rs_n192_t1<HI_W>(qkv, xf[h][4], xf[h][5], xf[h][6], xf[h][7], sd + QB1, 1);
                    wgmma_rs_n24_t1<HI_T>(tl, xf[h][4], xf[h][5], xf[h][6], xf[h][7], dt + QT1, 1);
                    wgmma_rs_n128_t1<HI_W>(gu, xf[h][4], xf[h][5], xf[h][6], xf[h][7], db + 128, 1);
                    wg_commit();
                    wg_wait<1>();
                    if (kk > 0) release();
                    STAGE_NEXT;
                }
            }
#pragma unroll
            for (int kk = 0; kk < DEFER; kk++) {
                mbar_wait(fb + kk * 8, ph);
                const uint32_t st = sd + kk * (SLOT >> 4);
                const uint32_t da = st + wg * 256 + dlo(OFF_AX, 16), dt = st + dlo(OFF_TL, 128);
                wg_fence();
                wgmma_ss_n192_t1<HI_X, HI_W>(qkv, da, st + QB0, 1);
                wgmma_ss_n24_t1<HI_X, HI_T>(tl, da, dt, 1);
                wgmma_ss_n192_t1<HI_X, HI_W>(qkv, da + 2, st + QB1, 1);
                wgmma_ss_n24_t1<HI_X, HI_T>(tl, da + 2, dt + QT1, 1);
                wg_commit();
                if (kk == 0) { wg_wait<1>(); release(); }
            }
#pragma unroll
            for (int kk = 0; kk < DEFER; kk++) {
                const uint32_t st = sd + kk * (SLOT >> 4);
                const uint32_t da = st + wg * 256 + dlo(OFF_AX, 16), db = st + dlo(0, 4096);
                wgmma_ss_n128_t1<HI_X, HI_W>(gu, da, db, 1);
                wgmma_ss_n128_t1<HI_X, HI_W>(gu, da + 2, db + 128, 1);
            }
            wg_commit();
            wg_wait<1>();
            fence_regs(qkv); fence_regs(tl);
            constexpr float QS = 0.23570226039551584f * 1.4426950408889634f;
            uint32_t kp[9][2], vp[9][2];
#pragma unroll
            for (int i = 0; i < 9; i++) {
                const float* k4 = i < 8 ? &qkv[32 + 4 * i] : &tl[4];
                const float* v4 = i < 8 ? &qkv[64 + 4 * i] : &tl[8];
                kp[i][0] = pack(k4[0], k4[1]); kp[i][1] = pack(k4[2], k4[3]);
                vp[i][0] = pack(v4[0], v4[1]); vp[i][1] = pack(v4[2], v4[3]);
            }
            const int quad = lane & ~3;
            const uint32_t cst = c == 1 ? 0x3F80u : 0u;
            {
                const uint32_t a = sb + (2 + rank * 2 + wg) * SLOT + OFF_KV + wq * 1280 + lane * 4;
#pragma unroll
                for (int r = 0; r < 2; r++) {
                    const uint32_t kt = __shfl_sync(0xffffffffu, kp[2][r], quad);
                    sts32(a + r * 640, kp[0][r]);       sts32(a + r * 640 + 128, kp[1][r]);
                    sts32(a + r * 640 + 256, vp[0][r]); sts32(a + r * 640 + 384, vp[1][r]);
                    sts32(a + r * 640 + 512, c == 0 ? vp[2][r] : c == 2 ? kt : cst);
                }
                fence_async_shared();
                __syncwarp();
                if (lane == 0) mbar_arrive(bar_st + wg * 8);
            }
#pragma unroll
            for (int i = 0; i < 9; i++) {
                const float* q4 = i < 8 ? &qkv[4 * i] : &tl[0];
                const uint32_t q0 = pack(q4[0] * QS, q4[1] * QS), q1 = pack(q4[2] * QS, q4[3] * QS);
                if (i < 2) { at.q[2 * i] = q0; at.q[2 * i + 1] = q1; }
                else {
                    if (i == 2) {
                        const uint32_t t0 = __shfl_sync(0xffffffffu, q0, quad), t1 = __shfl_sync(0xffffffffu, q1, quad);
                        at.q[4] = c == 2 ? t0 : 0u; at.q[5] = c == 2 ? t1 : 0u;
                    }
                    const int lc = 8 * i + 2 * c;
                    const int hd = (lc * 3641) >> 16;
                    const int d = lc - hd * 18;
                    const bool last = (i & 1) == 0 && c == i / 2 - 1;
                    const uint32_t aq = qa + hd * 4608 + (last ? 512 + (lane >> 2) * 4 : (d >> 3) * 128 + (d & 7) * 2 + (lane >> 2) * 16);
                    if (i > 2 || c > 0) { sts32(aq, q0); sts32(aq + (last ? 32 : 256), q1); }
                }
            }
            mbar_wait(bar_st, 0);
            mbar_wait(bar_st + 8, 0);
#pragma unroll
            for (int i = 2; i < 9; i++) {
                const int lc = 8 * i + 2 * c;
                const int hd = (lc * 3641) >> 16;
                const int d = lc - hd * 18;
                const uint32_t ak = sb + (wg * 3 - 1 + hd) * SLOT + OFF_GAP + wq * 1280 + (lane >> 2) * 16;
                const uint32_t off = (d >> 3) * 128 + (d & 7) * 2;
                if ((i & 1) == 0 && c == i / 2 - 1) {
                    if (i > 2) { sts128(ak + 512, vp[i][0], 0x3F80u, kp[i][0], 0u); sts128(ak + 512 + 640, vp[i][1], 0x3F80u, kp[i][1], 0u); }
                } else {
                    sts32(ak + off, kp[i][0]); sts32(ak + off + 640, kp[i][1]); sts32(ak + off + 256, vp[i][0]); sts32(ak + off + 256 + 640, vp[i][1]);
                }
            }
            fence_async_shared();
            __syncwarp();
            if (lane == 0) mbar_arrive(bar_st + (2 + wg) * 8);
            wg_wait<0>();
            fence_regs(gu);
            if (tid < 2 * DEFER) mbar_arrive_cluster(fb + 64 + (tid >> 1) * 8, tid & 1);
#pragma unroll
            for (int kk = 0; kk < 2; kk++) {
                mbar_wait(bar_full + kk * 8, 1);
                const uint32_t st = sbd + kk * (SLOT >> 4);
                const uint32_t da = st + wg * 256 + dlo(OFF_AX, 16), db = st + dlo(0, 4096);
                wg_fence();
                wgmma_ss_n256_t1<HI_X, HI_W>(acc, da, db, kk);
                wgmma_ss_n256_t1<HI_X, HI_W>(acc, da + 2, db + 128, 1);
                wg_commit();
            }
            sd = sbd + 2 * (SLOT >> 4); fb = bar_full + 16; pb = bar_full; ph = 1;
            uint8_t* hp = a2w + (j * 36 + 32) * 4096;
#pragma unroll
            for (int i = 0; i < 16; i++)
                stg32(hp + (i >> 2) * 4096 + ((i >> 1) & 1) * 128 + (i & 1) * 256, pack(geglu2(gu[2 * i], gu[32 + 2 * i]), geglu2(gu[2 * i + 1], gu[32 + 2 * i + 1])));
            signal(4);
            wg_wait<1>();
            release();
            mbar_wait(fb, ph);
        }

        const uint32_t gaddr = s_gate + (grp * 8 + (lane >> 2)) * 4;
        at.q[6] = lds32(s_zero); at.q[7] = lds32(s_zero + 4);
#pragma unroll
        for (int i = 0; i < 16; i++) at.p[i] = 0u;
#pragma unroll
        for (int i = 0; i < 12; i++) at.o[i] = 0.f;
        fence_regs(at.q); fence_regs(at.p); fence_regs(at.o);
        pd = sd;
        uint32_t rel = bar_empty + 8;
        asm volatile("mapa.shared::cluster.u32 %0, %0, %1;" : "+r"(rel) : "r"(tid & 1));
        const uint32_t rel_off = rel - (bar_full + 8);

#define ISSUE_PV() do {                                                                                            \
            const uint32_t dv = pd + dlo(OFF_KV + 256, 640);                                                       \
            wgmma_rs_n24_t1<HI_V>(at.o, at.p[0], at.p[1], at.p[2], at.p[3], dv, 1);                                \
            wgmma_rs_n24_t1<HI_V>(at.o, at.p[4], at.p[5], at.p[6], at.p[7], dv + 80, 1);                           \
            wgmma_rs_n24_t1<HI_V>(at.o, at.p[8], at.p[9], at.p[10], at.p[11], dv + 160, 1);                        \
            wgmma_rs_n24_t1<HI_V>(at.o, at.p[12], at.p[13], at.p[14], at.p[15], dv + 240, 1);                      \
        } while (0)
#define EXPS() do {                                                                                                \
            _Pragma("unroll") for (int i = 0; i < 16; i++) at.p[i] = pack(ex2(at.s[2 * i]), ex2(at.s[2 * i + 1])); \
            fence_regs(at.p);                                                                                      \
        } while (0)
#define FUSED_STEP(DV, DK, NB, NPH, REL, GEMM_CODE) do {                                                           \
            wg_fence();                                                                                            \
            wgmma6_rs_n24_t1(at.o, at.p[0], at.p[1], at.p[2], at.p[3], (DV), 1);                                   \
            wgmma6_rs_n24_t1(at.o, at.p[4], at.p[5], at.p[6], at.p[7], (DV) + 80, 1);                              \
            wgmma6_rs_n24_t1(at.o, at.p[8], at.p[9], at.p[10], at.p[11], (DV) + 160, 1);                           \
            wgmma6_rs_n24_t1(at.o, at.p[12], at.p[13], at.p[14], at.p[15], (DV) + 240, 1);                         \
            wgmma6_rs_n64_t0(at.s, at.q[0], at.q[1], at.q[2], at.q[3], (DK) + dlo(0, 128), 0);                     \
            wgmma6_rs_n64_t0(at.s, at.q[4], at.q[5], at.q[6], at.q[7], (DK) + 32, 1);                              \
            wg_commit();                                                                                           \
            GEMM_CODE;                                                                                             \
            wg_commit();                                                                                           \
            const uint32_t rdy = mbar_test(NB, NPH);                                                               \
            wg_wait<1>();                                                                                          \
            fence_regs(at.s); fence_regs(at.p);                                                                    \
            if (tid < 2) asm volatile("mbarrier.arrive.shared::cluster.b64 _, [%0];" ::"r"(REL) : "memory");       \
            EXPS();                                                                                                \
            mbar_wait_unless(rdy, NB, NPH);                                                                        \
        } while (0)
#define FUSED_PAIR(HIA, LOA, LOB, STEP0, GEMM) do {                                                                \
            const uint64_t dv0 = mkdesc<HI_V>(pd + dlo(OFF_KV + 256, 640));                                        \
            const uint64_t dv1 = mkdesc<HI_V>(sd + dlo(OFF_KV + 256, 640));                                        \
            const uint64_t dk = mkdesc<HI_K>(sd + dlo(OFF_KV, 0));                                                 \
            const uint64_t da = mkdesc<HIA>(sd + (LOA)), db = mkdesc<HI_W>(sd + (LOB));                            \
            STEP0(dv0, dk, fb + 8, ph, rel, GEMM(da, db, first));                                                  \
            const uint32_t r1 = fb + rel_off;                                                                      \
            rel = r1 + 8;                                                                                          \
            pd = sd + (SLOT >> 4); pb = fb + 8;                                                                    \
            if (fb == bar_full + (NSTAGE - 2) * 8) { fb = bar_full; ph ^= 1; } else fb += 16;                      \
            sd = (sd == sbd + (NSTAGE - 2) * (SLOT >> 4)) ? sbd : sd + 2 * (SLOT >> 4);                            \
            FUSED_STEP(dv1, dk + (SLOT >> 4), fb, ph, r1, GEMM(da + (SLOT >> 4), db + (SLOT >> 4), 1));            \
            first = 1;                                                                                             \
        } while (0)
#define GEMM_256(A, B, SC) do { wgmma6_ss_n256_t1(acc, A, B, SC); wgmma6_ss_n256_t1(acc, (A) + 2, (B) + 128, 1); } while (0)
#define GEMM_80(A, B, SC) do { wgmma6_ss_n80_t1(keep, A, B, SC); wgmma6_ss_n80_t1(keep, (A) + 256, (B) + 128, 1); wgmma6_ss_n80_t1(keep, (A) + 512, (B) + 256, 1); } while (0)
#define GEMM_144(A, B, SC) do { wgmma6_ss_n144_t1(ah, A, B, SC); wgmma6_ss_n144_t1(ah, (A) + 256, (B) + 128, 1); wgmma6_ss_n144_t1(ah, (A) + 512, (B) + 256, 1); } while (0)
#define NORM_ITEM(item) do {                                                                                       \
            if (norm_o(ow, at.o, lane, gaddr)) {                                                                   \
                attn_true_max(at.o, at.q, g_kv + (size_t)(j * 4 + (item)) * HEAD_BYTES + lane * 4);                \
                norm_o(ow, at.o, lane, gaddr);                                                                     \
            }                                                                                                      \
        } while (0)
#define STORE_ITEM(item) do { uint32_t ow[6]; NORM_ITEM(item); PUT_ITEM(item); } while (0)
#define PUT_ITEM(item) do {                                                                                        \
            uint8_t* op = a2w + (288 + ((item) * 4 + (j >> 1)) * 3) * 4096 + (j & 1) * 4224;                       \
            const int step = (j & 1) ? 3968 : 128;                                                                 \
            stg32(op, ow[0]);        stg32(op + 256, ow[1]);                                                       \
            stg32(op + step, ow[2]); stg32(op + step + 256, ow[3]);                                                \
            stg32(op + 4096, ow[4]); stg32(op + 4096 + 256, ow[5]);                                                \
        } while (0)
#define ITEM_STEP(DV, DK, NB, NPH, REL, GEMM_CODE) do {                                                            \
            uint32_t qo[8];                                                                                        \
            _Pragma("unroll") for (int i = 0; i < 6; i++) asm volatile("mov.b32 %0, %1;" : "=r"(qo[i]) : "r"(at.q[i])); \
            load_q(at.q, qa + (item + 1) * 4608, lane);                                                            \
            fence_regs(at.q);                                                                                      \
            wg_fence();                                                                                            \
            wgmma6_rs_n24_t1(at.o, at.p[0], at.p[1], at.p[2], at.p[3], (DV), 1);                                   \
            wgmma6_rs_n24_t1(at.o, at.p[4], at.p[5], at.p[6], at.p[7], (DV) + 80, 1);                              \
            wgmma6_rs_n24_t1(at.o, at.p[8], at.p[9], at.p[10], at.p[11], (DV) + 160, 1);                           \
            wgmma6_rs_n24_t1(at.o, at.p[12], at.p[13], at.p[14], at.p[15], (DV) + 240, 1);                         \
            wgmma6_rs_n64_t0(at.s, at.q[0], at.q[1], at.q[2], at.q[3], (DK) + dlo(0, 128), 0);                     \
            wgmma6_rs_n64_t0(at.s, at.q[4], at.q[5], at.q[6], at.q[7], (DK) + 32, 1);                              \
            wg_commit();                                                                                           \
            GEMM_CODE;                                                                                             \
            wg_commit();                                                                                           \
            const uint32_t rdy = mbar_test(NB, NPH);                                                               \
            wg_wait<1>();                                                                                          \
            fence_regs(at.o); fence_regs(at.p); fence_regs(at.s);                                                  \
            if (tid < 2) asm volatile("mbarrier.arrive.shared::cluster.b64 _, [%0];" ::"r"(REL) : "memory");       \
            uint32_t ow[6];                                                                                        \
            const bool bad = norm_o(ow, at.o, lane, gaddr);                                                        \
            EXPS();                                                                                                \
            if (bad) {                                                                                             \
                attn_true_max(at.o, qo, g_kv + (size_t)(j * 4 + (item)) * HEAD_BYTES + lane * 4);                  \
                norm_o(ow, at.o, lane, gaddr);                                                                     \
            }                                                                                                      \
            PUT_ITEM(item);                                                                                        \
            _Pragma("unroll") for (int i = 0; i < 12; i++) at.o[i] = 0.f;                                          \
            fence_regs(at.o);                                                                                      \
            mbar_wait_unless(rdy, NB, NPH);                                                                        \
        } while (0)
#define H2(i) pack(geglu2(acc[i], acc[64 + (i)]), geglu2(acc[(i) + 1], acc[65 + (i)]))
        float keep[40];
        float4 px[3];
        {
            float ah[72];
            int first = 1;
            {
#pragma unroll 1
                for (int t = 0; t < 5; t++) {
                    int n = 0x26988 >> (t * 4) & 15;
#pragma unroll 1
                    do { FUSED_PAIR(HI_X, wg * 256 + dlo(OFF_AX, 16), dlo(0, 4096), FUSED_STEP, GEMM_256); } while (--n);
                    if (t & 1) {
                        const int item = t >> 1;
                        mbar_wait(t == 1 ? bar_gate : bar_rdy + 2 * 8, 0);
                        FUSED_PAIR(HI_X, wg * 256 + dlo(OFF_AX, 16), dlo(0, 4096), ITEM_STEP, GEMM_256);
                    }
                    if (t < 3) {
                        mbar_wait(t > 0 ? bar_rdy + (t - 1) * 8 : bar_free + wg * 8, 0);
                        wg_wait<0>();
                        fence_regs(acc);
                        first = 0;
                        const uint32_t ha = sb + wg * 3 * SLOT + OFF_GAP + wq * 512 + lane * 16;
#pragma unroll
                        for (int k = 0; k < 8; k++) stsm4(ha + (k / 3) * SLOT + (k % 3) * 2048, H2(8 * k), H2(8 * k + 4), H2(8 * k + 2), H2(8 * k + 6));
                        fence_async_shared();
                        undef_regs(acc);
                        signal(t);
                    }
                }
                wg_wait<0>();
                fence_regs(acc);
                first = 0;
                uint8_t* hp = a2w + (j * 36 + 24) * 4096;
#pragma unroll
                for (int b = 0; b < 2; b++)
                    if (cta != 1000 + b) {
#pragma unroll
                        for (int k = b * 4; k < b * 4 + 4; k++) {
                            stg32(hp + k * 4096, H2(8 * k));           stg32(hp + k * 4096 + 256, H2(8 * k + 2));
                            stg32(hp + k * 4096 + 128, H2(8 * k + 4)); stg32(hp + k * 4096 + 384, H2(8 * k + 6));
                        }
                    }
                signal(3);
            }
#pragma unroll 1
            for (int seg = 0; seg < 3; seg++) {
                int n = 0x2AD >> (seg * 4) & 15;
#pragma unroll 1
                do { FUSED_PAIR(HI_A2, wg * 128 + dlo(OFF_A2, 128), dlo(0, 6144), FUSED_STEP, GEMM_144); } while (--n);
                if (seg == 0) {
                    constexpr int item = 2;
                    FUSED_PAIR(HI_A2, wg * 128 + dlo(OFF_A2, 128), dlo(0, 6144), ITEM_STEP, GEMM_144);
                    signal(5);
                } else if (seg == 1) {
                    wg_wait<0>();
                    fence_regs(ah);
                    const float w0 = 0.5f - 0.5f * __uint_as_float(lds32(gaddr)), w1 = 0.5f - 0.5f * __uint_as_float(lds32(gaddr + 32));
#pragma unroll
                    for (int i = 0; i < 72; i++) ah[i] *= (i & 2) ? w1 : w0;
                    fence_regs(ah);
                }
            }
            wg_wait<0>();
            fence_regs(ah);
            mbar_wait(bar_px, 0);
#pragma unroll
            for (int i = 0; i < 3; i++) px[i] = __ldcg(g_px + (size_t)(cta * 2 + wg) * 3 * 128 + tid + i * 128);
            uint4* mine = g_part + (size_t)(cta * 2 + wg) * 5 * 128 + tid;
#pragma unroll
            for (int i = 0; i < 5; i++) {
                const float* v = &ah[32 + 8 * i];
                __stcg(mine + i * 128, make_uint4(pack(v[0], v[1]), pack(v[2], v[3]), pack(v[4], v[5]), pack(v[6], v[7])));
            }
#pragma unroll
            for (int i = 0; i < 40; i++) keep[i] = ah[i < 32 ? i : 32 + i] + __uint_as_float(at.q[6]);
            signal(6);
            fence_regs(keep);
        }
        {
            int first = 1;
            FUSED_PAIR(HI_A2, wg * 128 + dlo(OFF_A2, 128), dlo(0, 6144), FUSED_STEP, GEMM_80);
        }
        wg_fence();
        ISSUE_PV();
        wg_commit();
        wg_wait<0>();
        fence_regs(at.o); fence_regs(at.p); fence_regs(at.q);
#pragma unroll
        for (int i = 0; i < 3; i++) { at.o[4 * i] += px[i].x; at.o[4 * i + 1] += px[i].y; at.o[4 * i + 2] += px[i].z; at.o[4 * i + 3] += px[i].w; }
        STORE_ITEM(3);
        signal(7);
        fence_regs(keep);
#pragma unroll 1
        for (int kk = 0; kk < 2; kk++) {
            mbar_wait(fb, ph);
            const uint64_t da = mkdesc<HI_A2>(sd + wg * 128 + dlo(OFF_A2, 128)), db = mkdesc<HI_W>(sd + dlo(0, 6144));
            wg_fence();
            GEMM_80(da, db, 1);
            wg_commit();
            wg_wait<1>();
            if (kk < 1) release();
            STAGE_NEXT;
        }
        {
            mbar_wait(bar_rdy + 6 * 8, 0);
            const uint4* theirs = g_part + (size_t)((cta ^ 8) * 2 + wg) * 5 * 128 + tid;
            uint4 pv[5];
#pragma unroll
            for (int i = 0; i < 5; i++) pv[i] = __ldcg(theirs + i * 128);
            wg_wait<0>();
            fence_regs(keep);
#pragma unroll
            for (int i = 0; i < 5; i++) {
                const uint32_t u[4] = {pv[i].x, pv[i].y, pv[i].z, pv[i].w};
#pragma unroll
                for (int e = 0; e < 4; e++) { keep[8 * i + 2 * e] += __uint_as_float(u[e] << 16); keep[8 * i + 2 * e + 1] += __uint_as_float(u[e] & 0xffff0000u); }
            }
            fence_regs(keep);
        }
        const uint32_t tb = sb + (warp >> 1) * SLOT + OFF_KV + (warp & 1) * 2560;
        const uint32_t trow = ((lane >> 3) & 1) * 8 + (lane & 7);
        uint8_t* op = (uint8_t*)(out + (size_t)(m * 128 + grp * 8) * DM);
        uint8_t* o1 = op + (lane >> 3) * (DM * 2) + nt * 256 + hf * 128 + (lane & 7) * 16;
        uint8_t* o2 = op + (lane >> 1) * (DM * 2) + 1024 + nt * 32 + (lane & 1) * 16;
        mbar_wait(bar_late, 0);
#pragma unroll 1
        for (int k = 2; k < 6; k++) {
            mbar_wait(bar_full + k * 8, 0);
            const uint32_t bo = __shfl_sync(0xffffffffu, lds32(s_order + k * 4), 0);
            const uint64_t da = mkdesc<HI_A2>(sbd + k * (SLOT >> 4) + wg * 128 + dlo(OFF_A2, 128)), db = mkdesc<HI_W>(sbd + bo + dlo(0, 6144));
            wg_fence();
            GEMM_80(da, db, 1);
            wg_commit();
        }
        asm volatile("barrier.cluster.arrive.relaxed.aligned;" ::: "memory");
        wg_wait<0>();
        fence_regs(keep);
#pragma unroll
        for (int i = 0; i < 5; i++) {
            const uint32_t a = i < 4 ? tb + trow * 128 + (((2 * i + (lane >> 4)) ^ (lane & 7)) << 4) : tb + 2048 + trow * 32 + (lane >> 4) * 16;
            stsm4(a, pack(keep[8 * i], keep[8 * i + 1]), pack(keep[8 * i + 2], keep[8 * i + 3]), pack(keep[8 * i + 4], keep[8 * i + 5]), pack(keep[8 * i + 6], keep[8 * i + 7]));
        }
        __syncwarp();
        uint4 v[5];
#pragma unroll
        for (int i = 0; i < 5; i++) {
            const uint32_t r = 4 * i + (lane >> 3);
            const uint32_t a = i < 4 ? tb + r * 128 + (((lane & 7) ^ (r & 7)) << 4) : tb + 2048 + lane * 16;
            asm volatile("ld.shared.v4.u32 {%0, %1, %2, %3}, [%4];" : "=r"(v[i].x), "=r"(v[i].y), "=r"(v[i].z), "=r"(v[i].w) : "r"(a) : "memory");
        }
#pragma unroll
        for (int i = 0; i < 5; i++)
            asm volatile("{\n.reg .pred p;\nsetp.ne.s32 p, %5, 0;\n@p st.global.v4.u32 [%0], {%1, %2, %3, %4};\n}"
                         ::"l"(i < 4 ? o1 + i * 4 * (DM * 2) : o2), "r"(v[i].x), "r"(v[i].y), "r"(v[i].z), "r"(v[i].w), "r"(i < 4 ? 1 : (int)(wg == hf)) : "memory");
        asm volatile("barrier.cluster.wait.aligned;" ::: "memory");
    }
}

typedef CUresult (*EncodeFn)(CUtensorMap*, CUtensorMapDataType, cuuint32_t, void*, const cuuint64_t*, const cuuint64_t*,
                             const cuuint32_t*, const cuuint32_t*, CUtensorMapInterleave, CUtensorMapSwizzle,
                             CUtensorMapL2promotion, CUtensorMapFloatOOBfill);

CUtensorMap make_map(EncodeFn enc, const void* ptr, uint64_t inner, uint64_t outer, uint32_t box_inner, uint32_t box_outer, CUtensorMapSwizzle swz) {
    CUtensorMap t;
    cuuint64_t dims[2] = {inner, outer};
    cuuint64_t strides[1] = {inner * 2};
    cuuint32_t box[2] = {box_inner, box_outer};
    cuuint32_t es[2] = {1, 1};
    enc(&t, CU_TENSOR_MAP_DATA_TYPE_BFLOAT16, 2, const_cast<void*>(ptr), dims, strides, box, es, CU_TENSOR_MAP_INTERLEAVE_NONE, swz,
        CU_TENSOR_MAP_L2_PROMOTION_L2_128B, CU_TENSOR_MAP_FLOAT_OOB_FILL_NONE);
    return t;
}

CUtensorMap make_qkv_map(EncodeFn enc, const void* ptr, uint32_t width, CUtensorMapSwizzle swz) {
    CUtensorMap t;
    cuuint64_t dims[3] = {DM, DM, 3};
    cuuint64_t strides[2] = {3 * DM * 2, DM * 2};
    cuuint32_t box[3] = {width, 16, 3};
    cuuint32_t es[3] = {1, 1, 1};
    enc(&t, CU_TENSOR_MAP_DATA_TYPE_BFLOAT16, 3, const_cast<void*>(ptr), dims, strides, box, es, CU_TENSOR_MAP_INTERLEAVE_NONE, swz,
        CU_TENSOR_MAP_L2_PROMOTION_L2_128B, CU_TENSOR_MAP_FLOAT_OOB_FILL_NONE);
    return t;
}

}

extern "C" void kernel_launch(void* const* d_in, const int* in_sizes, int n_in, void* d_out, int out_size) {
    (void)in_sizes; (void)n_in; (void)out_size;
    void* fn = nullptr;
    cudaDriverEntryPointQueryResult qr;
    cudaGetDriverEntryPoint("cuTensorMapEncodeTiled", &fn, cudaEnableDefault, &qr);
    EncodeFn enc = (EncodeFn)fn;
    const CUtensorMap tm_x = make_map(enc, d_in[0], DM, SEQ, 32, 128, CU_TENSOR_MAP_SWIZZLE_64B);
    const CUtensorMap tm_qkv = make_qkv_map(enc, d_in[1], 64, CU_TENSOR_MAP_SWIZZLE_128B);
    const CUtensorMap tm_qkv8 = make_qkv_map(enc, d_in[1], 8, CU_TENSOR_MAP_SWIZZLE_NONE);
    const CUtensorMap tm_wo = make_map(enc, d_in[2], DM, DM, 64, 24, CU_TENSOR_MAP_SWIZZLE_128B);
    const CUtensorMap tm_wg = make_map(enc, d_in[4], FF, DM, 64, 32, CU_TENSOR_MAP_SWIZZLE_128B);
    const CUtensorMap tm_wu = make_map(enc, d_in[5], FF, DM, 64, 32, CU_TENSOR_MAP_SWIZZLE_128B);
    const CUtensorMap tm_wd = make_map(enc, d_in[6], DM, FF, 64, 24, CU_TENSOR_MAP_SWIZZLE_128B);
    const CUtensorMap tm_wd16 = make_map(enc, d_in[6], DM, FF, 16, 24, CU_TENSOR_MAP_SWIZZLE_128B);
    const CUtensorMap tm_wo16 = make_map(enc, d_in[2], DM, DM, 16, 24, CU_TENSOR_MAP_SWIZZLE_128B);
    cudaFuncSetAttribute(fused_kernel, cudaFuncAttributeMaxDynamicSharedMemorySize, SMEM_BYTES);
    fused_kernel<<<NCTA + 4, 384, SMEM_BYTES>>>((__nv_bfloat16*)d_out, (const __nv_bfloat16*)d_in[0], (const __nv_bfloat16*)d_in[7],
                                               tm_x, tm_qkv, tm_qkv8, tm_wg, tm_wu, tm_wd, tm_wo, tm_wd16, tm_wo16);
}
```

```cpp
#include <cuda_runtime.h>
#include <cuda.h>
#include <cuda_bf16.h>
#include <stdint.h>

#define PROFILE 0
#define DOTRACE 0

#define HID 1
namespace {

constexpr int SEQ = 2048, DM = 576, FF = 4608;
constexpr int NCTA = 128;
constexpr int NSTAGE = 6;
constexpr int E0 = 2;
constexpr int DEFER = 2;
constexpr int SLOT = 35 * 1024;
constexpr int OFF_AX = 22528;
constexpr int OFF_A2 = 18432;
constexpr int OFF_TL = 20480;
constexpr int OFF_GAP = 16384;
constexpr int OFF_KV = 30720;
constexpr int OFF_Q = NSTAGE * SLOT - 4608;
constexpr int OFF_BAR = NSTAGE * SLOT + 3 * 4608;
constexpr int SMEM_BYTES = OFF_BAR + 1024 + 1024;

constexpr int STRIPB = 48 * 32;
constexpr int HEAD_BYTES = 256 * 640;
constexpr int A2_TILE = 336 * 4096;

constexpr int FL_KV = 0;
constexpr int FL_M = FL_KV + 8 * 32;
constexpr int FM_H = 0;
constexpr int FM_LATE = 7;
constexpr int FM_R = 16;
constexpr int FL_G = FL_M + 16 * 64;
constexpr int FL_E = FL_G + 4 * 32;
constexpr int FL_N = FL_E + (NCTA + 4) * 32;

__device__ __align__(1024) uint8_t g_kv[32 * HEAD_BYTES];
__device__ __align__(1024) uint8_t g_a2[16 * A2_TILE];
__device__ __align__(1024) uint4 g_part[NCTA * 2 * 5 * 128];
__device__ __align__(1024) uint8_t g_q3[NCTA * 4608];
__device__ __align__(1024) float4 g_px[NCTA * 2 * 3 * 128];
__device__ float g_gate[SEQ];
__device__ __align__(256) uint32_t g_flags[FL_N];

template <uint32_t BHI>
__device__ __forceinline__ void wgmma_rs_n24_t1(float (&d)[12], uint32_t a0, uint32_t a1, uint32_t a2, uint32_t a3, uint32_t db, int scale_d) {
  asm volatile("{\n.reg .pred p;\n.reg .b64 da, db;\n"
    "mov.b64 db, {%16, %18};\n"
    "setp.ne.b32 p, %17, 0;\n"
    "wgmma.mma_async.sync.aligned.m64n24k16.f32.bf16.bf16 "
    "{%0, %1, %2, %3, %4, %5, %6, %7, %8, %9, %10, %11}, "
    "{%12, %13, %14, %15}, db, p, 1, 1, 1;\n}\n"
    : "+f"(d[0]), "+f"(d[1]), "+f"(d[2]), "+f"(d[3]), "+f"(d[4]), "+f"(d[5]), "+f"(d[6]), "+f"(d[7]),
      "+f"(d[8]), "+f"(d[9]), "+f"(d[10]), "+f"(d[11])
    : "r"(a0), "r"(a1), "r"(a2), "r"(a3), "r"(db), "r"(scale_d), "n"(BHI));
}
template <uint32_t BHI>
__device__ __forceinline__ void wgmma_rs_n128_t0(float (&d)[64], uint32_t a0, uint32_t a1, uint32_t a2, uint32_t a3, uint32_t db, int scale_d) {
  asm volatile("{\n.reg .pred p;\n.reg .b64 da, db;\n"
    "mov.b64 db, {%68, %70};\n"
    "setp.ne.b32 p, %69, 0;\n"
    "wgmma.mma_async.sync.aligned.m64n128k16.f32.bf16.bf16 "
    "{%0, %1, %2, %3, %4, %5, %6, %7, %8, %9, %10, %11, %12, %13, %14, %15, "
    "%16, %17, %18, %19, %20, %21, %22, %23, %24, %25, %26, %27, %28, %29, %30, %31, "
    "%32, %33, %34, %35, %36, %37, %38, %39, %40, %41, %42, %43, %44, %45, %46, %47, "
    "%48, %49, %50, %51, %52, %53, %54, %55, %56, %57, %58, %59, %60, %61, %62, %63}, "
    "{%64, %65, %66, %67}, db, p, 1, 1, 0;\n}\n"
    : "+f"(d[0]), "+f"(d[1]), "+f"(d[2]), "+f"(d[3]), "+f"(d[4]), "+f"(d[5]), "+f"(d[6]), "+f"(d[7]),
      "+f"(d[8]), "+f"(d[9]), "+f"(d[10]), "+f"(d[11]), "+f"(d[12]), "+f"(d[13]), "+f"(d[14]), "+f"(d[15]),
      "+f"(d[16]), "+f"(d[17]), "+f"(d[18]), "+f"(d[19]), "+f"(d[20]), "+f"(d[21]), "+f"(d[22]), "+f"(d[23]),
      "+f"(d[24]), "+f"(d[25]), "+f"(d[26]), "+f"(d[27]), "+f"(d[28]), "+f"(d[29]), "+f"(d[30]), "+f"(d[31]),
      "+f"(d[32]), "+f"(d[33]), "+f"(d[34]), "+f"(d[35]), "+f"(d[36]), "+f"(d[37]), "+f"(d[38]), "+f"(d[39]),
      "+f"(d[40]), "+f"(d[41]), "+f"(d[42]), "+f"(d[43]), "+f"(d[44]), "+f"(d[45]), "+f"(d[46]), "+f"(d[47]),
      "+f"(d[48]), "+f"(d[49]), "+f"(d[50]), "+f"(d[51]), "+f"(d[52]), "+f"(d[53]), "+f"(d[54]), "+f"(d[55]),
      "+f"(d[56]), "+f"(d[57]), "+f"(d[58]), "+f"(d[59]), "+f"(d[60]), "+f"(d[61]), "+f"(d[62]), "+f"(d[63])
    : "r"(a0), "r"(a1), "r"(a2), "r"(a3), "r"(db), "r"(scale_d), "n"(BHI));
}
template <uint32_t BHI>
__device__ __forceinline__ void wgmma_rs_n128_t1(float (&d)[64], uint32_t a0, uint32_t a1, uint32_t a2, uint32_t a3, uint32_t db, int scale_d) {
  asm volatile("{\n.reg .pred p;\n.reg .b64 da, db;\n"
    "mov.b64 db, {%68, %70};\n"
    "setp.ne.b32 p, %69, 0;\n"
    "wgmma.mma_async.sync.aligned.m64n128k16.f32.bf16.bf16 "
    "{%0, %1, %2, %3, %4, %5, %6, %7, %8, %9, %10, %11, %12, %13, %14, %15, "
    "%16, %17, %18, %19, %20, %21, %22, %23, %24, %25, %26, %27, %28, %29, %30, %31, "
    "%32, %33, %34, %35, %36, %37, %38, %39, %40, %41, %42, %43, %44, %45, %46, %47, "
    "%48, %49, %50, %51, %52, %53, %54, %55, %56, %57, %58, %59, %60, %61, %62, %63}, "
    "{%64, %65, %66, %67}, db, p, 1, 1, 1;\n}\n"
    : "+f"(d[0]), "+f"(d[1]), "+f"(d[2]), "+f"(d[3]), "+f"(d[4]), "+f"(d[5]), "+f"(d[6]), "+f"(d[7]),
      "+f"(d[8]), "+f"(d[9]), "+f"(d[10]), "+f"(d[11]), "+f"(d[12]), "+f"(d[13]), "+f"(d[14]), "+f"(d[15]),
      "+f"(d[16]), "+f"(d[17]), "+f"(d[18]), "+f"(d[19]), "+f"(d[20]), "+f"(d[21]), "+f"(d[22]), "+f"(d[23]),
      "+f"(d[24]), "+f"(d[25]), "+f"(d[26]), "+f"(d[27]), "+f"(d[28]), "+f"(d[29]), "+f"(d[30]), "+f"(d[31]),
      "+f"(d[32]), "+f"(d[33]), "+f"(d[34]), "+f"(d[35]), "+f"(d[36]), "+f"(d[37]), "+f"(d[38]), "+f"(d[39]),
      "+f"(d[40]), "+f"(d[41]), "+f"(d[42]), "+f"(d[43]), "+f"(d[44]), "+f"(d[45]), "+f"(d[46]), "+f"(d[47]),
      "+f"(d[48]), "+f"(d[49]), "+f"(d[50]), "+f"(d[51]), "+f"(d[52]), "+f"(d[53]), "+f"(d[54]), "+f"(d[55]),
      "+f"(d[56]), "+f"(d[57]), "+f"(d[58]), "+f"(d[59]), "+f"(d[60]), "+f"(d[61]), "+f"(d[62]), "+f"(d[63])
    : "r"(a0), "r"(a1), "r"(a2), "r"(a3), "r"(db), "r"(scale_d), "n"(BHI));
}
template <uint32_t BHI>
__device__ __forceinline__ void wgmma_rs_n192_t1(float (&d)[96], uint32_t a0, uint32_t a1, uint32_t a2, uint32_t a3, uint32_t db, int scale_d) {
  asm volatile("{\n.reg .pred p;\n.reg .b64 da, db;\n"
    "mov.b64 db, {%100, %102};\n"
    "setp.ne.b32 p, %101, 0;\n"
    "wgmma.mma_async.sync.aligned.m64n192k16.f32.bf16.bf16 "
    "{%0, %1, %2, %3, %4, %5, %6, %7, %8, %9, %10, %11, %12, %13, %14, %15, "
    "%16, %17, %18, %19, %20, %21, %22, %23, %24, %25, %26, %27, %28, %29, %30, %31, "
    "%32, %33, %34, %35, %36, %37, %38, %39, %40, %41, %42, %43, %44, %45, %46, %47, "
    "%48, %49, %50, %51, %52, %53, %54, %55, %56, %57, %58, %59, %60, %61, %62, %63, "
    "%64, %65, %66, %67, %68, %69, %70, %71, %72, %73, %74, %75, %76, %77, %78, %79, "
    "%80, %81, %82, %83, %84, %85, %86, %87, %88, %89, %90, %91, %92, %93, %94, %95}, "
    "{%96, %97, %98, %99}, db, p, 1, 1, 1;\n}\n"
    : "+f"(d[0]), "+f"(d[1]), "+f"(d[2]), "+f"(d[3]), "+f"(d[4]), "+f"(d[5]), "+f"(d[6]), "+f"(d[7]),
      "+f"(d[8]), "+f"(d[9]), "+f"(d[10]), "+f"(d[11]), "+f"(d[12]), "+f"(d[13]), "+f"(d[14]), "+f"(d[15]),
      "+f"(d[16]), "+f"(d[17]), "+f"(d[18]), "+f"(d[19]), "+f"(d[20]), "+f"(d[21]), "+f"(d[22]), "+f"(d[23]),
      "+f"(d[24]), "+f"(d[25]), "+f"(d[26]), "+f"(d[27]), "+f"(d[28]), "+f"(d[29]), "+f"(d[30]), "+f"(d[31]),
      "+f"(d[32]), "+f"(d[33]), "+f"(d[34]), "+f"(d[35]), "+f"(d[36]), "+f"(d[37]), "+f"(d[38]), "+f"(d[39]),
      "+f"(d[40]), "+f"(d[41]), "+f"(d[42]), "+f"(d[43]), "+f"(d[44]), "+f"(d[45]), "+f"(d[46]), "+f"(d[47]),
      "+f"(d[48]), "+f"(d[49]), "+f"(d[50]), "+f"(d[51]), "+f"(d[52]), "+f"(d[53]), "+f"(d[54]), "+f"(d[55]),
      "+f"(d[56]), "+f"(d[57]), "+f"(d[58]), "+f"(d[59]), "+f"(d[60]), "+f"(d[61]), "+f"(d[62]), "+f"(d[63]),
      "+f"(d[64]), "+f"(d[65]), "+f"(d[66]), "+f"(d[67]), "+f"(d[68]), "+f"(d[69]), "+f"(d[70]), "+f"(d[71]),
      "+f"(d[72]), "+f"(d[73]), "+f"(d[74]), "+f"(d[75]), "+f"(d[76]), "+f"(d[77]), "+f"(d[78]), "+f"(d[79]),
      "+f"(d[80]), "+f"(d[81]), "+f"(d[82]), "+f"(d[83]), "+f"(d[84]), "+f"(d[85]), "+f"(d[86]), "+f"(d[87]),
      "+f"(d[88]), "+f"(d[89]), "+f"(d[90]), "+f"(d[91]), "+f"(d[92]), "+f"(d[93]), "+f"(d[94]), "+f"(d[95])
    : "r"(a0), "r"(a1), "r"(a2), "r"(a3), "r"(db), "r"(scale_d), "n"(BHI));
}
template <uint32_t AHI, uint32_t BHI>
__device__ __forceinline__ void wgmma_ss_n24_t1(float (&d)[12], uint32_t da, uint32_t db, int scale_d) {
  asm volatile("{\n.reg .pred p;\n.reg .b64 da, db;\n"
    "mov.b64 da, {%12, %15};\nmov.b64 db, {%13, %16};\n"
    "setp.ne.b32 p, %14, 0;\n"
    "wgmma.mma_async.sync.aligned.m64n24k16.f32.bf16.bf16 "
    "{%0, %1, %2, %3, %4, %5, %6, %7, %8, %9, %10, %11}, "
    "da, db, p, 1, 1, 0, 1;\n}\n"
    : "+f"(d[0]), "+f"(d[1]), "+f"(d[2]), "+f"(d[3]), "+f"(d[4]), "+f"(d[5]), "+f"(d[6]), "+f"(d[7]),
      "+f"(d[8]), "+f"(d[9]), "+f"(d[10]), "+f"(d[11])
    : "r"(da), "r"(db), "r"(scale_d), "n"(AHI), "n"(BHI));
}
template <uint32_t AHI, uint32_t BHI>
__device__ __forceinline__ void wgmma_ss_n128_t1(float (&d)[64], uint32_t da, uint32_t db, int scale_d) {
  asm volatile("{\n.reg .pred p;\n.reg .b64 da, db;\n"
    "mov.b64 da, {%64, %67};\nmov.b64 db, {%65, %68};\n"
    "setp.ne.b32 p, %66, 0;\n"
    "wgmma.mma_async.sync.aligned.m64n128k16.f32.bf16.bf16 "
    "{%0, %1, %2, %3, %4, %5, %6, %7, %8, %9, %10, %11, %12, %13, %14, %15, "
    "%16, %17, %18, %19, %20, %21, %22, %23, %24, %25, %26, %27, %28, %29, %30, %31, "
    "%32, %33, %34, %35, %36, %37, %38, %39, %40, %41, %42, %43, %44, %45, %46, %47, "
    "%48, %49, %50, %51, %52, %53, %54, %55, %56, %57, %58, %59, %60, %61, %62, %63}, "
    "da, db, p, 1, 1, 0, 1;\n}\n"
    : "+f"(d[0]), "+f"(d[1]), "+f"(d[2]), "+f"(d[3]), "+f"(d[4]), "+f"(d[5]), "+f"(d[6]), "+f"(d[7]),
      "+f"(d[8]), "+f"(d[9]), "+f"(d[10]), "+f"(d[11]), "+f"(d[12]), "+f"(d[13]), "+f"(d[14]), "+f"(d[15]),
      "+f"(d[16]), "+f"(d[17]), "+f"(d[18]), "+f"(d[19]), "+f"(d[20]), "+f"(d[21]), "+f"(d[22]), "+f"(d[23]),
      "+f"(d[24]), "+f"(d[25]), "+f"(d[26]), "+f"(d[27]), "+f"(d[28]), "+f"(d[29]), "+f"(d[30]), "+f"(d[31]),
      "+f"(d[32]), "+f"(d[33]), "+f"(d[34]), "+f"(d[35]), "+f"(d[36]), "+f"(d[37]), "+f"(d[38]), "+f"(d[39]),
      "+f"(d[40]), "+f"(d[41]), "+f"(d[42]), "+f"(d[43]), "+f"(d[44]), "+f"(d[45]), "+f"(d[46]), "+f"(d[47]),
      "+f"(d[48]), "+f"(d[49]), "+f"(d[50]), "+f"(d[51]), "+f"(d[52]), "+f"(d[53]), "+f"(d[54]), "+f"(d[55]),
      "+f"(d[56]), "+f"(d[57]), "+f"(d[58]), "+f"(d[59]), "+f"(d[60]), "+f"(d[61]), "+f"(d[62]), "+f"(d[63])
    : "r"(da), "r"(db), "r"(scale_d), "n"(AHI), "n"(BHI));
}
template <uint32_t AHI, uint32_t BHI>
__device__ __forceinline__ void wgmma_ss_n192_t1(float (&d)[96], uint32_t da, uint32_t db, int scale_d) {
  asm volatile("{\n.reg .pred p;\n.reg .b64 da, db;\n"
    "mov.b64 da, {%96, %99};\nmov.b64 db, {%97, %100};\n"
    "setp.ne.b32 p, %98, 0;\n"
    "wgmma.mma_async.sync.aligned.m64n192k16.f32.bf16.bf16 "
    "{%0, %1, %2, %3, %4, %5, %6, %7, %8, %9, %10, %11, %12, %13, %14, %15, "
    "%16, %17, %18, %19, %20, %21, %22, %23, %24, %25, %26, %27, %28, %29, %30, %31, "
    "%32, %33, %34, %35, %36, %37, %38, %39, %40, %41, %42, %43, %44, %45, %46, %47, "
    "%48, %49, %50, %51, %52, %53, %54, %55, %56, %57, %58, %59, %60, %61, %62, %63, "
    "%64, %65, %66, %67, %68, %69, %70, %71, %72, %73, %74, %75, %76, %77, %78, %79, "
    "%80, %81, %82, %83, %84, %85, %86, %87, %88, %89, %90, %91, %92, %93, %94, %95}, "
    "da, db, p, 1, 1, 0, 1;\n}\n"
    : "+f"(d[0]), "+f"(d[1]), "+f"(d[2]), "+f"(d[3]), "+f"(d[4]), "+f"(d[5]), "+f"(d[6]), "+f"(d[7]),
      "+f"(d[8]), "+f"(d[9]), "+f"(d[10]), "+f"(d[11]), "+f"(d[12]), "+f"(d[13]), "+f"(d[14]), "+f"(d[15]),
      "+f"(d[16]), "+f"(d[17]), "+f"(d[18]), "+f"(d[19]), "+f"(d[20]), "+f"(d[21]), "+f"(d[22]), "+f"(d[23]),
      "+f"(d[24]), "+f"(d[25]), "+f"(d[26]), "+f"(d[27]), "+f"(d[28]), "+f"(d[29]), "+f"(d[30]), "+f"(d[31]),
      "+f"(d[32]), "+f"(d[33]), "+f"(d[34]), "+f"(d[35]), "+f"(d[36]), "+f"(d[37]), "+f"(d[38]), "+f"(d[39]),
      "+f"(d[40]), "+f"(d[41]), "+f"(d[42]), "+f"(d[43]), "+f"(d[44]), "+f"(d[45]), "+f"(d[46]), "+f"(d[47]),
      "+f"(d[48]), "+f"(d[49]), "+f"(d[50]), "+f"(d[51]), "+f"(d[52]), "+f"(d[53]), "+f"(d[54]), "+f"(d[55]),
      "+f"(d[56]), "+f"(d[57]), "+f"(d[58]), "+f"(d[59]), "+f"(d[60]), "+f"(d[61]), "+f"(d[62]), "+f"(d[63]),
      "+f"(d[64]), "+f"(d[65]), "+f"(d[66]), "+f"(d[67]), "+f"(d[68]), "+f"(d[69]), "+f"(d[70]), "+f"(d[71]),
      "+f"(d[72]), "+f"(d[73]), "+f"(d[74]), "+f"(d[75]), "+f"(d[76]), "+f"(d[77]), "+f"(d[78]), "+f"(d[79]),
      "+f"(d[80]), "+f"(d[81]), "+f"(d[82]), "+f"(d[83]), "+f"(d[84]), "+f"(d[85]), "+f"(d[86]), "+f"(d[87]),
      "+f"(d[88]), "+f"(d[89]), "+f"(d[90]), "+f"(d[91]), "+f"(d[92]), "+f"(d[93]), "+f"(d[94]), "+f"(d[95])
    : "r"(da), "r"(db), "r"(scale_d), "n"(AHI), "n"(BHI));
}
template <uint32_t AHI, uint32_t BHI>
__device__ __forceinline__ void wgmma_ss_n256_t1(float (&d)[128], uint32_t da, uint32_t db, int scale_d) {
  asm volatile("{\n.reg .pred p;\n.reg .b64 da, db;\n"
    "mov.b64 da, {%128, %131};\nmov.b64 db, {%129, %132};\n"
    "setp.ne.b32 p, %130, 0;\n"
    "wgmma.mma_async.sync.aligned.m64n256k16.f32.bf16.bf16 "
    "{%0, %1, %2, %3, %4, %5, %6, %7, %8, %9, %10, %11, %12, %13, %14, %15, "
    "%16, %17, %18, %19, %20, %21, %22, %23, %24, %25, %26, %27, %28, %29, %30, %31, "
    "%32, %33, %34, %35, %36, %37, %38, %39, %40, %41, %42, %43, %44, %45, %46, %47, "
    "%48, %49, %50, %51, %52, %53, %54, %55, %56, %57, %58, %59, %60, %61, %62, %63, "
    "%64, %65, %66, %67, %68, %69, %70, %71, %72, %73, %74, %75, %76, %77, %78, %79, "
    "%80, %81, %82, %83, %84, %85, %86, %87, %88, %89, %90, %91, %92, %93, %94, %95, "
    "%96, %97, %98, %99, %100, %101, %102, %103, %104, %105, %106, %107, %108, %109, %110, %111, "
    "%112, %113, %114, %115, %116, %117, %118, %119, %120, %121, %122, %123, %124, %125, %126, %127}, "
    "da, db, p, 1, 1, 0, 1;\n}\n"
    : "+f"(d[0]), "+f"(d[1]), "+f"(d[2]), "+f"(d[3]), "+f"(d[4]), "+f"(d[5]), "+f"(d[6]), "+f"(d[7]),
      "+f"(d[8]), "+f"(d[9]), "+f"(d[10]), "+f"(d[11]), "+f"(d[12]), "+f"(d[13]), "+f"(d[14]), "+f"(d[15]),
      "+f"(d[16]), "+f"(d[17]), "+f"(d[18]), "+f"(d[19]), "+f"(d[20]), "+f"(d[21]), "+f"(d[22]), "+f"(d[23]),
      "+f"(d[24]), "+f"(d[25]), "+f"(d[26]), "+f"(d[27]), "+f"(d[28]), "+f"(d[29]), "+f"(d[30]), "+f"(d[31]),
      "+f"(d[32]), "+f"(d[33]), "+f"(d[34]), "+f"(d[35]), "+f"(d[36]), "+f"(d[37]), "+f"(d[38]), "+f"(d[39]),
      "+f"(d[40]), "+f"(d[41]), "+f"(d[42]), "+f"(d[43]), "+f"(d[44]), "+f"(d[45]), "+f"(d[46]), "+f"(d[47]),
      "+f"(d[48]), "+f"(d[49]), "+f"(d[50]), "+f"(d[51]), "+f"(d[52]), "+f"(d[53]), "+f"(d[54]), "+f"(d[55]),
      "+f"(d[56]), "+f"(d[57]), "+f"(d[58]), "+f"(d[59]), "+f"(d[60]), "+f"(d[61]), "+f"(d[62]), "+f"(d[63]),
      "+f"(d[64]), "+f"(d[65]), "+f"(d[66]), "+f"(d[67]), "+f"(d[68]), "+f"(d[69]), "+f"(d[70]), "+f"(d[71]),
      "+f"(d[72]), "+f"(d[73]), "+f"(d[74]), "+f"(d[75]), "+f"(d[76]), "+f"(d[77]), "+f"(d[78]), "+f"(d[79]),
      "+f"(d[80]), "+f"(d[81]), "+f"(d[82]), "+f"(d[83]), "+f"(d[84]), "+f"(d[85]), "+f"(d[86]), "+f"(d[87]),
      "+f"(d[88]), "+f"(d[89]), "+f"(d[90]), "+f"(d[91]), "+f"(d[92]), "+f"(d[93]), "+f"(d[94]), "+f"(d[95]),
      "+f"(d[96]), "+f"(d[97]), "+f"(d[98]), "+f"(d[99]), "+f"(d[100]), "+f"(d[101]), "+f"(d[102]), "+f"(d[103]),
      "+f"(d[104]), "+f"(d[105]), "+f"(d[106]), "+f"(d[107]), "+f"(d[108]), "+f"(d[109]), "+f"(d[110]), "+f"(d[111]),
      "+f"(d[112]), "+f"(d[113]), "+f"(d[114]), "+f"(d[115]), "+f"(d[116]), "+f"(d[117]), "+f"(d[118]), "+f"(d[119]),
      "+f"(d[120]), "+f"(d[121]), "+f"(d[122]), "+f"(d[123]), "+f"(d[124]), "+f"(d[125]), "+f"(d[126]), "+f"(d[127])
    : "r"(da), "r"(db), "r"(scale_d), "n"(AHI), "n"(BHI));
}
__device__ __forceinline__ void wgmma6_rs_n24_t1(float (&d)[12], uint32_t a0, uint32_t a1, uint32_t a2, uint32_t a3, uint64_t db, int scale_d) {
  asm volatile("{\n.reg .pred p;\n"
    "setp.ne.b32 p, %17, 0;\n"
    "wgmma.mma_async.sync.aligned.m64n24k16.f32.bf16.bf16 "
    "{%0, %1, %2, %3, %4, %5, %6, %7, %8, %9, %10, %11}, "
    "{%12, %13, %14, %15}, %16, p, 1, 1, 1;\n}\n"
    : "+f"(d[0]), "+f"(d[1]), "+f"(d[2]), "+f"(d[3]), "+f"(d[4]), "+f"(d[5]), "+f"(d[6]), "+f"(d[7]),
      "+f"(d[8]), "+f"(d[9]), "+f"(d[10]), "+f"(d[11])
    : "r"(a0), "r"(a1), "r"(a2), "r"(a3), "l"(db), "r"(scale_d));
}
__device__ __forceinline__ void wgmma6_rs_n64_t0(float (&d)[32], uint32_t a0, uint32_t a1, uint32_t a2, uint32_t a3, uint64_t db, int scale_d) {
  asm volatile("{\n.reg .pred p;\n"
    "setp.ne.b32 p, %37, 0;\n"
    "wgmma.mma_async.sync.aligned.m64n64k16.f32.bf16.bf16 "
    "{%0, %1, %2, %3, %4, %5, %6, %7, %8, %9, %10, %11, %12, %13, %14, %15, "
    "%16, %17, %18, %19, %20, %21, %22, %23, %24, %25, %26, %27, %28, %29, %30, %31}, "
    "{%32, %33, %34, %35}, %36, p, 1, 1, 0;\n}\n"
    : "+f"(d[0]), "+f"(d[1]), "+f"(d[2]), "+f"(d[3]), "+f"(d[4]), "+f"(d[5]), "+f"(d[6]), "+f"(d[7]),
      "+f"(d[8]), "+f"(d[9]), "+f"(d[10]), "+f"(d[11]), "+f"(d[12]), "+f"(d[13]), "+f"(d[14]), "+f"(d[15]),
      "+f"(d[16]), "+f"(d[17]), "+f"(d[18]), "+f"(d[19]), "+f"(d[20]), "+f"(d[21]), "+f"(d[22]), "+f"(d[23]),
      "+f"(d[24]), "+f"(d[25]), "+f"(d[26]), "+f"(d[27]), "+f"(d[28]), "+f"(d[29]), "+f"(d[30]), "+f"(d[31])
    : "r"(a0), "r"(a1), "r"(a2), "r"(a3), "l"(db), "r"(scale_d));
}
__device__ __forceinline__ void wgmma6_ss_n80_t1(float (&d)[40], uint64_t da, uint64_t db, int scale_d) {
  asm volatile("{\n.reg .pred p;\n"
    "setp.ne.b32 p, %42, 0;\n"
    "wgmma.mma_async.sync.aligned.m64n80k16.f32.bf16.bf16 "
    "{%0, %1, %2, %3, %4, %5, %6, %7, %8, %9, %10, %11, %12, %13, %14, %15, "
    "%16, %17, %18, %19, %20, %21, %22, %23, %24, %25, %26, %27, %28, %29, %30, %31, "
    "%32, %33, %34, %35, %36, %37, %38, %39}, "
    "%40, %41, p, 1, 1, 0, 1;\n}\n"
    : "+f"(d[0]), "+f"(d[1]), "+f"(d[2]), "+f"(d[3]), "+f"(d[4]), "+f"(d[5]), "+f"(d[6]), "+f"(d[7]),
      "+f"(d[8]), "+f"(d[9]), "+f"(d[10]), "+f"(d[11]), "+f"(d[12]), "+f"(d[13]), "+f"(d[14]), "+f"(d[15]),
      "+f"(d[16]), "+f"(d[17]), "+f"(d[18]), "+f"(d[19]), "+f"(d[20]), "+f"(d[21]), "+f"(d[22]), "+f"(d[23]),
      "+f"(d[24]), "+f"(d[25]), "+f"(d[26]), "+f"(d[27]), "+f"(d[28]), "+f"(d[29]), "+f"(d[30]), "+f"(d[31]),
      "+f"(d[32]), "+f"(d[33]), "+f"(d[34]), "+f"(d[35]), "+f"(d[36]), "+f"(d[37]), "+f"(d[38]), "+f"(d[39])
    : "l"(da), "l"(db), "r"(scale_d));
}
__device__ __forceinline__ void wgmma6_ss_n144_t1(float (&d)[72], uint64_t da, uint64_t db, int scale_d) {
  asm volatile("{\n.reg .pred p;\n"
    "setp.ne.b32 p, %74, 0;\n"
    "wgmma.mma_async.sync.aligned.m64n144k16.f32.bf16.bf16 "
    "{%0, %1, %2, %3, %4, %5, %6, %7, %8, %9, %10, %11, %12, %13, %14, %15, "
    "%16, %17, %18, %19, %20, %21, %22, %23, %24, %25, %26, %27, %28, %29, %30, %31, "
    "%32, %33, %34, %35, %36, %37, %38, %39, %40, %41, %42, %43, %44, %45, %46, %47, "
    "%48, %49, %50, %51, %52, %53, %54, %55, %56, %57, %58, %59, %60, %61, %62, %63, "
    "%64, %65, %66, %67, %68, %69, %70, %71}, "
    "%72, %73, p, 1, 1, 0, 1;\n}\n"
    : "+f"(d[0]), "+f"(d[1]), "+f"(d[2]), "+f"(d[3]), "+f"(d[4]), "+f"(d[5]), "+f"(d[6]), "+f"(d[7]),
      "+f"(d[8]), "+f"(d[9]), "+f"(d[10]), "+f"(d[11]), "+f"(d[12]), "+f"(d[13]), "+f"(d[14]), "+f"(d[15]),
      "+f"(d[16]), "+f"(d[17]), "+f"(d[18]), "+f"(d[19]), "+f"(d[20]), "+f"(d[21]), "+f"(d[22]), "+f"(d[23]),
      "+f"(d[24]), "+f"(d[25]), "+f"(d[26]), "+f"(d[27]), "+f"(d[28]), "+f"(d[29]), "+f"(d[30]), "+f"(d[31]),
      "+f"(d[32]), "+f"(d[33]), "+f"(d[34]), "+f"(d[35]), "+f"(d[36]), "+f"(d[37]), "+f"(d[38]), "+f"(d[39]),
      "+f"(d[40]), "+f"(d[41]), "+f"(d[42]), "+f"(d[43]), "+f"(d[44]), "+f"(d[45]), "+f"(d[46]), "+f"(d[47]),
      "+f"(d[48]), "+f"(d[49]), "+f"(d[50]), "+f"(d[51]), "+f"(d[52]), "+f"(d[53]), "+f"(d[54]), "+f"(d[55]),
      "+f"(d[56]), "+f"(d[57]), "+f"(d[58]), "+f"(d[59]), "+f"(d[60]), "+f"(d[61]), "+f"(d[62]), "+f"(d[63]),
      "+f"(d[64]), "+f"(d[65]), "+f"(d[66]), "+f"(d[67]), "+f"(d[68]), "+f"(d[69]), "+f"(d[70]), "+f"(d[71])
    : "l"(da), "l"(db), "r"(scale_d));
}
__device__ __forceinline__ void wgmma6_ss_n256_t1(float (&d)[128], uint64_t da, uint64_t db, int scale_d) {
  asm volatile("{\n.reg .pred p;\n"
    "setp.ne.b32 p, %130, 0;\n"
    "wgmma.mma_async.sync.aligned.m64n256k16.f32.bf16.bf16 "
    "{%0, %1, %2, %3, %4, %5, %6, %7, %8, %9, %10, %11, %12, %13, %14, %15, "
    "%16, %17, %18, %19, %20, %21, %22, %23, %24, %25, %26, %27, %28, %29, %30, %31, "
    "%32, %33, %34, %35, %36, %37, %38, %39, %40, %41, %42, %43, %44, %45, %46, %47, "
    "%48, %49, %50, %51, %52, %53, %54, %55, %56, %57, %58, %59, %60, %61, %62, %63, "
    "%64, %65, %66, %67, %68, %69, %70, %71, %72, %73, %74, %75, %76, %77, %78, %79, "
    "%80, %81, %82, %83, %84, %85, %86, %87, %88, %89, %90, %91, %92, %93, %94, %95, "
    "%96, %97, %98, %99, %100, %101, %102, %103, %104, %105, %106, %107, %108, %109, %110, %111, "
    "%112, %113, %114, %115, %116, %117, %118, %119, %120, %121, %122, %123, %124, %125, %126, %127}, "
    "%128, %129, p, 1, 1, 0, 1;\n}\n"
    : "+f"(d[0]), "+f"(d[1]), "+f"(d[2]), "+f"(d[3]), "+f"(d[4]), "+f"(d[5]), "+f"(d[6]), "+f"(d[7]),
      "+f"(d[8]), "+f"(d[9]), "+f"(d[10]), "+f"(d[11]), "+f"(d[12]), "+f"(d[13]), "+f"(d[14]), "+f"(d[15]),
      "+f"(d[16]), "+f"(d[17]), "+f"(d[18]), "+f"(d[19]), "+f"(d[20]), "+f"(d[21]), "+f"(d[22]), "+f"(d[23]),
      "+f"(d[24]), "+f"(d[25]), "+f"(d[26]), "+f"(d[27]), "+f"(d[28]), "+f"(d[29]), "+f"(d[30]), "+f"(d[31]),
      "+f"(d[32]), "+f"(d[33]), "+f"(d[34]), "+f"(d[35]), "+f"(d[36]), "+f"(d[37]), "+f"(d[38]), "+f"(d[39]),
      "+f"(d[40]), "+f"(d[41]), "+f"(d[42]), "+f"(d[43]), "+f"(d[44]), "+f"(d[45]), "+f"(d[46]), "+f"(d[47]),
      "+f"(d[48]), "+f"(d[49]), "+f"(d[50]), "+f"(d[51]), "+f"(d[52]), "+f"(d[53]), "+f"(d[54]), "+f"(d[55]),
      "+f"(d[56]), "+f"(d[57]), "+f"(d[58]), "+f"(d[59]), "+f"(d[60]), "+f"(d[61]), "+f"(d[62]), "+f"(d[63]),
      "+f"(d[64]), "+f"(d[65]), "+f"(d[66]), "+f"(d[67]), "+f"(d[68]), "+f"(d[69]), "+f"(d[70]), "+f"(d[71]),
      "+f"(d[72]), "+f"(d[73]), "+f"(d[74]), "+f"(d[75]), "+f"(d[76]), "+f"(d[77]), "+f"(d[78]), "+f"(d[79]),
      "+f"(d[80]), "+f"(d[81]), "+f"(d[82]), "+f"(d[83]), "+f"(d[84]), "+f"(d[85]), "+f"(d[86]), "+f"(d[87]),
      "+f"(d[88]), "+f"(d[89]), "+f"(d[90]), "+f"(d[91]), "+f"(d[92]), "+f"(d[93]), "+f"(d[94]), "+f"(d[95]),
      "+f"(d[96]), "+f"(d[97]), "+f"(d[98]), "+f"(d[99]), "+f"(d[100]), "+f"(d[101]), "+f"(d[102]), "+f"(d[103]),
      "+f"(d[104]), "+f"(d[105]), "+f"(d[106]), "+f"(d[107]), "+f"(d[108]), "+f"(d[109]), "+f"(d[110]), "+f"(d[111]),
      "+f"(d[112]), "+f"(d[113]), "+f"(d[114]), "+f"(d[115]), "+f"(d[116]), "+f"(d[117]), "+f"(d[118]), "+f"(d[119]),
      "+f"(d[120]), "+f"(d[121]), "+f"(d[122]), "+f"(d[123]), "+f"(d[124]), "+f"(d[125]), "+f"(d[126]), "+f"(d[127])
    : "l"(da), "l"(db), "r"(scale_d));
}

__device__ __forceinline__ void wg_fence() { asm volatile("wgmma.fence.sync.aligned;" ::: "memory"); }
__device__ __forceinline__ void wg_commit() { asm volatile("wgmma.commit_group.sync.aligned;" ::: "memory"); }
template <int N> __device__ __forceinline__ void wg_wait() { asm volatile("wgmma.wait_group.sync.aligned %0;" ::"n"(N) : "memory"); }
__host__ __device__ constexpr uint32_t dlo(uint32_t off, uint32_t lbo) { return (off >> 4) | ((lbo >> 4) << 16); }
__host__ __device__ constexpr uint32_t dhi(uint32_t sbo, uint32_t swz) { return (sbo >> 4) | (swz << 30); }
constexpr uint32_t HI_X = dhi(512, 2), HI_W = dhi(1024, 1), HI_A2 = dhi(256, 0), HI_K = dhi(640, 0), HI_V = dhi(128, 0), HI_T = dhi(256, 0);
constexpr uint32_t QB0 = dlo(8192, 2048), QB1 = QB0 + 384, QT1 = 48;
__device__ __forceinline__ float ex2(float x) { float y; asm volatile("ex2.approx.ftz.f32 %0, %1;" : "=f"(y) : "f"(x)); return y; }
template <uint32_t HI> __device__ __forceinline__ uint64_t mkdesc(uint32_t lo) {
    uint64_t d;
    asm("mov.b64 %0, {%1, %2};" : "=l"(d) : "r"(lo), "n"(HI));
    return d;
}
__device__ __forceinline__ float rcp_fast(float x) { float y; asm("rcp.approx.ftz.f32 %0, %1;" : "=f"(y) : "f"(x)); return y; }
__device__ __forceinline__ float tanh_fast(float x) { float y; asm("tanh.approx.f32 %0, %1;" : "=f"(y) : "f"(x)); return y; }
__device__ __forceinline__ uint32_t pack(float lo, float hi) { uint32_t y; asm("cvt.rn.bf16x2.f32 %0, %1, %2;" : "=r"(y) : "f"(hi), "f"(lo)); return y; }
template <int N> __device__ __forceinline__ void fence_regs(float (&d)[N]) {
#pragma unroll
    for (int i = 0; i < N; i++) asm volatile("" : "+f"(d[i])::"memory");
}
template <int N> __device__ __forceinline__ void fence_regs(uint32_t (&d)[N]) {
#pragma unroll
    for (int i = 0; i < N; i++) asm volatile("" : "+r"(d[i])::"memory");
}
template <int N> __device__ __forceinline__ void undef_regs(float (&d)[N]) {
#pragma unroll
    for (int i = 0; i < N; i++) asm volatile("" : "=f"(d[i]));
}
__device__ __forceinline__ void mbar_init(uint32_t bar, uint32_t cnt) { asm volatile("mbarrier.init.shared::cta.b64 [%0], %1;" ::"r"(bar), "r"(cnt) : "memory"); }
__device__ __forceinline__ void mbar_expect_tx(uint32_t bar, uint32_t bytes) { asm volatile("mbarrier.arrive.expect_tx.shared::cta.b64 _, [%0], %1;" ::"r"(bar), "r"(bytes) : "memory"); }
__device__ __forceinline__ void mbar_arrive(uint32_t bar) { asm volatile("mbarrier.arrive.shared::cta.b64 _, [%0];" ::"r"(bar) : "memory"); }
__device__ __forceinline__ void mbar_arrive_cluster(uint32_t bar, uint32_t cta) {
    asm volatile("{\n.reg .b32 ra;\nmapa.shared::cluster.u32 ra, %0, %1;\nmbarrier.arrive.shared::cluster.b64 _, [ra];\n}" ::"r"(bar), "r"(cta) : "memory");
}
__device__ __forceinline__ void mbar_wait(uint32_t bar, uint32_t parity) {
    asm volatile(
        "{\n.reg .pred p;\n.reg .u32 n;\n"
        "mbarrier.try_wait.parity.shared::cta.b64 p, [%0], %1;\n"
        "@p bra.uni LAB_DONE;\n"
        "mov.u32 n, 0;\n"
        "LAB_WAIT:\n"
        "mbarrier.try_wait.parity.shared::cta.b64 p, [%0], %1, 1000;\n"
        "@p bra.uni LAB_DONE;\n"
        "add.u32 n, n, 1;\n"
        "setp.ge.u32 p, n, 0x400000;\n"
        "@p trap;\n"
        "bra.uni LAB_WAIT;\n"
        "LAB_DONE:\n}" ::"r"(bar), "r"(parity) : "memory");
}
__device__ __forceinline__ void flag_wait(const uint32_t* p, uint32_t target) {
    asm volatile(
        "{\n.reg .pred p;\n.reg .u32 n;\n.reg .s32 v;\n"
        "mov.u32 n, 0;\n"
        "LAB_WAIT:\n"
        "ld.acquire.gpu.global.s32 v, [%0];\n"
        "sub.s32 v, v, %1;\n"
        "setp.ge.s32 p, v, 0;\n"
        "@p bra.uni LAB_DONE;\n"
        "add.u32 n, n, 1;\n"
        "setp.ge.u32 p, n, 0x800000;\n"
        "@p trap;\n"
        "bra.uni LAB_WAIT;\n"
        "LAB_DONE:\n}" ::"l"(p), "r"(target) : "memory");
}
__device__ __forceinline__ uint32_t flag_wait_bits(const uint32_t* p, uint32_t base, uint32_t mask) {
    uint32_t v;
    asm volatile(
        "{\n.reg .pred p;\n.reg .u32 n, t;\n"
        "mov.u32 n, 0;\n"
        "LAB_WAIT:\n"
        "ld.acquire.gpu.global.u32 %0, [%1];\n"
        "sub.u32 %0, %0, %2;\n"
        "and.b32 t, %0, %3;\n"
        "setp.ne.u32 p, t, 0;\n"
        "@p bra.uni LAB_DONE;\n"
        "add.u32 n, n, 1;\n"
        "setp.ge.u32 p, n, 0x800000;\n"
        "@p trap;\n"
        "bra.uni LAB_WAIT;\n"
        "LAB_DONE:\n}" : "=&r"(v) : "l"(p), "r"(base), "r"(mask) : "memory");
    return v;
}
__device__ __forceinline__ void flag_add(uint32_t* p) { asm volatile("red.release.gpu.global.add.u32 [%0], 1;" ::"l"(p) : "memory"); }
__device__ __forceinline__ void flag_addv(uint32_t* p, uint32_t v) { asm volatile("red.release.gpu.global.add.u32 [%0], %1;" ::"l"(p), "r"(v) : "memory"); }
__device__ __forceinline__ void fence_async_global() { asm volatile("fence.proxy.async.global;" ::: "memory"); }
__device__ __forceinline__ void fence_async_shared() { asm volatile("fence.proxy.async.shared::cta;" ::: "memory"); }
__device__ __forceinline__ bool elect_one() {
    uint32_t p;
    asm volatile("{\n.reg .pred p;\nelect.sync _|p, 0xffffffff;\nselp.u32 %0, 1, 0, p;\n}" : "=r"(p));
    return p != 0;
}
__device__ __forceinline__ uint32_t mbar_test(uint32_t bar, uint32_t parity) {
    uint32_t p;
    asm volatile("{\n.reg .pred p;\nmbarrier.test_wait.parity.shared::cta.b64 p, [%1], %2;\nselp.u32 %0, 1, 0, p;\n}" : "=r"(p) : "r"(bar), "r"(parity) : "memory");
    return p;
}
__device__ __forceinline__ void mbar_wait_unless(uint32_t done, uint32_t bar, uint32_t parity) {
    asm volatile(
        "{\n.reg .pred p;\n.reg .u32 n;\n"
        "setp.ne.u32 p, %2, 0;\n"
        "@p bra.uni LAB_DONE;\n"
        "mov.u32 n, 0;\n"
        "LAB_WAIT:\n"
        "mbarrier.try_wait.parity.shared::cta.b64 p, [%0], %1, 1000;\n"
        "@p bra.uni LAB_DONE;\n"
        "add.u32 n, n, 1;\n"
        "setp.ge.u32 p, n, 0x400000;\n"
        "@p trap;\n"
        "bra.uni LAB_WAIT;\n"
        "LAB_DONE:\n}" ::"r"(bar), "r"(parity), "r"(done) : "memory");
}
__device__ __forceinline__ void bulk_s2g(void* dst, uint32_t src, uint32_t bytes) {
    asm volatile("cp.async.bulk.global.shared::cta.bulk_group [%0], [%1], %2;" ::"l"(dst), "r"(src), "r"(bytes) : "memory");
}
__device__ __forceinline__ void bulk_s2c(uint32_t addr, uint32_t bytes, uint32_t bar, uint32_t cta) {
    asm volatile("{\n.reg .b32 d, b;\nmapa.shared::cluster.u32 d, %0, %3;\nmapa.shared::cluster.u32 b, %2, %3;\n"
                 "cp.async.bulk.shared::cluster.shared::cta.mbarrier::complete_tx::bytes [d], [%0], %1, [b];\n}"
                 ::"r"(addr), "r"(bytes), "r"(bar), "r"(cta) : "memory");
}
__device__ __forceinline__ void sts32(uint32_t a, uint32_t v) { asm volatile("st.shared.u32 [%0], %1;" ::"r"(a), "r"(v) : "memory"); }
__device__ __forceinline__ void sts128(uint32_t a, uint32_t x, uint32_t y, uint32_t z, uint32_t w) { asm volatile("st.shared.v4.u32 [%0], {%1, %2, %3, %4};" ::"r"(a), "r"(x), "r"(y), "r"(z), "r"(w) : "memory"); }
__device__ __forceinline__ void stsm4(uint32_t a, uint32_t r0, uint32_t r1, uint32_t r2, uint32_t r3) {
    asm volatile("stmatrix.sync.aligned.m8n8.x4.shared.b16 [%0], {%1, %2, %3, %4};" ::"r"(a), "r"(r0), "r"(r1), "r"(r2), "r"(r3) : "memory");
}
__device__ __forceinline__ void ldsm4(uint32_t* r, uint32_t a) {
    asm volatile("ldmatrix.sync.aligned.m8n8.x4.shared.b16 {%0, %1, %2, %3}, [%4];" : "=r"(r[0]), "=r"(r[1]), "=r"(r[2]), "=r"(r[3]) : "r"(a) : "memory");
}
__device__ __forceinline__ uint32_t lds32(uint32_t a) { uint32_t v; asm volatile("ld.shared.u32 %0, [%1];" : "=r"(v) : "r"(a) : "memory"); return v; }
__device__ __forceinline__ void tma_2d(uint32_t dst, const CUtensorMap* tm, int c0, int c1, uint32_t bar) {
    asm volatile("cp.async.bulk.tensor.2d.shared::cluster.global.mbarrier::complete_tx::bytes [%0], [%1, {%3, %4}], [%2];"
                 ::"r"(dst), "l"(tm), "r"(bar), "r"(c0), "r"(c1) : "memory");
}
__device__ __forceinline__ void tma_2d_mc(uint32_t dst, const CUtensorMap* tm, int c0, int c1, uint32_t bar) {
    asm volatile("cp.async.bulk.tensor.2d.shared::cluster.global.mbarrier::complete_tx::bytes.multicast::cluster [%0], [%1, {%3, %4}], [%2], %5;"
                 ::"r"(dst), "l"(tm), "r"(bar), "r"(c0), "r"(c1), "h"((uint16_t)3) : "memory");
}
__device__ __forceinline__ void tma_3d(uint32_t dst, const CUtensorMap* tm, int c0, int c1, int c2, uint32_t bar) {
    asm volatile("cp.async.bulk.tensor.3d.shared::cluster.global.mbarrier::complete_tx::bytes [%0], [%1, {%3, %4, %5}], [%2];"
                 ::"r"(dst), "l"(tm), "r"(bar), "r"(c0), "r"(c1), "r"(c2) : "memory");
}
__device__ __forceinline__ void tma_3d_mc(uint32_t dst, const CUtensorMap* tm, int c0, int c1, int c2, uint32_t bar) {
    asm volatile("cp.async.bulk.tensor.3d.shared::cluster.global.mbarrier::complete_tx::bytes.multicast::cluster [%0], [%1, {%3, %4, %5}], [%2], %6;"
                 ::"r"(dst), "l"(tm), "r"(bar), "r"(c0), "r"(c1), "r"(c2), "h"((uint16_t)3) : "memory");
}
__device__ __forceinline__ void bulk_g2s(uint32_t dst, const void* src, uint32_t bytes, uint32_t bar) {
    asm volatile("cp.async.bulk.shared::cluster.global.mbarrier::complete_tx::bytes [%0], [%1], %2, [%3];"
                 ::"r"(dst), "l"(src), "r"(bytes), "r"(bar) : "memory");
}
__device__ __forceinline__ void bulk_g2s_mc(uint32_t dst, const void* src, uint32_t bytes, uint32_t bar) {
    asm volatile("cp.async.bulk.shared::cluster.global.mbarrier::complete_tx::bytes.multicast::cluster [%0], [%1], %2, [%3], %4;"
                 ::"r"(dst), "l"(src), "r"(bytes), "r"(bar), "h"((uint16_t)3) : "memory");
}
__device__ __forceinline__ void mma_16816(float* d, uint32_t a0, uint32_t a1, uint32_t a2, uint32_t a3, uint32_t b0, uint32_t b1) {
    asm volatile("mma.sync.aligned.m16n8k16.row.col.f32.bf16.bf16.f32 {%0,%1,%2,%3}, {%4,%5,%6,%7}, {%8,%9}, {%0,%1,%2,%3};"
                 : "+f"(d[0]), "+f"(d[1]), "+f"(d[2]), "+f"(d[3]) : "r"(a0), "r"(a1), "r"(a2), "r"(a3), "r"(b0), "r"(b1));
}
__device__ __forceinline__ uint32_t movm_t(uint32_t a) { uint32_t d; asm volatile("movmatrix.sync.aligned.m8n8.trans.b16 %0, %1;" : "=r"(d) : "r"(a)); return d; }
__device__ __forceinline__ uint32_t ldg32(const uint8_t* p) { uint32_t v; asm volatile("ld.global.u32 %0, [%1];" : "=r"(v) : "l"(p) : "memory"); return v; }
__device__ __forceinline__ void stg32(uint8_t* p, uint32_t v) { asm volatile("st.global.u32 [%0], %1;" ::"l"(p), "r"(v) : "memory"); }
#define PROF(i) do {} while (0)
#define TRACE() do {} while (0)
#define PROFX(w, i) do {} while (0)

struct Ring {
    uint32_t slot;
    uint32_t phase;
    __device__ __forceinline__ void next() { if (++slot == NSTAGE) { slot = 0; phase ^= 1; } }
};

__device__ __forceinline__ void load_q(uint32_t (&q)[8], uint32_t qa, int lane) {
    q[0] = lds32(qa + lane * 4);       q[1] = lds32(qa + lane * 4 + 256);
    q[2] = lds32(qa + lane * 4 + 128); q[3] = lds32(qa + lane * 4 + 384);
    const uint32_t t0 = lds32(qa + 512 + (lane & ~3)), t1 = lds32(qa + 544 + (lane & ~3));
    q[4] = (lane & 3) == 2 ? t0 : 0u;  q[5] = (lane & 3) == 2 ? t1 : 0u;
}

__device__ __forceinline__ bool norm_o(uint32_t (&w)[6], const float (&o)[12], int lane, uint32_t gaddr) {
    const float l0 = __shfl_sync(0xffffffffu, o[8], (lane & ~3) | 1);
    const float l1 = __shfl_sync(0xffffffffu, o[10], (lane & ~3) | 1);
    const float i0 = rcp_fast(l0) * __uint_as_float(lds32(gaddr)), i1 = rcp_fast(l1) * __uint_as_float(lds32(gaddr + 32));
    uint32_t big = 0;
#pragma unroll
    for (int b = 0; b < 3; b++) {
        w[2 * b] = pack(o[4 * b] * i0, o[4 * b + 1] * i0);
        w[2 * b + 1] = pack(o[4 * b + 2] * i1, o[4 * b + 3] * i1);
        if (b == 2 && (lane & 3) != 0) w[4] = w[5] = 0u;
        big |= ((w[2 * b] & 0x7F807F80u) + 0x00800080u) | ((w[2 * b + 1] & 0x7F807F80u) + 0x00800080u);
    }
    const bool ok = fminf(l0, l1) >= 0x1p-30f && l0 <= 0x1p80f && l1 <= 0x1p80f && (big & 0x80008000u) == 0;
    return !__all_sync(0xffffffffu, ok);
}

__device__ __forceinline__ void attn_true_max(float (&o)[12], const uint32_t (&q)[8], const uint8_t* kv) {
    float m0 = -INFINITY, m1 = -INFINITY;
#pragma unroll
    for (int i = 0; i < 12; i++) o[i] = 0.f;
#pragma unroll 1
    for (int kb = 0; kb < SEQ / 16; kb++) {
        uint32_t t[2][5];
#pragma unroll
        for (int g = 0; g < 2; g++)
#pragma unroll
            for (int ch = 0; ch < 5; ch++) t[g][ch] = ldg32(kv + (kb * 2 + g) * 640 + ch * 128);
        float s[2][4];
#pragma unroll
        for (int g = 0; g < 2; g++) {
            s[g][0] = s[g][1] = s[g][2] = s[g][3] = 0.f;
            mma_16816(s[g], q[0], q[1], q[2], q[3], t[g][0], t[g][1]);
            mma_16816(s[g], q[4], q[5], 0u, 0u, t[g][4], 0u);
        }
        float x0 = fmaxf(fmaxf(s[0][0], s[0][1]), fmaxf(s[1][0], s[1][1]));
        float x1 = fmaxf(fmaxf(s[0][2], s[0][3]), fmaxf(s[1][2], s[1][3]));
        x0 = fmaxf(x0, __shfl_xor_sync(0xffffffffu, x0, 1)); x0 = fmaxf(x0, __shfl_xor_sync(0xffffffffu, x0, 2));
        x1 = fmaxf(x1, __shfl_xor_sync(0xffffffffu, x1, 1)); x1 = fmaxf(x1, __shfl_xor_sync(0xffffffffu, x1, 2));
        const float n0 = fmaxf(m0, x0), n1 = fmaxf(m1, x1);
        const float u0 = (n0 == -INFINITY) ? 0.f : n0, u1 = (n1 == -INFINITY) ? 0.f : n1;
        const float c0 = ex2(m0 - u0), c1 = ex2(m1 - u1);
        m0 = n0; m1 = n1;
#pragma unroll
        for (int b = 0; b < 3; b++) { o[4 * b] *= c0; o[4 * b + 1] *= c0; o[4 * b + 2] *= c1; o[4 * b + 3] *= c1; }
        const uint32_t a0 = pack(ex2(s[0][0] - u0), ex2(s[0][1] - u0)), a1 = pack(ex2(s[0][2] - u1), ex2(s[0][3] - u1));
        const uint32_t a2 = pack(ex2(s[1][0] - u0), ex2(s[1][1] - u0)), a3 = pack(ex2(s[1][2] - u1), ex2(s[1][3] - u1));
#pragma unroll
        for (int b = 0; b < 3; b++) mma_16816(&o[4 * b], a0, a1, a2, a3, movm_t(t[0][2 + b]), movm_t(t[1][2 + b]));
    }
}

__device__ __forceinline__ float geglu2(float g, float u) {
    const float p = fmaf(g * g, 0.044715f * 0.7978845608028654f, 0.7978845608028654f);
    const float th = tanh_fast(g * p);
    const float y = g * u;
    return fmaf(y, th, y);
}

struct Attn {
    float s[32];
    float o[12];
    uint32_t p[16];
    uint32_t q[8];
};

__global__ void __cluster_dims__(2, 1, 1) __launch_bounds__(384, 1)
fused_kernel(__nv_bfloat16* __restrict__ out, const __nv_bfloat16* __restrict__ x, const __nv_bfloat16* __restrict__ gate_w,
             const __grid_constant__ CUtensorMap tm_x, const __grid_constant__ CUtensorMap tm_qkv,
             const __grid_constant__ CUtensorMap tm_qkv8,
             const __grid_constant__ CUtensorMap tm_wg, const __grid_constant__ CUtensorMap tm_wu,
             const __grid_constant__ CUtensorMap tm_wd, const __grid_constant__ CUtensorMap tm_wo,
             const __grid_constant__ CUtensorMap tm_wd16, const __grid_constant__ CUtensorMap tm_wo16) {
    extern __shared__ uint8_t smem_raw[];
    const uint32_t sb = __shfl_sync(0xffffffffu, ((uint32_t)__cvta_generic_to_shared(smem_raw) + 1023) & ~1023u, 0);
    const uint32_t bars = sb + OFF_BAR;
    const uint32_t bar_full = bars, bar_empty = bars + 64;
    const uint32_t bar_ev = bars + 128;
    const uint32_t bar_rdy = bars + 256;
    const uint32_t bar_ep = bars + 320, bar_gate = bars + 328;
    const uint32_t bar_st = bars + 336;
    const uint32_t bar_late = bars + 408;
    const uint32_t bar_px = bars + 416;
    const uint32_t bar_free = bars + 424;
    const uint32_t s_epoch = bars + 448, s_zero = bars + 452, s_order = bars + 464, s_gate = bars + 512;

    const int cta = blockIdx.x >= NCTA ? blockIdx.x : ((blockIdx.x & 14) << 3) | ((blockIdx.x >> 4) << 1) | (blockIdx.x & 1);
    const int rank = cta & 1;
    const int j = (cta >> 1) & 7;
    const int m = (cta >> 4) * 2 + rank;
    const int hf = j >> 2, nt = j & 3;
    const int warp = __shfl_sync(0xffffffffu, threadIdx.x >> 5, 0);
    const int lane = threadIdx.x & 31;
    const int wg = warp >> 2;

    const bool leader = elect_one();
    if (leader) {
        if (warp == 8) {
#pragma unroll
            for (int e = 0; e < E0; e++) mbar_init(bar_full + e * 8, 2);
        } else if (warp < NSTAGE) {
            if (warp >= E0) mbar_init(bar_full + warp * 8, 2);
            mbar_init(bar_empty + warp * 8, 4);
        }
        asm volatile("fence.mbarrier_init.release.cluster;" ::: "memory");
    }
    __syncwarp();
    asm volatile("barrier.cluster.arrive.relaxed.aligned;" ::: "memory");
    if (cta < NCTA && warp == 8 && leader) {
#pragma unroll 1
        for (int e = 0; e < E0; e++) {
            const uint32_t st = sb + e * SLOT, fb = bar_full + e * 8;
            mbar_arrive(fb);
            mbar_expect_tx(fb, 8192 + 12288 + 8192 + 1536);
            tma_2d(st + OFF_AX, &tm_x, e * 32, m * 128, fb);
#pragma unroll
            for (int r = 0; r < 2; r++) {
                tma_3d(st + 8192 + r * 6144, &tm_qkv, j * 72, e * 32 + r * 16, 0, fb);
                tma_3d(st + OFF_TL + r * 768, &tm_qkv8, j * 72 + 64, e * 32 + r * 16, 0, fb);
                tma_2d(st + r * 4096, r ? &tm_wu : &tm_wg, j * 576 + 512, e * 32, fb);
            }
        }
    }
    if (warp != 8) {
        if (leader && warp < 8) {
            const uint32_t lo = (warp >= 4 && warp <= 6) ? 1 : 4, hi = warp == 6 ? 4 : lo;
            mbar_init(bar_ev + warp * 32, lo); mbar_init(bar_ev + warp * 32 + 8, lo);
            mbar_init(bar_ev + warp * 32 + 16, hi); mbar_init(bar_ev + warp * 32 + 24, hi);
            if (warp < 4) mbar_init(bar_late + warp * 8, 1);
            sts32(s_zero, 0u); sts32(s_zero + 4, 0u);
            asm volatile("fence.mbarrier_init.release.cluster;" ::: "memory");
        }
        __syncwarp();
        asm volatile("bar.sync 1, 352;" ::: "memory");
    }
    __syncwarp();
    asm volatile("barrier.cluster.wait.acquire.aligned;" ::: "memory");

    if (wg == 2) {
        asm volatile("setmaxnreg.dec.sync.aligned.u32 24;");
        if (cta >= NCTA) {
            if (warp == 9 && elect_one()) {
                const uint32_t ep = g_flags[FL_E + cta * 32] + 1;
                g_flags[FL_E + cta * 32] = ep;
                mbar_wait(bar_ev + 2 * 8, 0);
                mbar_wait(bar_ev + 10 * 8, 0);
                flag_add(&g_flags[FL_G + (cta - NCTA) * 32]);
#pragma unroll 1
                for (int i = 0; i < 2; i++) {
                    const int jx = (cta - NCTA) * 2 + i;
                    flag_wait(&g_flags[FL_KV + jx * 32 + 1], ep * 32);
                    fence_async_global();
                    mbar_expect_tx(bar_rdy + i * 8, 20480 + 16 * 4608);
#pragma unroll 1
                    for (int p = 0; p < 8; p++) bulk_g2s(sb + 40960 + (i * 8 + p) * 9216, g_q3 + (p * 16 + jx * 2) * 4608, 9216, bar_rdy + i * 8);
                    bulk_g2s(sb + i * 20480, g_kv + (size_t)(jx * 4 + 3) * HEAD_BYTES + 28 * 5120, 20480, bar_rdy + i * 8);
                }
#pragma unroll 1
                for (int i = 0; i < 2; i++) {
                    mbar_wait(bar_ev + i * 8, 0);
                    mbar_wait(bar_ev + (8 + i) * 8, 0);
                    flag_add(&g_flags[FL_KV + ((cta - NCTA) * 2 + i) * 32 + 2]);
                }
            }
        } else if (warp == 8) {
            if (elect_one()) {
                Ring r{E0, 1};
                const int row0 = m * 128;
                const CUtensorMap* tw = rank ? &tm_wu : &tm_wg;
                PROFX(0, 40); PROFX(1, 40);
#pragma unroll 1
                for (int kk = E0; kk < 18; kk++) {
                    if (kk == 1) { PROFX(0, 41); PROFX(1, 41); }
                    if (kk == 6) { PROFX(0, 42); PROFX(1, 42); }
                    const uint32_t st = sb + r.slot * SLOT, fb = bar_full + r.slot * 8;
                    mbar_wait(bar_empty + r.slot * 8, r.phase);
                    mbar_arrive(fb);
                    mbar_expect_tx(fb, 8192 + 12288 + 8192 + 1536);
                    tma_2d(st + OFF_AX, &tm_x, kk * 32, row0, fb);
                    tma_3d_mc(st + 8192 + rank * 6144, &tm_qkv, j * 72, kk * 32 + rank * 16, 0, fb);
                    tma_3d_mc(st + OFF_TL + rank * 768, &tm_qkv8, j * 72 + 64, kk * 32 + rank * 16, 0, fb);
                    tma_2d_mc(st + rank * 4096, tw, j * 576 + 512, kk * 32, fb);
                    r.next();
                }
                int k0 = DM - NSTAGE * 32;
#pragma unroll 1
                for (int t = 0; t < 4; t++)
#pragma unroll 1
                    for (int kk = 0; kk < 18; kk++) {
                        const uint32_t st = sb + r.slot * SLOT, fb = bar_full + r.slot * 8;
                        mbar_wait(bar_empty + r.slot * 8, r.phase);
                        if (t == 0 && kk < 2) mbar_arrive(fb);
                        const bool have_x = kk < NSTAGE;
                        mbar_expect_tx(fb, have_x ? 16384 : 8192 + 16384);
                        tma_2d_mc(st + rank * 8192, tw, j * 576 + t * 128, k0, fb);
                        tma_2d_mc(st + rank * 8192 + 4096, tw, j * 576 + t * 128 + 64, k0, fb);
                        if (!have_x) tma_2d(st + OFF_AX, &tm_x, k0, row0, fb);
                        k0 += kk == 17 ? DM + 32 - NSTAGE * 32 : 32;
                        if (k0 >= DM) k0 -= DM;
                        r.next();
                    }
                const uint8_t* a2 = g_a2 + (size_t)m * A2_TILE;
                mbar_wait(bar_rdy + 4 * 8, 0);
#pragma unroll 1
                for (int n = 0; n < 48; n++) {
                    const int u = n >> 2, jj = n & 3;
                    const uint32_t st = sb + r.slot * SLOT, fb = bar_full + r.slot * 8;
                    mbar_wait(bar_empty + r.slot * 8, r.phase);
                    mbar_expect_tx(fb, 12288 + 12288 + STRIPB);
                    const int ks = (hf * 4 + jj) * 36 + u * 3;
#pragma unroll
                    for (int b = 0; b < 2; b++) tma_2d_mc(st + b * 6144 + rank * 3072, &tm_wd, nt * 128 + (b ^ hf) * 64, ks * 16 + rank * 24, fb);
                    tma_2d_mc(st + 12288 + rank * 3072, &tm_wd16, 512 + nt * 16, ks * 16 + rank * 24, fb);
                    if (jj == 0) { mbar_wait(bar_rdy + ((3 * u + 2) >> 3) * 8, 0); fence_async_global(); }
                    bulk_g2s(st + OFF_A2, a2 + ks * 4096, 12288, fb);
                    r.next();
                }
#pragma unroll 1
                for (int n = 0; n < 4; n++) {
                    const uint32_t st = sb + r.slot * SLOT, fb = bar_full + r.slot * 8;
                    mbar_wait(bar_empty + r.slot * 8, r.phase);
                    mbar_expect_tx(fb, 12288 + 12288 + STRIPB);
                    const int pr = hf * 2 + (n & 1), head = (pr * 2 + rank) * 4 + (n >> 1);
#pragma unroll
                    for (int b = 0; b < 2; b++) tma_2d_mc(st + b * 6144 + rank * 3072, &tm_wo, nt * 128 + (b ^ hf) * 64, head * 18, fb);
                    tma_2d_mc(st + 12288 + rank * 3072, &tm_wo16, 512 + nt * 16, head * 18, fb);
                    if (n == 0) { mbar_wait(bar_rdy + 5 * 8, 0); fence_async_global(); }
                    bulk_g2s(st + OFF_A2, a2 + (288 + ((n >> 1) * 4 + pr) * 3) * 4096, 12288, fb);
                    r.next();
                }
                mbar_expect_tx(bar_late, 4 * (6144 + STRIPB));
#pragma unroll 1
                for (int n = 0; n < 8; n++) {
                    const uint32_t st = sb + r.slot * SLOT, fb = bar_full + r.slot * 8;
                    mbar_wait(bar_empty + r.slot * 8, r.phase);
                    if (n >= 2) mbar_arrive(fb);
                    if (n < 4) mbar_expect_tx(fb, 12288 + 6144 + STRIPB);
                    const int head = ((n & 3) * 2 + rank) * 4 + 2 + (n >> 2);
                    tma_2d_mc(st + rank * 3072, &tm_wo, nt * 128 + hf * 64, head * 18, n < 4 ? fb : bar_late);
                    tma_2d_mc(st + 6144 + rank * 3072, &tm_wo16, 512 + nt * 16, head * 18, n < 4 ? fb : bar_late);
                    if (n < 4) bulk_g2s(st + OFF_A2, a2 + (288 + (8 + n) * 3) * 4096, 12288, fb);
                    r.next();
                }
                mbar_wait(bar_ep, 0);
                const uint32_t base = (lds32(s_epoch) - 1) * 0x04040404u;
                uint32_t todo = 0x04040404u, k = 2;
#pragma unroll 1
                while (todo) {
                    const uint32_t got = flag_wait_bits(&g_flags[FL_M + m * 64 + FM_LATE], base, todo) & todo;
                    fence_async_global();
#pragma unroll 1
                    for (int pr = 0; pr < 4; pr++)
                        if ((got >> (pr * 8)) & 4) {
                            sts32(s_order + k * 4, (2 + pr) * (SLOT >> 4));
                            mbar_expect_tx(bar_full + k * 8, 12288);
                            bulk_g2s(sb + k * SLOT + OFF_A2, a2 + (288 + (12 + pr) * 3) * 4096, 12288, bar_full + k * 8);
                            k++;
                        }
                    todo &= ~got;
                }
                PROFX(0, 50); PROFX(1, 50);
            }
        } else if (warp == 9) {
            if (elect_one()) {
                const uint32_t ep = g_flags[FL_E + cta * 32] + 1;
                g_flags[FL_E + cta * 32] = ep;
                sts32(s_epoch, ep);
                mbar_arrive(bar_ep);
                Ring r{0, 1};
                const uint8_t* kv = g_kv + (size_t)(j * 4) * HEAD_BYTES + rank * 2560;
                const int rot = (cta >> 4) * 4;
                uint32_t have = flag_wait_bits(&g_flags[FL_KV + j * 32], (ep - 1) * 0x44444444u, 4u << rot);
                fence_async_global();
#pragma unroll 1
                for (int it = 4; it < 124; it++) {
                    const uint32_t fb = bar_full + r.slot * 8;
                    if (it < 32 && !((have >> ((it + rot) & 28)) & 4)) {
                        have = flag_wait_bits(&g_flags[FL_KV + j * 32], (ep - 1) * 0x44444444u, 4u << ((it + rot) & 28));
                        fence_async_global();
                    }
                    if (it == 4) { PROFX(0, 37); PROFX(1, 37); }
                    if (it == 24) { flag_wait(&g_flags[FL_KV + j * 32 + 1], ep * 32); fence_async_global(); }
                    mbar_wait(bar_empty + r.slot * 8, r.phase);
                    mbar_expect_tx(fb, 5120);
                    bulk_g2s_mc(sb + r.slot * SLOT + OFF_KV + rank * 2560, kv + (it < 32 ? (it + rot) & 31 : it) * 5120, 2560, fb);
                    r.next();
                }
                flag_wait(&g_flags[FL_KV + j * 32 + 2], ep);
                mbar_arrive(bar_px);
                uint32_t* fr = &g_flags[FL_M + m * 64 + FM_R];
                mbar_wait(bar_ev + 6 * 8, 0);
                mbar_wait(bar_ev + 14 * 8, 0);
                PROFX(0, 51); PROFX(1, 51);
                flag_add(fr + j);
                PROFX(0, 52); PROFX(1, 52);
                flag_wait(fr + (j ^ 4), ep);
                PROFX(0, 53); PROFX(1, 53);
                mbar_arrive(bar_rdy + 6 * 8);
            }
        } else {
            const int w = warp - 10;
            if (elect_one()) {
                const uint32_t mine = 2 + rank * 2 + w, other = 2 + (rank ^ 1) * 2 + w;
                mbar_wait(bar_st + w * 8, 0);
                PROFX(w, 32);
                bulk_s2g(g_kv + (size_t)(j * 4) * HEAD_BYTES + (m * 16 + w * 8) * 640, sb + mine * SLOT + OFF_KV, 5120);
                asm volatile("cp.async.bulk.commit_group;" ::: "memory");
                mbar_arrive(bar_full + mine * 8);
                mbar_expect_tx(bar_full + other * 8, 5120);
#pragma unroll 1
                for (int i = 0; i < 2; i++) {
                    if (i == rank) {
                        mbar_wait(bar_empty + mine * 8, 0);
                        bulk_s2c(sb + mine * SLOT + OFF_KV, 5120, bar_full + mine * 8, rank ^ 1);
                    } else {
                        asm volatile("cp.async.bulk.wait_group 0;" ::: "memory");
                        flag_addv(&g_flags[FL_KV + j * 32], 1u << ((cta >> 4) * 4));
                    }
                }
                PROFX(w, 34);
                mbar_wait(bar_st + (2 + w) * 8, 0);
                __nanosleep(1500);
                bulk_s2g(g_q3 + cta * 4608 + w * 2304, sb + OFF_Q + 3 * 4608 + w * 2304, 2304);
#pragma unroll 1
                for (int h = 1; h < 4; h++) {
                    __nanosleep(200);
                    bulk_s2g(g_kv + (size_t)(j * 4 + h) * HEAD_BYTES + (m * 16 + w * 8) * 640, sb + (w * 3 + h - 1) * SLOT + OFF_GAP, 5120);
                    asm volatile("cp.async.bulk.commit_group;\ncp.async.bulk.wait_group 0;" ::: "memory");
                }
                mbar_arrive(bar_free + w * 8);
                flag_add(&g_flags[FL_KV + j * 32 + 1]);
                PROFX(w, 35);
            }
            __syncwarp();
            uint32_t* fm = &g_flags[FL_M + m * 64];
            mbar_wait(bar_ep, 0);
            const uint32_t ep = lds32(s_epoch);
            if (w == 1) {
                flag_wait(&g_flags[FL_G + (m >> 2) * 32], ep);
                const uint4 gv = __ldcg((const uint4*)(g_gate + m * 128) + lane);
                sts128(s_gate + lane * 16, gv.x, gv.y, gv.z, gv.w);
                __syncwarp();
                if (lane == 0) mbar_arrive(bar_gate);
            }
            if (elect_one()) {
#pragma unroll 1
                for (int i = 0; i < 6; i++) {
                    const int e = i == 0 ? 4 : i == 5 ? 5 : i - 1;
                    mbar_wait(bar_ev + (w * 8 + e) * 8, 0);
                    if (e < 3) {
                        uint8_t* hp = g_a2 + (size_t)m * A2_TILE + (j * 36 + e * 8) * 4096 + w * 2048;
#pragma unroll 1
                        for (int k = 0; k < 8; k++) {
                            const int g = (k * 11) >> 5;
                            bulk_s2g(hp + k * 4096, sb + (w * 3 + g) * SLOT + OFF_GAP + (k - g * 3) * 2048, 2048);
                        }
                        asm volatile("cp.async.bulk.commit_group;\ncp.async.bulk.wait_group 0;" ::: "memory");
                    }
                    uint32_t* fl = fm + FM_H + (e == 5 ? 5 : hf * 8 + e);
                    flag_add(fl);
                    if (w == 0) { flag_wait(fl, ep * (e == 5 ? 16 : 8)); mbar_arrive(bar_rdy + e * 8); }
                }
                mbar_wait(bar_ev + (w * 8 + 7) * 8, 0);
                PROFX(w, 48);
                flag_addv(fm + FM_LATE, 1u << ((j >> 1) * 8));
                PROFX(w, 49);
            }
        }
    } else {
        asm volatile("setmaxnreg.inc.sync.aligned.u32 240;");
        const int wq = warp & 3;
        const int c = lane & 3;
        const int tid = threadIdx.x & 127;
        const int grp = wg * 8 + wq * 2;
        const uint32_t sbd = (sb & 0x3FFFF) >> 4;
        uint32_t sd = sbd, pd = sbd, fb = bar_full, pb = bar_full, ph = 0;
#define STAGE_NEXT do { pd = sd; sd = (sd == sbd + (NSTAGE - 1) * (SLOT >> 4)) ? sbd : sd + (SLOT >> 4);           \
                        pb = fb; fb += 8; if (fb == bar_full + NSTAGE * 8) { fb = bar_full; ph ^= 1; } } while (0)
        auto release = [&]() { if (tid < 2) mbar_arrive_cluster(pb + 64, tid); };
        auto signal = [&](int e) { __syncwarp(); if (lane == 0) mbar_arrive(bar_ev + (wg * 8 + e) * 8); };
        if (cta >= NCTA) {
            PROF(0);
            {
                float wv[72];
#pragma unroll
                for (int i = 0; i < 9; i++) {
                    const uint4 t = __ldg((const uint4*)gate_w + (lane & 7) + i * 8);
                    const uint32_t u[4] = {t.x, t.y, t.z, t.w};
#pragma unroll
                    for (int e = 0; e < 4; e++) { wv[8 * i + 2 * e] = __uint_as_float(u[e] << 16); wv[8 * i + 2 * e + 1] = __uint_as_float(u[e] & 0xffff0000u); }
                }
                __nanosleep(1500);
#pragma unroll 1
                for (int b = 0; b < 8; b++) {
                    const int row = (cta - NCTA) * 512 + warp * 64 + b * 8 + (lane >> 3);
                    uint4 xa[2][9];
#pragma unroll
                    for (int r = 0; r < 2; r++)
#pragma unroll
                        for (int i = 0; i < 9; i++) xa[r][i] = __ldg((const uint4*)(x + (size_t)(row + r * 4) * DM) + (lane & 7) + i * 8);
#pragma unroll
                    for (int r = 0; r < 2; r++) {
                        float z = 0.f, y = 0.f;
#pragma unroll
                        for (int i = 0; i < 9; i++) {
                            const uint32_t u[4] = {xa[r][i].x, xa[r][i].y, xa[r][i].z, xa[r][i].w};
#pragma unroll
                            for (int e = 0; e < 4; e++) {
                                z = fmaf(__uint_as_float(u[e] << 16), wv[8 * i + 2 * e], z);
                                y = fmaf(__uint_as_float(u[e] & 0xffff0000u), wv[8 * i + 2 * e + 1], y);
                            }
                        }
                        z += y;
#pragma unroll
                        for (int d = 1; d < 8; d <<= 1) z += __shfl_xor_sync(0xffffffffu, z, d);
                        if ((lane & 7) == 0) g_gate[row + r * 4] = rcp_fast(1.f + ex2(-1.4426950408889634f * z));
                    }
                }
                signal(2);
                PROF(2);
            }
            float s0[64], s1[64], o[12];
            uint32_t p0[32], p1[32], q[8];
            q[6] = lds32(s_zero); q[7] = lds32(s_zero + 4);
#pragma unroll
            for (int i = 0; i < 12; i++) o[i] = 0.f;
            auto store_px = [&](int u) {
                const int src = ((u & 15) >> 1) * 16 + ((cta - NCTA) * 2 + (u >> 4)) * 2 + (u & 1);
                float4* dst = g_px + (size_t)(src * 2 + wg) * 3 * 128 + tid;
#pragma unroll
                for (int i = 0; i < 3; i++) __stcg(dst + i * 128, make_float4(o[4 * i], o[4 * i + 1], o[4 * i + 2], o[4 * i + 3]));
            };
            mbar_wait(bar_rdy, 0);
            PROF(1);
            load_q(q, sb + 40960 + warp * 576, lane);
            fence_regs(q); fence_regs(o);
            wg_fence();
            wgmma_rs_n128_t0<HI_K>(s0, q[0], q[1], q[2], q[3], sbd + dlo(0, 128), 0);
            wgmma_rs_n128_t0<HI_K>(s0, q[4], q[5], q[6], q[7], sbd + dlo(512, 0), 1);
            wg_commit();
            wg_wait<0>();
            fence_regs(s0);
#pragma unroll 1
            for (int u = 0; u < 32; u++) {
                const uint32_t kb = sbd + (u >> 4) * 1280;
                wg_fence();
                wgmma_rs_n128_t0<HI_K>(s1, q[0], q[1], q[2], q[3], kb + dlo(10240, 128), 0);
                wgmma_rs_n128_t0<HI_K>(s1, q[4], q[5], q[6], q[7], kb + dlo(10240 + 512, 0), 1);
                wg_commit();
#pragma unroll
                for (int i = 0; i < 32; i++) p0[i] = pack(ex2(s0[2 * i]), ex2(s0[2 * i + 1]));
                fence_regs(p0);
                wg_wait<0>();
                fence_regs(o); fence_regs(s1); fence_regs(q);
                store_px(u > 0 ? u - 1 : 0);
                if (u == 16) signal(0);
                if (u == 15) mbar_wait(bar_rdy + 8, 0);
                const int un = u < 31 ? u + 1 : u;
                load_q(q, sb + 40960 + un * 4608 + warp * 576, lane);
                fence_regs(q);
                const uint32_t kn = sbd + (un >> 4) * 1280;
                wg_fence();
#pragma unroll
                for (int i = 0; i < 8; i++) wgmma_rs_n24_t1<HI_V>(o, p0[4 * i], p0[4 * i + 1], p0[4 * i + 2], p0[4 * i + 3], kb + dlo(256, 640) + 80 * i, i != 0);
                wgmma_rs_n128_t0<HI_K>(s0, q[0], q[1], q[2], q[3], kn + dlo(0, 128), 0);
                wgmma_rs_n128_t0<HI_K>(s0, q[4], q[5], q[6], q[7], kn + dlo(512, 0), 1);
                wg_commit();
#pragma unroll
                for (int i = 0; i < 32; i++) p1[i] = pack(ex2(s1[2 * i]), ex2(s1[2 * i + 1]));
                fence_regs(p1);
                wg_fence();
#pragma unroll
                for (int i = 0; i < 8; i++) wgmma_rs_n24_t1<HI_V>(o, p1[4 * i], p1[4 * i + 1], p1[4 * i + 2], p1[4 * i + 3], kb + dlo(10240 + 256, 640) + 80 * i, 1);
                wg_commit();
                wg_wait<1>();
                fence_regs(s0); fence_regs(p0);
            }
            wg_wait<0>();
            fence_regs(o);
            store_px(31);
            signal(1);
            PROF(20);
            return;
        }
        Attn at;
        PROF(0);

        uint8_t* a2w = g_a2 + (size_t)m * A2_TILE + grp * 256 + lane * 4;
        const uint32_t qa = sb + OFF_Q + warp * 576;
        float acc[128];
        {
            float qkv[96], tl[12], gu[64];
            const uint32_t xrow = wg * 64 + wq * 16 + (lane & 15);
            const uint32_t xa0 = (sb & ~0x3FFFFu) + OFF_AX + xrow * 64 + (((lane >> 4) ^ ((xrow >> 1) & 3)) << 4);
            uint32_t xf[2][8];
#pragma unroll 1
            for (int k2 = 0; k2 < 18 - DEFER; k2 += 2) {
#pragma unroll
                for (int h = 0; h < 2; h++) {
                    const int kk = k2 + h;
                    mbar_wait(fb, ph);
                    if (kk == 0) PROF(21);
                    if (kk == 6) PROF(22);
                    if (kk == 12) PROF(23);
                    ldsm4(&xf[h][0], xa0 + sd * 16);
                    ldsm4(&xf[h][4], (xa0 ^ 32) + sd * 16);
                    fence_regs(xf[h]);
                    const uint32_t db = sd + dlo(0, 4096), dt = sd + dlo(OFF_TL, 128);
                    wg_fence();
                    wgmma_rs_n192_t1<HI_W>(qkv, xf[h][0], xf[h][1], xf[h][2], xf[h][3], sd + QB0, kk != 0);
                    wgmma_rs_n24_t1<HI_T>(tl, xf[h][0], xf[h][1], xf[h][2], xf[h][3], dt, kk != 0);
                    wgmma_rs_n128_t1<HI_W>(gu, xf[h][0], xf[h][1], xf[h][2], xf[h][3], db, kk != 0);
                    wgmma_rs_n192_t1<HI_W>(qkv, xf[h][4], xf[h][5], xf[h][6], xf[h][7], sd + QB1, 1);
                    wgmma_rs_n24_t1<HI_T>(tl, xf[h][4], xf[h][5], xf[h][6], xf[h][7], dt + QT1, 1);
                    wgmma_rs_n128_t1<HI_W>(gu, xf[h][4], xf[h][5], xf[h][6], xf[h][7], db + 128, 1);
                    wg_commit();
                    wg_wait<1>();
                    if (kk > 0) release();
                    STAGE_NEXT;
                }
            }
#pragma unroll
            for (int kk = 0; kk < DEFER; kk++) {
                mbar_wait(fb + kk * 8, ph);
                const uint32_t st = sd + kk * (SLOT >> 4);
                const uint32_t da = st + wg * 256 + dlo(OFF_AX, 16), dt = st + dlo(OFF_TL, 128);
                wg_fence();
                wgmma_ss_n192_t1<HI_X, HI_W>(qkv, da, st + QB0, 1);
                wgmma_ss_n24_t1<HI_X, HI_T>(tl, da, dt, 1);
                wgmma_ss_n192_t1<HI_X, HI_W>(qkv, da + 2, st + QB1, 1);
                wgmma_ss_n24_t1<HI_X, HI_T>(tl, da + 2, dt + QT1, 1);
                wg_commit();
                if (kk == 0) { wg_wait<1>(); release(); }
            }
#pragma unroll
            for (int kk = 0; kk < DEFER; kk++) {
                const uint32_t st = sd + kk * (SLOT >> 4);
                const uint32_t da = st + wg * 256 + dlo(OFF_AX, 16), db = st + dlo(0, 4096);
                wgmma_ss_n128_t1<HI_X, HI_W>(gu, da, db, 1);
                wgmma_ss_n128_t1<HI_X, HI_W>(gu, da + 2, db + 128, 1);
            }
            wg_commit();
            wg_wait<1>();
            fence_regs(qkv); fence_regs(tl);
            PROF(1);
            constexpr float QS = 0.23570226039551584f * 1.4426950408889634f;
            uint32_t kp[9][2], vp[9][2];
#pragma unroll
            for (int i = 0; i < 9; i++) {
                const float* k4 = i < 8 ? &qkv[32 + 4 * i] : &tl[4];
                const float* v4 = i < 8 ? &qkv[64 + 4 * i] : &tl[8];
                kp[i][0] = pack(k4[0], k4[1]); kp[i][1] = pack(k4[2], k4[3]);
                vp[i][0] = pack(v4[0], v4[1]); vp[i][1] = pack(v4[2], v4[3]);
            }
            const int quad = lane & ~3;
            const uint32_t cst = c == 1 ? 0x3F80u : 0u;
            {
                const uint32_t a = sb + (2 + rank * 2 + wg) * SLOT + OFF_KV + wq * 1280 + lane * 4;
#pragma unroll
                for (int r = 0; r < 2; r++) {
                    const uint32_t kt = __shfl_sync(0xffffffffu, kp[2][r], quad);
                    sts32(a + r * 640, kp[0][r]);       sts32(a + r * 640 + 128, kp[1][r]);
                    sts32(a + r * 640 + 256, vp[0][r]); sts32(a + r * 640 + 384, vp[1][r]);
                    sts32(a + r * 640 + 512, c == 0 ? vp[2][r] : c == 2 ? kt : cst);
                }
                fence_async_shared();
                __syncwarp();
                if (lane == 0) mbar_arrive(bar_st + wg * 8);
            }
            PROF(2);
#pragma unroll
            for (int i = 0; i < 9; i++) {
                const float* q4 = i < 8 ? &qkv[4 * i] : &tl[0];
                const uint32_t q0 = pack(q4[0] * QS, q4[1] * QS), q1 = pack(q4[2] * QS, q4[3] * QS);
                if (i < 2) { at.q[2 * i] = q0; at.q[2 * i + 1] = q1; }
                else {
                    if (i == 2) {
                        const uint32_t t0 = __shfl_sync(0xffffffffu, q0, quad), t1 = __shfl_sync(0xffffffffu, q1, quad);
                        at.q[4] = c == 2 ? t0 : 0u; at.q[5] = c == 2 ? t1 : 0u;
                    }
                    const int lc = 8 * i + 2 * c;
                    const int hd = (lc * 3641) >> 16;
                    const int d = lc - hd * 18;
                    const bool last = (i & 1) == 0 && c == i / 2 - 1;
                    const uint32_t aq = qa + hd * 4608 + (last ? 512 + (lane >> 2) * 4 : (d >> 3) * 128 + (d & 7) * 2 + (lane >> 2) * 16);
                    if (i > 2 || c > 0) { sts32(aq, q0); sts32(aq + (last ? 32 : 256), q1); }
                }
            }
            mbar_wait(bar_st, 0);
            mbar_wait(bar_st + 8, 0);
#pragma unroll
            for (int i = 2; i < 9; i++) {
                const int lc = 8 * i + 2 * c;
                const int hd = (lc * 3641) >> 16;
                const int d = lc - hd * 18;
                const uint32_t ak = sb + (wg * 3 - 1 + hd) * SLOT + OFF_GAP + wq * 1280 + (lane >> 2) * 16;
                const uint32_t off = (d >> 3) * 128 + (d & 7) * 2;
                if ((i & 1) == 0 && c == i / 2 - 1) {
                    if (i > 2) { sts128(ak + 512, vp[i][0], 0x3F80u, kp[i][0], 0u); sts128(ak + 512 + 640, vp[i][1], 0x3F80u, kp[i][1], 0u); }
                } else {
                    sts32(ak + off, kp[i][0]); sts32(ak + off + 640, kp[i][1]); sts32(ak + off + 256, vp[i][0]); sts32(ak + off + 256 + 640, vp[i][1]);
                }
            }
            fence_async_shared();
            __syncwarp();
            if (lane == 0) mbar_arrive(bar_st + (2 + wg) * 8);
            PROF(39);
            wg_wait<0>();
            fence_regs(gu);
            if (tid < 2 * DEFER) mbar_arrive_cluster(fb + 64 + (tid >> 1) * 8, tid & 1);
#pragma unroll
            for (int kk = 0; kk < 2; kk++) {
                mbar_wait(bar_full + kk * 8, 1);
                const uint32_t st = sbd + kk * (SLOT >> 4);
                const uint32_t da = st + wg * 256 + dlo(OFF_AX, 16), db = st + dlo(0, 4096);
                wg_fence();
                wgmma_ss_n256_t1<HI_X, HI_W>(acc, da, db, kk);
                wgmma_ss_n256_t1<HI_X, HI_W>(acc, da + 2, db + 128, 1);
                wg_commit();
            }
            sd = sbd + 2 * (SLOT >> 4); fb = bar_full + 16; pb = bar_full; ph = 1;
            uint8_t* hp = a2w + (j * 36 + 32) * 4096;
#pragma unroll
            for (int i = 0; i < 16; i++)
                stg32(hp + (i >> 2) * 4096 + ((i >> 1) & 1) * 128 + (i & 1) * 256, pack(geglu2(gu[2 * i], gu[32 + 2 * i]), geglu2(gu[2 * i + 1], gu[32 + 2 * i + 1])));
            signal(4);
            PROF(3);
            wg_wait<1>();
            release();
            mbar_wait(fb, ph);
            PROF(38);
        }

        const uint32_t gaddr = s_gate + (grp * 8 + (lane >> 2)) * 4;
        at.q[6] = lds32(s_zero); at.q[7] = lds32(s_zero + 4);
#pragma unroll
        for (int i = 0; i < 16; i++) at.p[i] = 0u;
#pragma unroll
        for (int i = 0; i < 12; i++) at.o[i] = 0.f;
        fence_regs(at.q); fence_regs(at.p); fence_regs(at.o);
        pd = sd;
        uint32_t rel = bar_empty + 8;
        asm volatile("mapa.shared::cluster.u32 %0, %0, %1;" : "+r"(rel) : "r"(tid & 1));
        const uint32_t rel_off = rel - (bar_full + 8);

#define ISSUE_PV() do {                                                                                            \
            const uint32_t dv = pd + dlo(OFF_KV + 256, 640);                                                       \
            wgmma_rs_n24_t1<HI_V>(at.o, at.p[0], at.p[1], at.p[2], at.p[3], dv, 1);                                \
            wgmma_rs_n24_t1<HI_V>(at.o, at.p[4], at.p[5], at.p[6], at.p[7], dv + 80, 1);                           \
            wgmma_rs_n24_t1<HI_V>(at.o, at.p[8], at.p[9], at.p[10], at.p[11], dv + 160, 1);                        \
            wgmma_rs_n24_t1<HI_V>(at.o, at.p[12], at.p[13], at.p[14], at.p[15], dv + 240, 1);                      \
        } while (0)
#define EXPS() do {                                                                                                \
            _Pragma("unroll") for (int i = 0; i < 16; i++) at.p[i] = pack(ex2(at.s[2 * i]), ex2(at.s[2 * i + 1])); \
            fence_regs(at.p);                                                                                      \
        } while (0)
#define FUSED_STEP_X(DV, DK, NB, NPH, REL, GEMM_CODE, HOOK) do {                                                           \
            wg_fence();                                                                                            \
            wgmma6_rs_n24_t1(at.o, at.p[0], at.p[1], at.p[2], at.p[3], (DV), 1);                                   \
            wgmma6_rs_n24_t1(at.o, at.p[4], at.p[5], at.p[6], at.p[7], (DV) + 80, 1);                              \
            wgmma6_rs_n24_t1(at.o, at.p[8], at.p[9], at.p[10], at.p[11], (DV) + 160, 1);                           \
            wgmma6_rs_n24_t1(at.o, at.p[12], at.p[13], at.p[14], at.p[15], (DV) + 240, 1);                         \
            wgmma6_rs_n64_t0(at.s, at.q[0], at.q[1], at.q[2], at.q[3], (DK) + dlo(0, 128), 0);                     \
            wgmma6_rs_n64_t0(at.s, at.q[4], at.q[5], at.q[6], at.q[7], (DK) + 32, 1);                              \
            wg_commit();                                                                                           \
            GEMM_CODE;                                                                                             \
            wg_commit();                                                                                           \
            HOOK; \
            const uint32_t rdy = mbar_test(NB, NPH);                                                               \
            wg_wait<1>();                                                                                          \
            fence_regs(at.s); fence_regs(at.p);                                                                    \
            if (tid < 2) asm volatile("mbarrier.arrive.shared::cluster.b64 _, [%0];" ::"r"(REL) : "memory");       \
            EXPS();                                                                                                \
            mbar_wait_unless(rdy, NB, NPH);                                                                        \
        } while (0)
#define FUSED_PAIR(HIA, LOA, LOB, STEP0, GEMM) do {                                                                \
            const uint64_t dv0 = mkdesc<HI_V>(pd + dlo(OFF_KV + 256, 640));                                        \
            const uint64_t dv1 = mkdesc<HI_V>(sd + dlo(OFF_KV + 256, 640));                                        \
            const uint64_t dk = mkdesc<HI_K>(sd + dlo(OFF_KV, 0));                                                 \
            const uint64_t da = mkdesc<HIA>(sd + (LOA)), db = mkdesc<HI_W>(sd + (LOB));                            \
            STEP0(dv0, dk, fb + 8, ph, rel, GEMM(da, db, first));                                                  \
            const uint32_t r1 = fb + rel_off;                                                                      \
            rel = r1 + 8;                                                                                          \
            pd = sd + (SLOT >> 4); pb = fb + 8;                                                                    \
            if (fb == bar_full + (NSTAGE - 2) * 8) { fb = bar_full; ph ^= 1; } else fb += 16;                      \
            sd = (sd == sbd + (NSTAGE - 2) * (SLOT >> 4)) ? sbd : sd + 2 * (SLOT >> 4);                            \
            FUSED_STEP(dv1, dk + (SLOT >> 4), fb, ph, r1, GEMM(da + (SLOT >> 4), db + (SLOT >> 4), 1));            \
            first = 1;                                                                                             \
            TRACE();                                                                                               \
        } while (0)
#define GEMM_256(A, B, SC) do { wgmma6_ss_n256_t1(acc, A, B, SC); wgmma6_ss_n256_t1(acc, (A) + 2, (B) + 128, 1); } while (0)
#define FUSED_STEP_H(DV, DK, NB, NPH, REL, GEMM_CODE) FUSED_STEP_X(DV, DK, NB, NPH, REL, GEMM_CODE, if (HID && !first) { fence_async_shared(); __syncwarp(); if (lane == 0) mbar_arrive(pend); })
#define FUSED_STEP(DV, DK, NB, NPH, REL, GEMM_CODE) FUSED_STEP_X(DV, DK, NB, NPH, REL, GEMM_CODE, {})
#define GEMM_80(A, B, SC) do { wgmma6_ss_n80_t1(keep, A, B, SC); wgmma6_ss_n80_t1(keep, (A) + 256, (B) + 128, 1); wgmma6_ss_n80_t1(keep, (A) + 512, (B) + 256, 1); } while (0)
#define GEMM_144(A, B, SC) do { wgmma6_ss_n144_t1(ah, A, B, SC); wgmma6_ss_n144_t1(ah, (A) + 256, (B) + 128, 1); wgmma6_ss_n144_t1(ah, (A) + 512, (B) + 256, 1); } while (0)
#define NORM_ITEM(item) do {                                                                                       \
            if (norm_o(ow, at.o, lane, gaddr)) {                                                                   \
                attn_true_max(at.o, at.q, g_kv + (size_t)(j * 4 + (item)) * HEAD_BYTES + lane * 4);                \
                norm_o(ow, at.o, lane, gaddr);                                                                     \
            }                                                                                                      \
        } while (0)
#define STORE_ITEM(item) do { uint32_t ow[6]; NORM_ITEM(item); PUT_ITEM(item); } while (0)
#define PUT_ITEM(item) do {                                                                                        \
            uint8_t* op = a2w + (288 + ((item) * 4 + (j >> 1)) * 3) * 4096 + (j & 1) * 4224;                       \
            const int step = (j & 1) ? 3968 : 128;                                                                 \
            stg32(op, ow[0]);        stg32(op + 256, ow[1]);                                                       \
            stg32(op + step, ow[2]); stg32(op + step + 256, ow[3]);                                                \
            stg32(op + 4096, ow[4]); stg32(op + 4096 + 256, ow[5]);                                                \
        } while (0)
#define ITEM_STEP(DV, DK, NB, NPH, REL, GEMM_CODE) do {                                                            \
            uint32_t qo[8];                                                                                        \
            _Pragma("unroll") for (int i = 0; i < 6; i++) asm volatile("mov.b32 %0, %1;" : "=r"(qo[i]) : "r"(at.q[i])); \
            load_q(at.q, qa + (item + 1) * 4608, lane);                                                            \
            fence_regs(at.q);                                                                                      \
            wg_fence();                                                                                            \
            wgmma6_rs_n24_t1(at.o, at.p[0], at.p[1], at.p[2], at.p[3], (DV), 1);                                   \
            wgmma6_rs_n24_t1(at.o, at.p[4], at.p[5], at.p[6], at.p[7], (DV) + 80, 1);                              \
            wgmma6_rs_n24_t1(at.o, at.p[8], at.p[9], at.p[10], at.p[11], (DV) + 160, 1);                           \
            wgmma6_rs_n24_t1(at.o, at.p[12], at.p[13], at.p[14], at.p[15], (DV) + 240, 1);                         \
            wgmma6_rs_n64_t0(at.s, at.q[0], at.q[1], at.q[2], at.q[3], (DK) + dlo(0, 128), 0);                     \
            wgmma6_rs_n64_t0(at.s, at.q[4], at.q[5], at.q[6], at.q[7], (DK) + 32, 1);                              \
            wg_commit();                                                                                           \
            GEMM_CODE;                                                                                             \
            wg_commit();                                                                                           \
            const uint32_t rdy = mbar_test(NB, NPH);                                                               \
            wg_wait<1>();                                                                                          \
            fence_regs(at.o); fence_regs(at.p); fence_regs(at.s);                                                  \
            if (tid < 2) asm volatile("mbarrier.arrive.shared::cluster.b64 _, [%0];" ::"r"(REL) : "memory");       \
            uint32_t ow[6];                                                                                        \
            const bool bad = norm_o(ow, at.o, lane, gaddr);                                                        \
            EXPS();                                                                                                \
            if (bad) {                                                                                             \
                attn_true_max(at.o, qo, g_kv + (size_t)(j * 4 + (item)) * HEAD_BYTES + lane * 4);                  \
                norm_o(ow, at.o, lane, gaddr);                                                                     \
            }                                                                                                      \
            PUT_ITEM(item);                                                                                        \
            _Pragma("unroll") for (int i = 0; i < 12; i++) at.o[i] = 0.f;                                          \
            fence_regs(at.o);                                                                                      \
            mbar_wait_unless(rdy, NB, NPH);                                                                        \
        } while (0)
#define H2(i) pack(geglu2(acc[i], acc[64 + (i)]), geglu2(acc[(i) + 1], acc[65 + (i)]))
        float keep[40];
        float4 px[3];
        {
            float ah[72];
            int first = 1;
            uint32_t pend = 0;
            {
#pragma unroll 1
                for (int t = 0; t < 5; t++) {
                    int n = 0x26988 >> (t * 4) & 15;
#pragma unroll 1
                    do { FUSED_PAIR(HI_X, wg * 256 + dlo(OFF_AX, 16), dlo(0, 4096), FUSED_STEP_H, GEMM_256); } while (--n);
                    if (t & 1) {
                        const int item = t >> 1;
                        mbar_wait(t == 1 ? bar_gate : bar_rdy + 2 * 8, 0);
                        FUSED_PAIR(HI_X, wg * 256 + dlo(OFF_AX, 16), dlo(0, 4096), ITEM_STEP, GEMM_256);
                    }
                    if (t < 3) {
                        mbar_wait(t > 0 ? bar_rdy + (t - 1) * 8 : bar_free + wg * 8, 0);
                        wg_wait<0>();
                        fence_regs(acc);
                        first = 0;
                        PROF(4 + 2 * t);
                        const uint32_t ha = sb + wg * 3 * SLOT + OFF_GAP + wq * 512 + lane * 16;
#pragma unroll
                        for (int k = 0; k < 8; k++) stsm4(ha + (k / 3) * SLOT + (k % 3) * 2048, H2(8 * k), H2(8 * k + 4), H2(8 * k + 2), H2(8 * k + 6));
                        if (!HID) { fence_async_shared(); signal(t); }
                        else pend = bar_ev + (wg * 8 + t) * 8;
                        undef_regs(acc);
                        PROF(5 + 2 * t);
                    }
                }
                wg_wait<0>();
                fence_regs(acc);
                first = 0;
                PROF(10);
                uint8_t* hp = a2w + (j * 36 + 24) * 4096;
#pragma unroll
                for (int b = 0; b < 2; b++)
                    if (cta != 1000 + b) {
#pragma unroll
                        for (int k = b * 4; k < b * 4 + 4; k++) {
                            stg32(hp + k * 4096, H2(8 * k));           stg32(hp + k * 4096 + 256, H2(8 * k + 2));
                            stg32(hp + k * 4096 + 128, H2(8 * k + 4)); stg32(hp + k * 4096 + 384, H2(8 * k + 6));
                        }
                    }
                signal(3);
                PROF(11);
            }
#pragma unroll 1
            for (int seg = 0; seg < 3; seg++) {
                int n = 0x2AD >> (seg * 4) & 15;
#pragma unroll 1
                do { FUSED_PAIR(HI_A2, wg * 128 + dlo(OFF_A2, 128), dlo(0, 6144), FUSED_STEP, GEMM_144); } while (--n);
                if (seg == 0) {
                    constexpr int item = 2;
                    FUSED_PAIR(HI_A2, wg * 128 + dlo(OFF_A2, 128), dlo(0, 6144), ITEM_STEP, GEMM_144);
                    signal(5);
                } else if (seg == 1) {
                    wg_wait<0>();
                    fence_regs(ah);
                    PROF(12);
                    const float w0 = 0.5f - 0.5f * __uint_as_float(lds32(gaddr)), w1 = 0.5f - 0.5f * __uint_as_float(lds32(gaddr + 32));
#pragma unroll
                    for (int i = 0; i < 72; i++) ah[i] *= (i & 2) ? w1 : w0;
                    fence_regs(ah);
                }
            }
            wg_wait<0>();
            fence_regs(ah);
            PROF(17);
            mbar_wait(bar_px, 0);
#pragma unroll
            for (int i = 0; i < 3; i++) px[i] = __ldcg(g_px + (size_t)(cta * 2 + wg) * 3 * 128 + tid + i * 128);
            uint4* mine = g_part + (size_t)(cta * 2 + wg) * 5 * 128 + tid;
#pragma unroll
            for (int i = 0; i < 5; i++) {
                const float* v = &ah[32 + 8 * i];
                __stcg(mine + i * 128, make_uint4(pack(v[0], v[1]), pack(v[2], v[3]), pack(v[4], v[5]), pack(v[6], v[7])));
            }
#pragma unroll
            for (int i = 0; i < 40; i++) keep[i] = ah[i < 32 ? i : 32 + i] + __uint_as_float(at.q[6]);
            signal(6);
            fence_regs(keep);
        }
        {
            int first = 1;
            FUSED_PAIR(HI_A2, wg * 128 + dlo(OFF_A2, 128), dlo(0, 6144), FUSED_STEP, GEMM_80);
        }
        PROF(13);
        wg_fence();
        ISSUE_PV();
        wg_commit();
        wg_wait<0>();
        fence_regs(at.o); fence_regs(at.p); fence_regs(at.q);
#pragma unroll
        for (int i = 0; i < 3; i++) { at.o[4 * i] += px[i].x; at.o[4 * i + 1] += px[i].y; at.o[4 * i + 2] += px[i].z; at.o[4 * i + 3] += px[i].w; }
        STORE_ITEM(3);
        signal(7);
        fence_regs(keep);
        PROF(14);
#pragma unroll 1
        for (int kk = 0; kk < 2; kk++) {
            mbar_wait(fb, ph);
            const uint64_t da = mkdesc<HI_A2>(sd + wg * 128 + dlo(OFF_A2, 128)), db = mkdesc<HI_W>(sd + dlo(0, 6144));
            wg_fence();
            GEMM_80(da, db, 1);
            wg_commit();
            wg_wait<1>();
            if (kk < 1) release();
            STAGE_NEXT;
        }
        {
            mbar_wait(bar_rdy + 6 * 8, 0);
            const uint4* theirs = g_part + (size_t)((cta ^ 8) * 2 + wg) * 5 * 128 + tid;
            uint4 pv[5];
#pragma unroll
            for (int i = 0; i < 5; i++) pv[i] = __ldcg(theirs + i * 128);
            wg_wait<0>();
            fence_regs(keep);
#pragma unroll
            for (int i = 0; i < 5; i++) {
                const uint32_t u[4] = {pv[i].x, pv[i].y, pv[i].z, pv[i].w};
#pragma unroll
                for (int e = 0; e < 4; e++) { keep[8 * i + 2 * e] += __uint_as_float(u[e] << 16); keep[8 * i + 2 * e + 1] += __uint_as_float(u[e] & 0xffff0000u); }
            }
            fence_regs(keep);
        }
        const uint32_t tb = sb + (warp >> 1) * SLOT + OFF_KV + (warp & 1) * 2560;
        const uint32_t trow = ((lane >> 3) & 1) * 8 + (lane & 7);
        uint8_t* op = (uint8_t*)(out + (size_t)(m * 128 + grp * 8) * DM);
        uint8_t* o1 = op + (lane >> 3) * (DM * 2) + nt * 256 + hf * 128 + (lane & 7) * 16;
        uint8_t* o2 = op + (lane >> 1) * (DM * 2) + 1024 + nt * 32 + (lane & 1) * 16;
        mbar_wait(bar_late, 0);
#pragma unroll 1
        for (int k = 2; k < 6; k++) {
            mbar_wait(bar_full + k * 8, 0);
            if (k == 2) PROF(15);
            const uint32_t bo = __shfl_sync(0xffffffffu, lds32(s_order + k * 4), 0);
            const uint64_t da = mkdesc<HI_A2>(sbd + k * (SLOT >> 4) + wg * 128 + dlo(OFF_A2, 128)), db = mkdesc<HI_W>(sbd + bo + dlo(0, 6144));
            wg_fence();
            GEMM_80(da, db, 1);
            wg_commit();
        }
        asm volatile("barrier.cluster.arrive.relaxed.aligned;" ::: "memory");
        wg_wait<0>();
        fence_regs(keep);
        PROF(16);
#pragma unroll
        for (int i = 0; i < 5; i++) {
            const uint32_t a = i < 4 ? tb + trow * 128 + (((2 * i + (lane >> 4)) ^ (lane & 7)) << 4) : tb + 2048 + trow * 32 + (lane >> 4) * 16;
            stsm4(a, pack(keep[8 * i], keep[8 * i + 1]), pack(keep[8 * i + 2], keep[8 * i + 3]), pack(keep[8 * i + 4], keep[8 * i + 5]), pack(keep[8 * i + 6], keep[8 * i + 7]));
        }
        __syncwarp();
        uint4 v[5];
#pragma unroll
        for (int i = 0; i < 5; i++) {
            const uint32_t r = 4 * i + (lane >> 3);
            const uint32_t a = i < 4 ? tb + r * 128 + (((lane & 7) ^ (r & 7)) << 4) : tb + 2048 + lane * 16;
            asm volatile("ld.shared.v4.u32 {%0, %1, %2, %3}, [%4];" : "=r"(v[i].x), "=r"(v[i].y), "=r"(v[i].z), "=r"(v[i].w) : "r"(a) : "memory");
        }
#pragma unroll
        for (int i = 0; i < 5; i++)
            asm volatile("{\n.reg .pred p;\nsetp.ne.s32 p, %5, 0;\n@p st.global.v4.u32 [%0], {%1, %2, %3, %4};\n}"
                         ::"l"(i < 4 ? o1 + i * 4 * (DM * 2) : o2), "r"(v[i].x), "r"(v[i].y), "r"(v[i].z), "r"(v[i].w), "r"(i < 4 ? 1 : (int)(wg == hf)) : "memory");
        PROF(20);
        asm volatile("barrier.cluster.wait.aligned;" ::: "memory");
    }
}

typedef CUresult (*EncodeFn)(CUtensorMap*, CUtensorMapDataType, cuuint32_t, void*, const cuuint64_t*, const cuuint64_t*,
                             const cuuint32_t*, const cuuint32_t*, CUtensorMapInterleave, CUtensorMapSwizzle,
                             CUtensorMapL2promotion, CUtensorMapFloatOOBfill);

CUtensorMap make_map(EncodeFn enc, const void* ptr, uint64_t inner, uint64_t outer, uint32_t box_inner, uint32_t box_outer, CUtensorMapSwizzle swz) {
    CUtensorMap t;
    cuuint64_t dims[2] = {inner, outer};
    cuuint64_t strides[1] = {inner * 2};
    cuuint32_t box[2] = {box_inner, box_outer};
    cuuint32_t es[2] = {1, 1};
    enc(&t, CU_TENSOR_MAP_DATA_TYPE_BFLOAT16, 2, const_cast<void*>(ptr), dims, strides, box, es, CU_TENSOR_MAP_INTERLEAVE_NONE, swz,
        CU_TENSOR_MAP_L2_PROMOTION_L2_128B, CU_TENSOR_MAP_FLOAT_OOB_FILL_NONE);
    return t;
}

CUtensorMap make_qkv_map(EncodeFn enc, const void* ptr, uint32_t width, CUtensorMapSwizzle swz) {
    CUtensorMap t;
    cuuint64_t dims[3] = {DM, DM, 3};
    cuuint64_t strides[2] = {3 * DM * 2, DM * 2};
    cuuint32_t box[3] = {width, 16, 3};
    cuuint32_t es[3] = {1, 1, 1};
    enc(&t, CU_TENSOR_MAP_DATA_TYPE_BFLOAT16, 3, const_cast<void*>(ptr), dims, strides, box, es, CU_TENSOR_MAP_INTERLEAVE_NONE, swz,
        CU_TENSOR_MAP_L2_PROMOTION_L2_128B, CU_TENSOR_MAP_FLOAT_OOB_FILL_NONE);
    return t;
}

}

extern "C" void kernel_launch(void* const* d_in, const int* in_sizes, int n_in, void* d_out, int out_size) {
    (void)in_sizes; (void)n_in; (void)out_size;
    void* fn = nullptr;
    cudaDriverEntryPointQueryResult qr;
    cudaGetDriverEntryPoint("cuTensorMapEncodeTiled", &fn, cudaEnableDefault, &qr);
    EncodeFn enc = (EncodeFn)fn;
    const CUtensorMap tm_x = make_map(enc, d_in[0], DM, SEQ, 32, 128, CU_TENSOR_MAP_SWIZZLE_64B);
    const CUtensorMap tm_qkv = make_qkv_map(enc, d_in[1], 64, CU_TENSOR_MAP_SWIZZLE_128B);
    const CUtensorMap tm_qkv8 = make_qkv_map(enc, d_in[1], 8, CU_TENSOR_MAP_SWIZZLE_NONE);
    const CUtensorMap tm_wo = make_map(enc, d_in[2], DM, DM, 64, 24, CU_TENSOR_MAP_SWIZZLE_128B);
    const CUtensorMap tm_wg = make_map(enc, d_in[4], FF, DM, 64, 32, CU_TENSOR_MAP_SWIZZLE_128B);
    const CUtensorMap tm_wu = make_map(enc, d_in[5], FF, DM, 64, 32, CU_TENSOR_MAP_SWIZZLE_128B);
    const CUtensorMap tm_wd = make_map(enc, d_in[6], DM, FF, 64, 24, CU_TENSOR_MAP_SWIZZLE_128B);
    const CUtensorMap tm_wd16 = make_map(enc, d_in[6], DM, FF, 16, 24, CU_TENSOR_MAP_SWIZZLE_128B);
    const CUtensorMap tm_wo16 = make_map(enc, d_in[2], DM, DM, 16, 24, CU_TENSOR_MAP_SWIZZLE_128B);
    cudaFuncSetAttribute(fused_kernel, cudaFuncAttributeMaxDynamicSharedMemorySize, SMEM_BYTES);
    fused_kernel<<<NCTA + 4, 384, SMEM_BYTES>>>((__nv_bfloat16*)d_out, (const __nv_bfloat16*)d_in[0], (const __nv_bfloat16*)d_in[7],
                                               tm_x, tm_qkv, tm_qkv8, tm_wg, tm_wu, tm_wd, tm_wo, tm_wd16, tm_wo16);
}
```

```cpp
#include <cuda_runtime.h>
#include <cuda.h>
#include <cuda_bf16.h>
#include <stdint.h>


namespace {

constexpr int SEQ = 2048, DM = 576, FF = 4608;
constexpr int NCTA = 128;
constexpr int NSTAGE = 6;
constexpr int E0 = 2;
constexpr int DEFER = 2;
constexpr int SLOT = 35 * 1024;
constexpr int OFF_AX = 22528;
constexpr int OFF_A2 = 18432;
constexpr int OFF_TL = 20480;
constexpr int OFF_GAP = 16384;
constexpr int OFF_KV = 30720;
constexpr int OFF_Q = NSTAGE * SLOT - 4608;
constexpr int OFF_BAR = NSTAGE * SLOT + 3 * 4608;
constexpr int SMEM_BYTES = OFF_BAR + 1024 + 1024;

constexpr int STRIPB = 48 * 32;
constexpr int HEAD_BYTES = 256 * 640;
constexpr int A2_TILE = 336 * 4096;

constexpr int FL_KV = 0;
constexpr int FL_M = FL_KV + 8 * 32;
constexpr int FM_H = 0;
constexpr int FM_LATE = 7;
constexpr int FM_R = 16;
constexpr int FL_G = FL_M + 16 * 64;
constexpr int FL_E = FL_G + 4 * 32;
constexpr int FL_N = FL_E + (NCTA + 4) * 32;

__device__ __align__(1024) uint8_t g_kv[32 * HEAD_BYTES];
__device__ __align__(1024) uint8_t g_a2[16 * A2_TILE];
__device__ __align__(1024) uint4 g_part[NCTA * 2 * 5 * 128];
__device__ __align__(1024) uint8_t g_q3[NCTA * 4608];
__device__ __align__(1024) float4 g_px[NCTA * 2 * 3 * 128];
__device__ __align__(512) float g_gate[SEQ];
__device__ __align__(256) uint32_t g_flags[FL_N];

template <uint32_t BHI>
__device__ __forceinline__ void wgmma_rs_n24_t1(float (&d)[12], uint32_t a0, uint32_t a1, uint32_t a2, uint32_t a3, uint32_t db, int scale_d) {
  asm volatile("{\n.reg .pred p;\n.reg .b64 da, db;\n"
    "mov.b64 db, {%16, %18};\n"
    "setp.ne.b32 p, %17, 0;\n"
    "wgmma.mma_async.sync.aligned.m64n24k16.f32.bf16.bf16 "
    "{%0, %1, %2, %3, %4, %5, %6, %7, %8, %9, %10, %11}, "
    "{%12, %13, %14, %15}, db, p, 1, 1, 1;\n}\n"
    : "+f"(d[0]), "+f"(d[1]), "+f"(d[2]), "+f"(d[3]), "+f"(d[4]), "+f"(d[5]), "+f"(d[6]), "+f"(d[7]),
      "+f"(d[8]), "+f"(d[9]), "+f"(d[10]), "+f"(d[11])
    : "r"(a0), "r"(a1), "r"(a2), "r"(a3), "r"(db), "r"(scale_d), "n"(BHI));
}
template <uint32_t BHI>
__device__ __forceinline__ void wgmma_rs_n128_t0(float (&d)[64], uint32_t a0, uint32_t a1, uint32_t a2, uint32_t a3, uint32_t db, int scale_d) {
  asm volatile("{\n.reg .pred p;\n.reg .b64 da, db;\n"
    "mov.b64 db, {%68, %70};\n"
    "setp.ne.b32 p, %69, 0;\n"
    "wgmma.mma_async.sync.aligned.m64n128k16.f32.bf16.bf16 "
    "{%0, %1, %2, %3, %4, %5, %6, %7, %8, %9, %10, %11, %12, %13, %14, %15, "
    "%16, %17, %18, %19, %20, %21, %22, %23, %24, %25, %26, %27, %28, %29, %30, %31, "
    "%32, %33, %34, %35, %36, %37, %38, %39, %40, %41, %42, %43, %44, %45, %46, %47, "
    "%48, %49, %50, %51, %52, %53, %54, %55, %56, %57, %58, %59, %60, %61, %62, %63}, "
    "{%64, %65, %66, %67}, db, p, 1, 1, 0;\n}\n"
    : "+f"(d[0]), "+f"(d[1]), "+f"(d[2]), "+f"(d[3]), "+f"(d[4]), "+f"(d[5]), "+f"(d[6]), "+f"(d[7]),
      "+f"(d[8]), "+f"(d[9]), "+f"(d[10]), "+f"(d[11]), "+f"(d[12]), "+f"(d[13]), "+f"(d[14]), "+f"(d[15]),
      "+f"(d[16]), "+f"(d[17]), "+f"(d[18]), "+f"(d[19]), "+f"(d[20]), "+f"(d[21]), "+f"(d[22]), "+f"(d[23]),
      "+f"(d[24]), "+f"(d[25]), "+f"(d[26]), "+f"(d[27]), "+f"(d[28]), "+f"(d[29]), "+f"(d[30]), "+f"(d[31]),
      "+f"(d[32]), "+f"(d[33]), "+f"(d[34]), "+f"(d[35]), "+f"(d[36]), "+f"(d[37]), "+f"(d[38]), "+f"(d[39]),
      "+f"(d[40]), "+f"(d[41]), "+f"(d[42]), "+f"(d[43]), "+f"(d[44]), "+f"(d[45]), "+f"(d[46]), "+f"(d[47]),
      "+f"(d[48]), "+f"(d[49]), "+f"(d[50]), "+f"(d[51]), "+f"(d[52]), "+f"(d[53]), "+f"(d[54]), "+f"(d[55]),
      "+f"(d[56]), "+f"(d[57]), "+f"(d[58]), "+f"(d[59]), "+f"(d[60]), "+f"(d[61]), "+f"(d[62]), "+f"(d[63])
    : "r"(a0), "r"(a1), "r"(a2), "r"(a3), "r"(db), "r"(scale_d), "n"(BHI));
}
template <uint32_t BHI>
__device__ __forceinline__ void wgmma_rs_n128_t1(float (&d)[64], uint32_t a0, uint32_t a1, uint32_t a2, uint32_t a3, uint32_t db, int scale_d) {
  asm volatile("{\n.reg .pred p;\n.reg .b64 da, db;\n"
    "mov.b64 db, {%68, %70};\n"
    "setp.ne.b32 p, %69, 0;\n"
    "wgmma.mma_async.sync.aligned.m64n128k16.f32.bf16.bf16 "
    "{%0, %1, %2, %3, %4, %5, %6, %7, %8, %9, %10, %11, %12, %13, %14, %15, "
    "%16, %17, %18, %19, %20, %21, %22, %23, %24, %25, %26, %27, %28, %29, %30, %31, "
    "%32, %33, %34, %35, %36, %37, %38, %39, %40, %41, %42, %43, %44, %45, %46, %47, "
    "%48, %49, %50, %51, %52, %53, %54, %55, %56, %57, %58, %59, %60, %61, %62, %63}, "
    "{%64, %65, %66, %67}, db, p, 1, 1, 1;\n}\n"
    : "+f"(d[0]), "+f"(d[1]), "+f"(d[2]), "+f"(d[3]), "+f"(d[4]), "+f"(d[5]), "+f"(d[6]), "+f"(d[7]),
      "+f"(d[8]), "+f"(d[9]), "+f"(d[10]), "+f"(d[11]), "+f"(d[12]), "+f"(d[13]), "+f"(d[14]), "+f"(d[15]),
      "+f"(d[16]), "+f"(d[17]), "+f"(d[18]), "+f"(d[19]), "+f"(d[20]), "+f"(d[21]), "+f"(d[22]), "+f"(d[23]),
      "+f"(d[24]), "+f"(d[25]), "+f"(d[26]), "+f"(d[27]), "+f"(d[28]), "+f"(d[29]), "+f"(d[30]), "+f"(d[31]),
      "+f"(d[32]), "+f"(d[33]), "+f"(d[34]), "+f"(d[35]), "+f"(d[36]), "+f"(d[37]), "+f"(d[38]), "+f"(d[39]),
      "+f"(d[40]), "+f"(d[41]), "+f"(d[42]), "+f"(d[43]), "+f"(d[44]), "+f"(d[45]), "+f"(d[46]), "+f"(d[47]),
      "+f"(d[48]), "+f"(d[49]), "+f"(d[50]), "+f"(d[51]), "+f"(d[52]), "+f"(d[53]), "+f"(d[54]), "+f"(d[55]),
      "+f"(d[56]), "+f"(d[57]), "+f"(d[58]), "+f"(d[59]), "+f"(d[60]), "+f"(d[61]), "+f"(d[62]), "+f"(d[63])
    : "r"(a0), "r"(a1), "r"(a2), "r"(a3), "r"(db), "r"(scale_d), "n"(BHI));
}
template <uint32_t BHI>
__device__ __forceinline__ void wgmma_rs_n192_t1(float (&d)[96], uint32_t a0, uint32_t a1, uint32_t a2, uint32_t a3, uint32_t db, int scale_d) {
  asm volatile("{\n.reg .pred p;\n.reg .b64 da, db;\n"
    "mov.b64 db, {%100, %102};\n"
    "setp.ne.b32 p, %101, 0;\n"
    "wgmma.mma_async.sync.aligned.m64n192k16.f32.bf16.bf16 "
    "{%0, %1, %2, %3, %4, %5, %6, %7, %8, %9, %10, %11, %12, %13, %14, %15, "
    "%16, %17, %18, %19, %20, %21, %22, %23, %24, %25, %26, %27, %28, %29, %30, %31, "
    "%32, %33, %34, %35, %36, %37, %38, %39, %40, %41, %42, %43, %44, %45, %46, %47, "
    "%48, %49, %50, %51, %52, %53, %54, %55, %56, %57, %58, %59, %60, %61, %62, %63, "
    "%64, %65, %66, %67, %68, %69, %70, %71, %72, %73, %74, %75, %76, %77, %78, %79, "
    "%80, %81, %82, %83, %84, %85, %86, %87, %88, %89, %90, %91, %92, %93, %94, %95}, "
    "{%96, %97, %98, %99}, db, p, 1, 1, 1;\n}\n"
    : "+f"(d[0]), "+f"(d[1]), "+f"(d[2]), "+f"(d[3]), "+f"(d[4]), "+f"(d[5]), "+f"(d[6]), "+f"(d[7]),
      "+f"(d[8]), "+f"(d[9]), "+f"(d[10]), "+f"(d[11]), "+f"(d[12]), "+f"(d[13]), "+f"(d[14]), "+f"(d[15]),
      "+f"(d[16]), "+f"(d[17]), "+f"(d[18]), "+f"(d[19]), "+f"(d[20]), "+f"(d[21]), "+f"(d[22]), "+f"(d[23]),
      "+f"(d[24]), "+f"(d[25]), "+f"(d[26]), "+f"(d[27]), "+f"(d[28]), "+f"(d[29]), "+f"(d[30]), "+f"(d[31]),
      "+f"(d[32]), "+f"(d[33]), "+f"(d[34]), "+f"(d[35]), "+f"(d[36]), "+f"(d[37]), "+f"(d[38]), "+f"(d[39]),
      "+f"(d[40]), "+f"(d[41]), "+f"(d[42]), "+f"(d[43]), "+f"(d[44]), "+f"(d[45]), "+f"(d[46]), "+f"(d[47]),
      "+f"(d[48]), "+f"(d[49]), "+f"(d[50]), "+f"(d[51]), "+f"(d[52]), "+f"(d[53]), "+f"(d[54]), "+f"(d[55]),
      "+f"(d[56]), "+f"(d[57]), "+f"(d[58]), "+f"(d[59]), "+f"(d[60]), "+f"(d[61]), "+f"(d[62]), "+f"(d[63]),
      "+f"(d[64]), "+f"(d[65]), "+f"(d[66]), "+f"(d[67]), "+f"(d[68]), "+f"(d[69]), "+f"(d[70]), "+f"(d[71]),
      "+f"(d[72]), "+f"(d[73]), "+f"(d[74]), "+f"(d[75]), "+f"(d[76]), "+f"(d[77]), "+f"(d[78]), "+f"(d[79]),
      "+f"(d[80]), "+f"(d[81]), "+f"(d[82]), "+f"(d[83]), "+f"(d[84]), "+f"(d[85]), "+f"(d[86]), "+f"(d[87]),
      "+f"(d[88]), "+f"(d[89]), "+f"(d[90]), "+f"(d[91]), "+f"(d[92]), "+f"(d[93]), "+f"(d[94]), "+f"(d[95])
    : "r"(a0), "r"(a1), "r"(a2), "r"(a3), "r"(db), "r"(scale_d), "n"(BHI));
}
template <uint32_t AHI, uint32_t BHI>
__device__ __forceinline__ void wgmma_ss_n24_t1(float (&d)[12], uint32_t da, uint32_t db, int scale_d) {
  asm volatile("{\n.reg .pred p;\n.reg .b64 da, db;\n"
    "mov.b64 da, {%12, %15};\nmov.b64 db, {%13, %16};\n"
    "setp.ne.b32 p, %14, 0;\n"
    "wgmma.mma_async.sync.aligned.m64n24k16.f32.bf16.bf16 "
    "{%0, %1, %2, %3, %4, %5, %6, %7, %8, %9, %10, %11}, "
    "da, db, p, 1, 1, 0, 1;\n}\n"
    : "+f"(d[0]), "+f"(d[1]), "+f"(d[2]), "+f"(d[3]), "+f"(d[4]), "+f"(d[5]), "+f"(d[6]), "+f"(d[7]),
      "+f"(d[8]), "+f"(d[9]), "+f"(d[10]), "+f"(d[11])
    : "r"(da), "r"(db), "r"(scale_d), "n"(AHI), "n"(BHI));
}
template <uint32_t AHI, uint32_t BHI>
__device__ __forceinline__ void wgmma_ss_n128_t1(float (&d)[64], uint32_t da, uint32_t db, int scale_d) {
  asm volatile("{\n.reg .pred p;\n.reg .b64 da, db;\n"
    "mov.b64 da, {%64, %67};\nmov.b64 db, {%65, %68};\n"
    "setp.ne.b32 p, %66, 0;\n"
    "wgmma.mma_async.sync.aligned.m64n128k16.f32.bf16.bf16 "
    "{%0, %1, %2, %3, %4, %5, %6, %7, %8, %9, %10, %11, %12, %13, %14, %15, "
    "%16, %17, %18, %19, %20, %21, %22, %23, %24, %25, %26, %27, %28, %29, %30, %31, "
    "%32, %33, %34, %35, %36, %37, %38, %39, %40, %41, %42, %43, %44, %45, %46, %47, "
    "%48, %49, %50, %51, %52, %53, %54, %55, %56, %57, %58, %59, %60, %61, %62, %63}, "
    "da, db, p, 1, 1, 0, 1;\n}\n"
    : "+f"(d[0]), "+f"(d[1]), "+f"(d[2]), "+f"(d[3]), "+f"(d[4]), "+f"(d[5]), "+f"(d[6]), "+f"(d[7]),
      "+f"(d[8]), "+f"(d[9]), "+f"(d[10]), "+f"(d[11]), "+f"(d[12]), "+f"(d[13]), "+f"(d[14]), "+f"(d[15]),
      "+f"(d[16]), "+f"(d[17]), "+f"(d[18]), "+f"(d[19]), "+f"(d[20]), "+f"(d[21]), "+f"(d[22]), "+f"(d[23]),
      "+f"(d[24]), "+f"(d[25]), "+f"(d[26]), "+f"(d[27]), "+f"(d[28]), "+f"(d[29]), "+f"(d[30]), "+f"(d[31]),
      "+f"(d[32]), "+f"(d[33]), "+f"(d[34]), "+f"(d[35]), "+f"(d[36]), "+f"(d[37]), "+f"(d[38]), "+f"(d[39]),
      "+f"(d[40]), "+f"(d[41]), "+f"(d[42]), "+f"(d[43]), "+f"(d[44]), "+f"(d[45]), "+f"(d[46]), "+f"(d[47]),
      "+f"(d[48]), "+f"(d[49]), "+f"(d[50]), "+f"(d[51]), "+f"(d[52]), "+f"(d[53]), "+f"(d[54]), "+f"(d[55]),
      "+f"(d[56]), "+f"(d[57]), "+f"(d[58]), "+f"(d[59]), "+f"(d[60]), "+f"(d[61]), "+f"(d[62]), "+f"(d[63])
    : "r"(da), "r"(db), "r"(scale_d), "n"(AHI), "n"(BHI));
}
template <uint32_t AHI, uint32_t BHI>
__device__ __forceinline__ void wgmma_ss_n192_t1(float (&d)[96], uint32_t da, uint32_t db, int scale_d) {
  asm volatile("{\n.reg .pred p;\n.reg .b64 da, db;\n"
    "mov.b64 da, {%96, %99};\nmov.b64 db, {%97, %100};\n"
    "setp.ne.b32 p, %98, 0;\n"
    "wgmma.mma_async.sync.aligned.m64n192k16.f32.bf16.bf16 "
    "{%0, %1, %2, %3, %4, %5, %6, %7, %8, %9, %10, %11, %12, %13, %14, %15, "
    "%16, %17, %18, %19, %20, %21, %22, %23, %24, %25, %26, %27, %28, %29, %30, %31, "
    "%32, %33, %34, %35, %36, %37, %38, %39, %40, %41, %42, %43, %44, %45, %46, %47, "
    "%48, %49, %50, %51, %52, %53, %54, %55, %56, %57, %58, %59, %60, %61, %62, %63, "
    "%64, %65, %66, %67, %68, %69, %70, %71, %72, %73, %74, %75, %76, %77, %78, %79, "
    "%80, %81, %82, %83, %84, %85, %86, %87, %88, %89, %90, %91, %92, %93, %94, %95}, "
    "da, db, p, 1, 1, 0, 1;\n}\n"
    : "+f"(d[0]), "+f"(d[1]), "+f"(d[2]), "+f"(d[3]), "+f"(d[4]), "+f"(d[5]), "+f"(d[6]), "+f"(d[7]),
      "+f"(d[8]), "+f"(d[9]), "+f"(d[10]), "+f"(d[11]), "+f"(d[12]), "+f"(d[13]), "+f"(d[14]), "+f"(d[15]),
      "+f"(d[16]), "+f"(d[17]), "+f"(d[18]), "+f"(d[19]), "+f"(d[20]), "+f"(d[21]), "+f"(d[22]), "+f"(d[23]),
      "+f"(d[24]), "+f"(d[25]), "+f"(d[26]), "+f"(d[27]), "+f"(d[28]), "+f"(d[29]), "+f"(d[30]), "+f"(d[31]),
      "+f"(d[32]), "+f"(d[33]), "+f"(d[34]), "+f"(d[35]), "+f"(d[36]), "+f"(d[37]), "+f"(d[38]), "+f"(d[39]),
      "+f"(d[40]), "+f"(d[41]), "+f"(d[42]), "+f"(d[43]), "+f"(d[44]), "+f"(d[45]), "+f"(d[46]), "+f"(d[47]),
      "+f"(d[48]), "+f"(d[49]), "+f"(d[50]), "+f"(d[51]), "+f"(d[52]), "+f"(d[53]), "+f"(d[54]), "+f"(d[55]),
      "+f"(d[56]), "+f"(d[57]), "+f"(d[58]), "+f"(d[59]), "+f"(d[60]), "+f"(d[61]), "+f"(d[62]), "+f"(d[63]),
      "+f"(d[64]), "+f"(d[65]), "+f"(d[66]), "+f"(d[67]), "+f"(d[68]), "+f"(d[69]), "+f"(d[70]), "+f"(d[71]),
      "+f"(d[72]), "+f"(d[73]), "+f"(d[74]), "+f"(d[75]), "+f"(d[76]), "+f"(d[77]), "+f"(d[78]), "+f"(d[79]),
      "+f"(d[80]), "+f"(d[81]), "+f"(d[82]), "+f"(d[83]), "+f"(d[84]), "+f"(d[85]), "+f"(d[86]), "+f"(d[87]),
      "+f"(d[88]), "+f"(d[89]), "+f"(d[90]), "+f"(d[91]), "+f"(d[92]), "+f"(d[93]), "+f"(d[94]), "+f"(d[95])
    : "r"(da), "r"(db), "r"(scale_d), "n"(AHI), "n"(BHI));
}
template <uint32_t AHI, uint32_t BHI>
__device__ __forceinline__ void wgmma_ss_n256_t1(float (&d)[128], uint32_t da, uint32_t db, int scale_d) {
  asm volatile("{\n.reg .pred p;\n.reg .b64 da, db;\n"
    "mov.b64 da, {%128, %131};\nmov.b64 db, {%129, %132};\n"
    "setp.ne.b32 p, %130, 0;\n"
    "wgmma.mma_async.sync.aligned.m64n256k16.f32.bf16.bf16 "
    "{%0, %1, %2, %3, %4, %5, %6, %7, %8, %9, %10, %11, %12, %13, %14, %15, "
    "%16, %17, %18, %19, %20, %21, %22, %23, %24, %25, %26, %27, %28, %29, %30, %31, "
    "%32, %33, %34, %35, %36, %37, %38, %39, %40, %41, %42, %43, %44, %45, %46, %47, "
    "%48, %49, %50, %51, %52, %53, %54, %55, %56, %57, %58, %59, %60, %61, %62, %63, "
    "%64, %65, %66, %67, %68, %69, %70, %71, %72, %73, %74, %75, %76, %77, %78, %79, "
    "%80, %81, %82, %83, %84, %85, %86, %87, %88, %89, %90, %91, %92, %93, %94, %95, "
    "%96, %97, %98, %99, %100, %101, %102, %103, %104, %105, %106, %107, %108, %109, %110, %111, "
    "%112, %113, %114, %115, %116, %117, %118, %119, %120, %121, %122, %123, %124, %125, %126, %127}, "
    "da, db, p, 1, 1, 0, 1;\n}\n"
    : "+f"(d[0]), "+f"(d[1]), "+f"(d[2]), "+f"(d[3]), "+f"(d[4]), "+f"(d[5]), "+f"(d[6]), "+f"(d[7]),
      "+f"(d[8]), "+f"(d[9]), "+f"(d[10]), "+f"(d[11]), "+f"(d[12]), "+f"(d[13]), "+f"(d[14]), "+f"(d[15]),
      "+f"(d[16]), "+f"(d[17]), "+f"(d[18]), "+f"(d[19]), "+f"(d[20]), "+f"(d[21]), "+f"(d[22]), "+f"(d[23]),
      "+f"(d[24]), "+f"(d[25]), "+f"(d[26]), "+f"(d[27]), "+f"(d[28]), "+f"(d[29]), "+f"(d[30]), "+f"(d[31]),
      "+f"(d[32]), "+f"(d[33]), "+f"(d[34]), "+f"(d[35]), "+f"(d[36]), "+f"(d[37]), "+f"(d[38]), "+f"(d[39]),
      "+f"(d[40]), "+f"(d[41]), "+f"(d[42]), "+f"(d[43]), "+f"(d[44]), "+f"(d[45]), "+f"(d[46]), "+f"(d[47]),
      "+f"(d[48]), "+f"(d[49]), "+f"(d[50]), "+f"(d[51]), "+f"(d[52]), "+f"(d[53]), "+f"(d[54]), "+f"(d[55]),
      "+f"(d[56]), "+f"(d[57]), "+f"(d[58]), "+f"(d[59]), "+f"(d[60]), "+f"(d[61]), "+f"(d[62]), "+f"(d[63]),
      "+f"(d[64]), "+f"(d[65]), "+f"(d[66]), "+f"(d[67]), "+f"(d[68]), "+f"(d[69]), "+f"(d[70]), "+f"(d[71]),
      "+f"(d[72]), "+f"(d[73]), "+f"(d[74]), "+f"(d[75]), "+f"(d[76]), "+f"(d[77]), "+f"(d[78]), "+f"(d[79]),
      "+f"(d[80]), "+f"(d[81]), "+f"(d[82]), "+f"(d[83]), "+f"(d[84]), "+f"(d[85]), "+f"(d[86]), "+f"(d[87]),
      "+f"(d[88]), "+f"(d[89]), "+f"(d[90]), "+f"(d[91]), "+f"(d[92]), "+f"(d[93]), "+f"(d[94]), "+f"(d[95]),
      "+f"(d[96]), "+f"(d[97]), "+f"(d[98]), "+f"(d[99]), "+f"(d[100]), "+f"(d[101]), "+f"(d[102]), "+f"(d[103]),
      "+f"(d[104]), "+f"(d[105]), "+f"(d[106]), "+f"(d[107]), "+f"(d[108]), "+f"(d[109]), "+f"(d[110]), "+f"(d[111]),
      "+f"(d[112]), "+f"(d[113]), "+f"(d[114]), "+f"(d[115]), "+f"(d[116]), "+f"(d[117]), "+f"(d[118]), "+f"(d[119]),
      "+f"(d[120]), "+f"(d[121]), "+f"(d[122]), "+f"(d[123]), "+f"(d[124]), "+f"(d[125]), "+f"(d[126]), "+f"(d[127])
    : "r"(da), "r"(db), "r"(scale_d), "n"(AHI), "n"(BHI));
}
__device__ __forceinline__ void wgmma6_rs_n24_t1(float (&d)[12], uint32_t a0, uint32_t a1, uint32_t a2, uint32_t a3, uint64_t db, int scale_d) {
  asm volatile("{\n.reg .pred p;\n"
    "setp.ne.b32 p, %17, 0;\n"
    "wgmma.mma_async.sync.aligned.m64n24k16.f32.bf16.bf16 "
    "{%0, %1, %2, %3, %4, %5, %6, %7, %8, %9, %10, %11}, "
    "{%12, %13, %14, %15}, %16, p, 1, 1, 1;\n}\n"
    : "+f"(d[0]), "+f"(d[1]), "+f"(d[2]), "+f"(d[3]), "+f"(d[4]), "+f"(d[5]), "+f"(d[6]), "+f"(d[7]),
      "+f"(d[8]), "+f"(d[9]), "+f"(d[10]), "+f"(d[11])
    : "r"(a0), "r"(a1), "r"(a2), "r"(a3), "l"(db), "r"(scale_d));
}
__device__ __forceinline__ void wgmma6_rs_n64_t0(float (&d)[32], uint32_t a0, uint32_t a1, uint32_t a2, uint32_t a3, uint64_t db, int scale_d) {
  asm volatile("{\n.reg .pred p;\n"
    "setp.ne.b32 p, %37, 0;\n"
    "wgmma.mma_async.sync.aligned.m64n64k16.f32.bf16.bf16 "
    "{%0, %1, %2, %3, %4, %5, %6, %7, %8, %9, %10, %11, %12, %13, %14, %15, "
    "%16, %17, %18, %19, %20, %21, %22, %23, %24, %25, %26, %27, %28, %29, %30, %31}, "
    "{%32, %33, %34, %35}, %36, p, 1, 1, 0;\n}\n"
    : "+f"(d[0]), "+f"(d[1]), "+f"(d[2]), "+f"(d[3]), "+f"(d[4]), "+f"(d[5]), "+f"(d[6]), "+f"(d[7]),
      "+f"(d[8]), "+f"(d[9]), "+f"(d[10]), "+f"(d[11]), "+f"(d[12]), "+f"(d[13]), "+f"(d[14]), "+f"(d[15]),
      "+f"(d[16]), "+f"(d[17]), "+f"(d[18]), "+f"(d[19]), "+f"(d[20]), "+f"(d[21]), "+f"(d[22]), "+f"(d[23]),
      "+f"(d[24]), "+f"(d[25]), "+f"(d[26]), "+f"(d[27]), "+f"(d[28]), "+f"(d[29]), "+f"(d[30]), "+f"(d[31])
    : "r"(a0), "r"(a1), "r"(a2), "r"(a3), "l"(db), "r"(scale_d));
}
__device__ __forceinline__ void wgmma6_ss_n80_t1(float (&d)[40], uint64_t da, uint64_t db, int scale_d) {
  asm volatile("{\n.reg .pred p;\n"
    "setp.ne.b32 p, %42, 0;\n"
    "wgmma.mma_async.sync.aligned.m64n80k16.f32.bf16.bf16 "
    "{%0, %1, %2, %3, %4, %5, %6, %7, %8, %9, %10, %11, %12, %13, %14, %15, "
    "%16, %17, %18, %19, %20, %21, %22, %23, %24, %25, %26, %27, %28, %29, %30, %31, "
    "%32, %33, %34, %35, %36, %37, %38, %39}, "
    "%40, %41, p, 1, 1, 0, 1;\n}\n"
    : "+f"(d[0]), "+f"(d[1]), "+f"(d[2]), "+f"(d[3]), "+f"(d[4]), "+f"(d[5]), "+f"(d[6]), "+f"(d[7]),
      "+f"(d[8]), "+f"(d[9]), "+f"(d[10]), "+f"(d[11]), "+f"(d[12]), "+f"(d[13]), "+f"(d[14]), "+f"(d[15]),
      "+f"(d[16]), "+f"(d[17]), "+f"(d[18]), "+f"(d[19]), "+f"(d[20]), "+f"(d[21]), "+f"(d[22]), "+f"(d[23]),
      "+f"(d[24]), "+f"(d[25]), "+f"(d[26]), "+f"(d[27]), "+f"(d[28]), "+f"(d[29]), "+f"(d[30]), "+f"(d[31]),
      "+f"(d[32]), "+f"(d[33]), "+f"(d[34]), "+f"(d[35]), "+f"(d[36]), "+f"(d[37]), "+f"(d[38]), "+f"(d[39])
    : "l"(da), "l"(db), "r"(scale_d));
}
__device__ __forceinline__ void wgmma6_ss_n144_t1(float (&d)[72], uint64_t da, uint64_t db, int scale_d) {
  asm volatile("{\n.reg .pred p;\n"
    "setp.ne.b32 p, %74, 0;\n"
    "wgmma.mma_async.sync.aligned.m64n144k16.f32.bf16.bf16 "
    "{%0, %1, %2, %3, %4, %5, %6, %7, %8, %9, %10, %11, %12, %13, %14, %15, "
    "%16, %17, %18, %19, %20, %21, %22, %23, %24, %25, %26, %27, %28, %29, %30, %31, "
    "%32, %33, %34, %35, %36, %37, %38, %39, %40, %41, %42, %43, %44, %45, %46, %47, "
    "%48, %49, %50, %51, %52, %53, %54, %55, %56, %57, %58, %59, %60, %61, %62, %63, "
    "%64, %65, %66, %67, %68, %69, %70, %71}, "
    "%72, %73, p, 1, 1, 0, 1;\n}\n"
    : "+f"(d[0]), "+f"(d[1]), "+f"(d[2]), "+f"(d[3]), "+f"(d[4]), "+f"(d[5]), "+f"(d[6]), "+f"(d[7]),
      "+f"(d[8]), "+f"(d[9]), "+f"(d[10]), "+f"(d[11]), "+f"(d[12]), "+f"(d[13]), "+f"(d[14]), "+f"(d[15]),
      "+f"(d[16]), "+f"(d[17]), "+f"(d[18]), "+f"(d[19]), "+f"(d[20]), "+f"(d[21]), "+f"(d[22]), "+f"(d[23]),
      "+f"(d[24]), "+f"(d[25]), "+f"(d[26]), "+f"(d[27]), "+f"(d[28]), "+f"(d[29]), "+f"(d[30]), "+f"(d[31]),
      "+f"(d[32]), "+f"(d[33]), "+f"(d[34]), "+f"(d[35]), "+f"(d[36]), "+f"(d[37]), "+f"(d[38]), "+f"(d[39]),
      "+f"(d[40]), "+f"(d[41]), "+f"(d[42]), "+f"(d[43]), "+f"(d[44]), "+f"(d[45]), "+f"(d[46]), "+f"(d[47]),
      "+f"(d[48]), "+f"(d[49]), "+f"(d[50]), "+f"(d[51]), "+f"(d[52]), "+f"(d[53]), "+f"(d[54]), "+f"(d[55]),
      "+f"(d[56]), "+f"(d[57]), "+f"(d[58]), "+f"(d[59]), "+f"(d[60]), "+f"(d[61]), "+f"(d[62]), "+f"(d[63]),
      "+f"(d[64]), "+f"(d[65]), "+f"(d[66]), "+f"(d[67]), "+f"(d[68]), "+f"(d[69]), "+f"(d[70]), "+f"(d[71])
    : "l"(da), "l"(db), "r"(scale_d));
}
__device__ __forceinline__ void wgmma6_ss_n256_t1(float (&d)[128], uint64_t da, uint64_t db, int scale_d) {
  asm volatile("{\n.reg .pred p;\n"
    "setp.ne.b32 p, %130, 0;\n"
    "wgmma.mma_async.sync.aligned.m64n256k16.f32.bf16.bf16 "
    "{%0, %1, %2, %3, %4, %5, %6, %7, %8, %9, %10, %11, %12, %13, %14, %15, "
    "%16, %17, %18, %19, %20, %21, %22, %23, %24, %25, %26, %27, %28, %29, %30, %31, "
    "%32, %33, %34, %35, %36, %37, %38, %39, %40, %41, %42, %43, %44, %45, %46, %47, "
    "%48, %49, %50, %51, %52, %53, %54, %55, %56, %57, %58, %59, %60, %61, %62, %63, "
    "%64, %65, %66, %67, %68, %69, %70, %71, %72, %73, %74, %75, %76, %77, %78, %79, "
    "%80, %81, %82, %83, %84, %85, %86, %87, %88, %89, %90, %91, %92, %93, %94, %95, "
    "%96, %97, %98, %99, %100, %101, %102, %103, %104, %105, %106, %107, %108, %109, %110, %111, "
    "%112, %113, %114, %115, %116, %117, %118, %119, %120, %121, %122, %123, %124, %125, %126, %127}, "
    "%128, %129, p, 1, 1, 0, 1;\n}\n"
    : "+f"(d[0]), "+f"(d[1]), "+f"(d[2]), "+f"(d[3]), "+f"(d[4]), "+f"(d[5]), "+f"(d[6]), "+f"(d[7]),
      "+f"(d[8]), "+f"(d[9]), "+f"(d[10]), "+f"(d[11]), "+f"(d[12]), "+f"(d[13]), "+f"(d[14]), "+f"(d[15]),
      "+f"(d[16]), "+f"(d[17]), "+f"(d[18]), "+f"(d[19]), "+f"(d[20]), "+f"(d[21]), "+f"(d[22]), "+f"(d[23]),
      "+f"(d[24]), "+f"(d[25]), "+f"(d[26]), "+f"(d[27]), "+f"(d[28]), "+f"(d[29]), "+f"(d[30]), "+f"(d[31]),
      "+f"(d[32]), "+f"(d[33]), "+f"(d[34]), "+f"(d[35]), "+f"(d[36]), "+f"(d[37]), "+f"(d[38]), "+f"(d[39]),
      "+f"(d[40]), "+f"(d[41]), "+f"(d[42]), "+f"(d[43]), "+f"(d[44]), "+f"(d[45]), "+f"(d[46]), "+f"(d[47]),
      "+f"(d[48]), "+f"(d[49]), "+f"(d[50]), "+f"(d[51]), "+f"(d[52]), "+f"(d[53]), "+f"(d[54]), "+f"(d[55]),
      "+f"(d[56]), "+f"(d[57]), "+f"(d[58]), "+f"(d[59]), "+f"(d[60]), "+f"(d[61]), "+f"(d[62]), "+f"(d[63]),
      "+f"(d[64]), "+f"(d[65]), "+f"(d[66]), "+f"(d[67]), "+f"(d[68]), "+f"(d[69]), "+f"(d[70]), "+f"(d[71]),
      "+f"(d[72]), "+f"(d[73]), "+f"(d[74]), "+f"(d[75]), "+f"(d[76]), "+f"(d[77]), "+f"(d[78]), "+f"(d[79]),
      "+f"(d[80]), "+f"(d[81]), "+f"(d[82]), "+f"(d[83]), "+f"(d[84]), "+f"(d[85]), "+f"(d[86]), "+f"(d[87]),
      "+f"(d[88]), "+f"(d[89]), "+f"(d[90]), "+f"(d[91]), "+f"(d[92]), "+f"(d[93]), "+f"(d[94]), "+f"(d[95]),
      "+f"(d[96]), "+f"(d[97]), "+f"(d[98]), "+f"(d[99]), "+f"(d[100]), "+f"(d[101]), "+f"(d[102]), "+f"(d[103]),
      "+f"(d[104]), "+f"(d[105]), "+f"(d[106]), "+f"(d[107]), "+f"(d[108]), "+f"(d[109]), "+f"(d[110]), "+f"(d[111]),
      "+f"(d[112]), "+f"(d[113]), "+f"(d[114]), "+f"(d[115]), "+f"(d[116]), "+f"(d[117]), "+f"(d[118]), "+f"(d[119]),
      "+f"(d[120]), "+f"(d[121]), "+f"(d[122]), "+f"(d[123]), "+f"(d[124]), "+f"(d[125]), "+f"(d[126]), "+f"(d[127])
    : "l"(da), "l"(db), "r"(scale_d));
}

__device__ __forceinline__ void wg_fence() { asm volatile("wgmma.fence.sync.aligned;" ::: "memory"); }
__device__ __forceinline__ void wg_commit() { asm volatile("wgmma.commit_group.sync.aligned;" ::: "memory"); }
template <int N> __device__ __forceinline__ void wg_wait() { asm volatile("wgmma.wait_group.sync.aligned %0;" ::"n"(N) : "memory"); }
__host__ __device__ constexpr uint32_t dlo(uint32_t off, uint32_t lbo) { return (off >> 4) | ((lbo >> 4) << 16); }
__host__ __device__ constexpr uint32_t dhi(uint32_t sbo, uint32_t swz) { return (sbo >> 4) | (swz << 30); }
constexpr uint32_t HI_X = dhi(512, 2), HI_W = dhi(1024, 1), HI_A2 = dhi(256, 0), HI_K = dhi(640, 0), HI_V = dhi(128, 0), HI_T = dhi(256, 0);
constexpr uint32_t QB0 = dlo(8192, 2048), QB1 = QB0 + 384, QT1 = 48;
__device__ __forceinline__ float ex2(float x) { float y; asm volatile("ex2.approx.ftz.f32 %0, %1;" : "=f"(y) : "f"(x)); return y; }
template <uint32_t HI> __device__ __forceinline__ uint64_t mkdesc(uint32_t lo) {
    uint64_t d;
    asm("mov.b64 %0, {%1, %2};" : "=l"(d) : "r"(lo), "n"(HI));
    return d;
}
__device__ __forceinline__ float rcp_fast(float x) { float y; asm("rcp.approx.ftz.f32 %0, %1;" : "=f"(y) : "f"(x)); return y; }
__device__ __forceinline__ float tanh_fast(float x) { float y; asm("tanh.approx.f32 %0, %1;" : "=f"(y) : "f"(x)); return y; }
__device__ __forceinline__ uint32_t pack(float lo, float hi) { uint32_t y; asm("cvt.rn.bf16x2.f32 %0, %1, %2;" : "=r"(y) : "f"(hi), "f"(lo)); return y; }
template <int N> __device__ __forceinline__ void fence_regs(float (&d)[N]) {
#pragma unroll
    for (int i = 0; i < N; i++) asm volatile("" : "+f"(d[i])::"memory");
}
template <int N> __device__ __forceinline__ void fence_regs(uint32_t (&d)[N]) {
#pragma unroll
    for (int i = 0; i < N; i++) asm volatile("" : "+r"(d[i])::"memory");
}
template <int N> __device__ __forceinline__ void undef_regs(float (&d)[N]) {
#pragma unroll
    for (int i = 0; i < N; i++) asm volatile("" : "=f"(d[i]));
}
__device__ __forceinline__ void mbar_init(uint32_t bar, uint32_t cnt) { asm volatile("mbarrier.init.shared::cta.b64 [%0], %1;" ::"r"(bar), "r"(cnt) : "memory"); }
__device__ __forceinline__ void mbar_expect_tx(uint32_t bar, uint32_t bytes) { asm volatile("mbarrier.arrive.expect_tx.shared::cta.b64 _, [%0], %1;" ::"r"(bar), "r"(bytes) : "memory"); }
__device__ __forceinline__ void mbar_arrive(uint32_t bar) { asm volatile("mbarrier.arrive.shared::cta.b64 _, [%0];" ::"r"(bar) : "memory"); }
__device__ __forceinline__ void mbar_arrive_cluster(uint32_t bar, uint32_t cta) {
    asm volatile("{\n.reg .b32 ra;\nmapa.shared::cluster.u32 ra, %0, %1;\nmbarrier.arrive.shared::cluster.b64 _, [ra];\n}" ::"r"(bar), "r"(cta) : "memory");
}
__device__ __forceinline__ void mbar_wait(uint32_t bar, uint32_t parity) {
    asm volatile(
        "{\n.reg .pred p;\n.reg .u32 n;\n"
        "mbarrier.try_wait.parity.shared::cta.b64 p, [%0], %1;\n"
        "@p bra.uni LAB_DONE;\n"
        "mov.u32 n, 0;\n"
        "LAB_WAIT:\n"
        "mbarrier.try_wait.parity.shared::cta.b64 p, [%0], %1, 1000;\n"
        "@p bra.uni LAB_DONE;\n"
        "add.u32 n, n, 1;\n"
        "setp.ge.u32 p, n, 0x400000;\n"
        "@p trap;\n"
        "bra.uni LAB_WAIT;\n"
        "LAB_DONE:\n}" ::"r"(bar), "r"(parity) : "memory");
}
__device__ __forceinline__ void flag_wait(const uint32_t* p, uint32_t target) {
    asm volatile(
        "{\n.reg .pred p;\n.reg .u32 n;\n.reg .s32 v;\n"
        "mov.u32 n, 0;\n"
        "LAB_WAIT:\n"
        "ld.acquire.gpu.global.s32 v, [%0];\n"
        "sub.s32 v, v, %1;\n"
        "setp.ge.s32 p, v, 0;\n"
        "@p bra.uni LAB_DONE;\n"
        "add.u32 n, n, 1;\n"
        "setp.ge.u32 p, n, 0x800000;\n"
        "@p trap;\n"
        "bra.uni LAB_WAIT;\n"
        "LAB_DONE:\n}" ::"l"(p), "r"(target) : "memory");
}
__device__ __forceinline__ uint32_t flag_wait_bits(const uint32_t* p, uint32_t base, uint32_t mask) {
    uint32_t v;
    asm volatile(
        "{\n.reg .pred p;\n.reg .u32 n, t;\n"
        "mov.u32 n, 0;\n"
        "LAB_WAIT:\n"
        "ld.acquire.gpu.global.u32 %0, [%1];\n"
        "sub.u32 %0, %0, %2;\n"
        "and.b32 t, %0, %3;\n"
        "setp.ne.u32 p, t, 0;\n"
        "@p bra.uni LAB_DONE;\n"
        "add.u32 n, n, 1;\n"
        "setp.ge.u32 p, n, 0x800000;\n"
        "@p trap;\n"
        "bra.uni LAB_WAIT;\n"
        "LAB_DONE:\n}" : "=&r"(v) : "l"(p), "r"(base), "r"(mask) : "memory");
    return v;
}
__device__ __forceinline__ void flag_add(uint32_t* p) { asm volatile("red.release.gpu.global.add.u32 [%0], 1;" ::"l"(p) : "memory"); }
__device__ __forceinline__ void flag_addv(uint32_t* p, uint32_t v) { asm volatile("red.release.gpu.global.add.u32 [%0], %1;" ::"l"(p), "r"(v) : "memory"); }
__device__ __forceinline__ void fence_async_global() { asm volatile("fence.proxy.async.global;" ::: "memory"); }
__device__ __forceinline__ void fence_async_shared() { asm volatile("fence.proxy.async.shared::cta;" ::: "memory"); }
__device__ __forceinline__ bool elect_one() {
    uint32_t p;
    asm volatile("{\n.reg .pred p;\nelect.sync _|p, 0xffffffff;\nselp.u32 %0, 1, 0, p;\n}" : "=r"(p));
    return p != 0;
}
__device__ __forceinline__ uint32_t mbar_test(uint32_t bar, uint32_t parity) {
    uint32_t p;
    asm volatile("{\n.reg .pred p;\nmbarrier.test_wait.parity.shared::cta.b64 p, [%1], %2;\nselp.u32 %0, 1, 0, p;\n}" : "=r"(p) : "r"(bar), "r"(parity) : "memory");
    return p;
}
__device__ __forceinline__ void mbar_wait_unless(uint32_t done, uint32_t bar, uint32_t parity) {
    asm volatile(
        "{\n.reg .pred p;\n.reg .u32 n;\n"
        "setp.ne.u32 p, %2, 0;\n"
        "@p bra.uni LAB_DONE;\n"
        "mov.u32 n, 0;\n"
        "LAB_WAIT:\n"
        "mbarrier.try_wait.parity.shared::cta.b64 p, [%0], %1, 1000;\n"
        "@p bra.uni LAB_DONE;\n"
        "add.u32 n, n, 1;\n"
        "setp.ge.u32 p, n, 0x400000;\n"
        "@p trap;\n"
        "bra.uni LAB_WAIT;\n"
        "LAB_DONE:\n}" ::"r"(bar), "r"(parity), "r"(done) : "memory");
}
__device__ __forceinline__ void bulk_s2g(void* dst, uint32_t src, uint32_t bytes) {
    asm volatile("cp.async.bulk.global.shared::cta.bulk_group [%0], [%1], %2;" ::"l"(dst), "r"(src), "r"(bytes) : "memory");
}
__device__ __forceinline__ void bulk_s2c(uint32_t addr, uint32_t bytes, uint32_t bar, uint32_t cta) {
    asm volatile("{\n.reg .b32 d, b;\nmapa.shared::cluster.u32 d, %0, %3;\nmapa.shared::cluster.u32 b, %2, %3;\n"
                 "cp.async.bulk.shared::cluster.shared::cta.mbarrier::complete_tx::bytes [d], [%0], %1, [b];\n}"
                 ::"r"(addr), "r"(bytes), "r"(bar), "r"(cta) : "memory");
}
__device__ __forceinline__ void sts32(uint32_t a, uint32_t v) { asm volatile("st.shared.u32 [%0], %1;" ::"r"(a), "r"(v) : "memory"); }
__device__ __forceinline__ void sts128(uint32_t a, uint32_t x, uint32_t y, uint32_t z, uint32_t w) { asm volatile("st.shared.v4.u32 [%0], {%1, %2, %3, %4};" ::"r"(a), "r"(x), "r"(y), "r"(z), "r"(w) : "memory"); }
__device__ __forceinline__ void stsm4(uint32_t a, uint32_t r0, uint32_t r1, uint32_t r2, uint32_t r3) {
    asm volatile("stmatrix.sync.aligned.m8n8.x4.shared.b16 [%0], {%1, %2, %3, %4};" ::"r"(a), "r"(r0), "r"(r1), "r"(r2), "r"(r3) : "memory");
}
__device__ __forceinline__ void ldsm4(uint32_t* r, uint32_t a) {
    asm volatile("ldmatrix.sync.aligned.m8n8.x4.shared.b16 {%0, %1, %2, %3}, [%4];" : "=r"(r[0]), "=r"(r[1]), "=r"(r[2]), "=r"(r[3]) : "r"(a) : "memory");
}
__device__ __forceinline__ uint32_t lds32(uint32_t a) { uint32_t v; asm volatile("ld.shared.u32 %0, [%1];" : "=r"(v) : "r"(a) : "memory"); return v; }
__device__ __forceinline__ void tma_2d(uint32_t dst, const CUtensorMap* tm, int c0, int c1, uint32_t bar) {
    asm volatile("cp.async.bulk.tensor.2d.shared::cluster.global.mbarrier::complete_tx::bytes [%0], [%1, {%3, %4}], [%2];"
                 ::"r"(dst), "l"(tm), "r"(bar), "r"(c0), "r"(c1) : "memory");
}
__device__ __forceinline__ void tma_2d_mc(uint32_t dst, const CUtensorMap* tm, int c0, int c1, uint32_t bar) {
    asm volatile("cp.async.bulk.tensor.2d.shared::cluster.global.mbarrier::complete_tx::bytes.multicast::cluster [%0], [%1, {%3, %4}], [%2], %5;"
                 ::"r"(dst), "l"(tm), "r"(bar), "r"(c0), "r"(c1), "h"((uint16_t)3) : "memory");
}
__device__ __forceinline__ void tma_3d(uint32_t dst, const CUtensorMap* tm, int c0, int c1, int c2, uint32_t bar) {
    asm volatile("cp.async.bulk.tensor.3d.shared::cluster.global.mbarrier::complete_tx::bytes [%0], [%1, {%3, %4, %5}], [%2];"
                 ::"r"(dst), "l"(tm), "r"(bar), "r"(c0), "r"(c1), "r"(c2) : "memory");
}
__device__ __forceinline__ void tma_3d_mc(uint32_t dst, const CUtensorMap* tm, int c0, int c1, int c2, uint32_t bar) {
    asm volatile("cp.async.bulk.tensor.3d.shared::cluster.global.mbarrier::complete_tx::bytes.multicast::cluster [%0], [%1, {%3, %4, %5}], [%2], %6;"
                 ::"r"(dst), "l"(tm), "r"(bar), "r"(c0), "r"(c1), "r"(c2), "h"((uint16_t)3) : "memory");
}
__device__ __forceinline__ void bulk_g2s(uint32_t dst, const void* src, uint32_t bytes, uint32_t bar) {
    asm volatile("cp.async.bulk.shared::cluster.global.mbarrier::complete_tx::bytes [%0], [%1], %2, [%3];"
                 ::"r"(dst), "l"(src), "r"(bytes), "r"(bar) : "memory");
}
__device__ __forceinline__ void bulk_g2s_mc(uint32_t dst, const void* src, uint32_t bytes, uint32_t bar) {
    asm volatile("cp.async.bulk.shared::cluster.global.mbarrier::complete_tx::bytes.multicast::cluster [%0], [%1], %2, [%3], %4;"
                 ::"r"(dst), "l"(src), "r"(bytes), "r"(bar), "h"((uint16_t)3) : "memory");
}
__device__ __forceinline__ void mma_16816(float* d, uint32_t a0, uint32_t a1, uint32_t a2, uint32_t a3, uint32_t b0, uint32_t b1) {
    asm volatile("mma.sync.aligned.m16n8k16.row.col.f32.bf16.bf16.f32 {%0,%1,%2,%3}, {%4,%5,%6,%7}, {%8,%9}, {%0,%1,%2,%3};"
                 : "+f"(d[0]), "+f"(d[1]), "+f"(d[2]), "+f"(d[3]) : "r"(a0), "r"(a1), "r"(a2), "r"(a3), "r"(b0), "r"(b1));
}
__device__ __forceinline__ uint32_t movm_t(uint32_t a) { uint32_t d; asm volatile("movmatrix.sync.aligned.m8n8.trans.b16 %0, %1;" : "=r"(d) : "r"(a)); return d; }
__device__ __forceinline__ uint32_t ldg32(const uint8_t* p) { uint32_t v; asm volatile("ld.global.u32 %0, [%1];" : "=r"(v) : "l"(p) : "memory"); return v; }
__device__ __forceinline__ void stg32(uint8_t* p, uint32_t v) { asm volatile("st.global.u32 [%0], %1;" ::"l"(p), "r"(v) : "memory"); }

struct Ring {
    uint32_t slot;
    uint32_t phase;
    __device__ __forceinline__ void next() { if (++slot == NSTAGE) { slot = 0; phase ^= 1; } }
};

__device__ __forceinline__ void load_q(uint32_t (&q)[8], uint32_t qa, int lane) {
    q[0] = lds32(qa + lane * 4);       q[1] = lds32(qa + lane * 4 + 256);
    q[2] = lds32(qa + lane * 4 + 128); q[3] = lds32(qa + lane * 4 + 384);
    const uint32_t t0 = lds32(qa + 512 + (lane & ~3)), t1 = lds32(qa + 544 + (lane & ~3));
    q[4] = (lane & 3) == 2 ? t0 : 0u;  q[5] = (lane & 3) == 2 ? t1 : 0u;
}

__device__ __forceinline__ bool norm_o(uint32_t (&w)[6], const float (&o)[12], int lane, uint32_t gaddr) {
    const float l0 = __shfl_sync(0xffffffffu, o[8], (lane & ~3) | 1);
    const float l1 = __shfl_sync(0xffffffffu, o[10], (lane & ~3) | 1);
    const float i0 = rcp_fast(l0) * __uint_as_float(lds32(gaddr)), i1 = rcp_fast(l1) * __uint_as_float(lds32(gaddr + 32));
    uint32_t big = 0;
#pragma unroll
    for (int b = 0; b < 3; b++) {
        w[2 * b] = pack(o[4 * b] * i0, o[4 * b + 1] * i0);
        w[2 * b + 1] = pack(o[4 * b + 2] * i1, o[4 * b + 3] * i1);
        if (b == 2 && (lane & 3) != 0) w[4] = w[5] = 0u;
        big |= ((w[2 * b] & 0x7F807F80u) + 0x00800080u) | ((w[2 * b + 1] & 0x7F807F80u) + 0x00800080u);
    }
    const bool ok = fminf(l0, l1) >= 0x1p-30f && l0 <= 0x1p80f && l1 <= 0x1p80f && (big & 0x80008000u) == 0;
    return !__all_sync(0xffffffffu, ok);
}

__device__ __forceinline__ void attn_true_max(float (&o)[12], const uint32_t (&q)[8], const uint8_t* kv) {
    float m0 = -INFINITY, m1 = -INFINITY;
#pragma unroll
    for (int i = 0; i < 12; i++) o[i] = 0.f;
#pragma unroll 1
    for (int kb = 0; kb < SEQ / 16; kb++) {
        uint32_t t[2][5];
#pragma unroll
        for (int g = 0; g < 2; g++)
#pragma unroll
            for (int ch = 0; ch < 5; ch++) t[g][ch] = ldg32(kv + (kb * 2 + g) * 640 + ch * 128);
        float s[2][4];
#pragma unroll
        for (int g = 0; g < 2; g++) {
            s[g][0] = s[g][1] = s[g][2] = s[g][3] = 0.f;
            mma_16816(s[g], q[0], q[1], q[2], q[3], t[g][0], t[g][1]);
            mma_16816(s[g], q[4], q[5], 0u, 0u, t[g][4], 0u);
        }
        float x0 = fmaxf(fmaxf(s[0][0], s[0][1]), fmaxf(s[1][0], s[1][1]));
        float x1 = fmaxf(fmaxf(s[0][2], s[0][3]), fmaxf(s[1][2], s[1][3]));
        x0 = fmaxf(x0, __shfl_xor_sync(0xffffffffu, x0, 1)); x0 = fmaxf(x0, __shfl_xor_sync(0xffffffffu, x0, 2));
        x1 = fmaxf(x1, __shfl_xor_sync(0xffffffffu, x1, 1)); x1 = fmaxf(x1, __shfl_xor_sync(0xffffffffu, x1, 2));
        const float n0 = fmaxf(m0, x0), n1 = fmaxf(m1, x1);
        const float u0 = (n0 == -INFINITY) ? 0.f : n0, u1 = (n1 == -INFINITY) ? 0.f : n1;
        const float c0 = ex2(m0 - u0), c1 = ex2(m1 - u1);
        m0 = n0; m1 = n1;
#pragma unroll
        for (int b = 0; b < 3; b++) { o[4 * b] *= c0; o[4 * b + 1] *= c0; o[4 * b + 2] *= c1; o[4 * b + 3] *= c1; }
        const uint32_t a0 = pack(ex2(s[0][0] - u0), ex2(s[0][1] - u0)), a1 = pack(ex2(s[0][2] - u1), ex2(s[0][3] - u1));
        const uint32_t a2 = pack(ex2(s[1][0] - u0), ex2(s[1][1] - u0)), a3 = pack(ex2(s[1][2] - u1), ex2(s[1][3] - u1));
#pragma unroll
        for (int b = 0; b < 3; b++) mma_16816(&o[4 * b], a0, a1, a2, a3, movm_t(t[0][2 + b]), movm_t(t[1][2 + b]));
    }
}

__device__ __forceinline__ float geglu2(float g, float u) {
    const float p = fmaf(g * g, 0.044715f * 0.7978845608028654f, 0.7978845608028654f);
    const float th = tanh_fast(g * p);
    const float y = g * u;
    return fmaf(y, th, y);
}

struct Attn {
    float s[32];
    float o[12];
    uint32_t p[16];
    uint32_t q[8];
};

__global__ void __cluster_dims__(2, 1, 1) __launch_bounds__(384, 1)
fused_kernel(__nv_bfloat16* __restrict__ out, const __nv_bfloat16* __restrict__ x, const __nv_bfloat16* __restrict__ gate_w,
             const __grid_constant__ CUtensorMap tm_x, const __grid_constant__ CUtensorMap tm_qkv,
             const __grid_constant__ CUtensorMap tm_qkv8,
             const __grid_constant__ CUtensorMap tm_wg, const __grid_constant__ CUtensorMap tm_wu,
             const __grid_constant__ CUtensorMap tm_wd, const __grid_constant__ CUtensorMap tm_wo,
             const __grid_constant__ CUtensorMap tm_wd16, const __grid_constant__ CUtensorMap tm_wo16) {
    extern __shared__ uint8_t smem_raw[];
    const uint32_t sb = __shfl_sync(0xffffffffu, ((uint32_t)__cvta_generic_to_shared(smem_raw) + 1023) & ~1023u, 0);
    const uint32_t bars = sb + OFF_BAR;
    const uint32_t bar_full = bars, bar_empty = bars + 64;
    const uint32_t bar_ev = bars + 128;
    const uint32_t bar_rdy = bars + 256;
    const uint32_t bar_ep = bars + 320, bar_gate = bars + 328;
    const uint32_t bar_st = bars + 336;
    const uint32_t bar_late = bars + 408;
    const uint32_t bar_px = bars + 416;
    const uint32_t bar_free = bars + 424;
    const uint32_t s_epoch = bars + 448, s_zero = bars + 452, s_order = bars + 464, s_gate = bars + 512;

    const int cta = blockIdx.x >= NCTA ? blockIdx.x : ((blockIdx.x & 14) << 3) | ((blockIdx.x >> 4) << 1) | (blockIdx.x & 1);
    const int rank = cta & 1;
    const int j = (cta >> 1) & 7;
    const int m = (cta >> 4) * 2 + rank;
    const int hf = j >> 2, nt = j & 3;
    const int warp = __shfl_sync(0xffffffffu, threadIdx.x >> 5, 0);
    const int lane = threadIdx.x & 31;
    const int wg = warp >> 2;

    const bool leader = elect_one();
    if (leader) {
        if (warp == 8) {
#pragma unroll
            for (int e = 0; e < E0; e++) mbar_init(bar_full + e * 8, 2);
        } else if (warp < NSTAGE) {
            if (warp >= E0) mbar_init(bar_full + warp * 8, 2);
            mbar_init(bar_empty + warp * 8, 4);
        }
        asm volatile("fence.mbarrier_init.release.cluster;" ::: "memory");
    }
    __syncwarp();
    asm volatile("barrier.cluster.arrive.relaxed.aligned;" ::: "memory");
    if (cta < NCTA && warp == 8 && leader) {
#pragma unroll 1
        for (int e = 0; e < E0; e++) {
            const uint32_t st = sb + e * SLOT, fb = bar_full + e * 8;
            mbar_arrive(fb);
            mbar_expect_tx(fb, 8192 + 12288 + 8192 + 1536);
            tma_2d(st + OFF_AX, &tm_x, e * 32, m * 128, fb);
#pragma unroll
            for (int r = 0; r < 2; r++) {
                tma_3d(st + 8192 + r * 6144, &tm_qkv, j * 72, e * 32 + r * 16, 0, fb);
                tma_3d(st + OFF_TL + r * 768, &tm_qkv8, j * 72 + 64, e * 32 + r * 16, 0, fb);
                tma_2d(st + r * 4096, r ? &tm_wu : &tm_wg, j * 576 + 512, e * 32, fb);
            }
        }
    }
    if (warp != 8) {
        if (leader && warp < 8) {
            const uint32_t lo = (warp >= 4 && warp <= 6) ? 1 : 4, hi = warp == 6 ? 4 : lo;
            mbar_init(bar_ev + warp * 32, lo); mbar_init(bar_ev + warp * 32 + 8, lo);
            mbar_init(bar_ev + warp * 32 + 16, hi); mbar_init(bar_ev + warp * 32 + 24, hi);
            if (warp < 4) mbar_init(bar_late + warp * 8, 1);
            sts32(s_zero, 0u); sts32(s_zero + 4, 0u);
            asm volatile("fence.mbarrier_init.release.cluster;" ::: "memory");
        }
        __syncwarp();
        asm volatile("bar.sync 1, 352;" ::: "memory");
    }
    __syncwarp();
    asm volatile("barrier.cluster.wait.acquire.aligned;" ::: "memory");

    if (wg == 2) {
        asm volatile("setmaxnreg.dec.sync.aligned.u32 24;");
        if (cta >= NCTA) {
            if (warp == 9 && elect_one()) {
                const uint32_t ep = g_flags[FL_E + cta * 32] + 1;
                g_flags[FL_E + cta * 32] = ep;
                mbar_wait(bar_ev + 2 * 8, 0);
                mbar_wait(bar_ev + 10 * 8, 0);
                flag_add(&g_flags[FL_G + (cta - NCTA) * 32]);
#pragma unroll 1
                for (int i = 0; i < 2; i++) {
                    const int jx = (cta - NCTA) * 2 + i;
                    flag_wait(&g_flags[FL_KV + jx * 32 + 1], ep * 32);
                    fence_async_global();
                    mbar_expect_tx(bar_rdy + i * 8, 20480 + 16 * 4608);
#pragma unroll 1
                    for (int p = 0; p < 8; p++) bulk_g2s(sb + 40960 + (i * 8 + p) * 9216, g_q3 + (p * 16 + jx * 2) * 4608, 9216, bar_rdy + i * 8);
                    bulk_g2s(sb + i * 20480, g_kv + (size_t)(jx * 4 + 3) * HEAD_BYTES + 28 * 5120, 20480, bar_rdy + i * 8);
                }
#pragma unroll 1
                for (int i = 0; i < 2; i++) {
                    mbar_wait(bar_ev + i * 8, 0);
                    mbar_wait(bar_ev + (8 + i) * 8, 0);
                    flag_add(&g_flags[FL_KV + ((cta - NCTA) * 2 + i) * 32 + 2]);
                }
            }
        } else if (warp == 8) {
            if (elect_one()) {
                Ring r{E0, 1};
                const int row0 = m * 128;
                const CUtensorMap* tw = rank ? &tm_wu : &tm_wg;
#pragma unroll 1
                for (int kk = E0; kk < 18; kk++) {
                    const uint32_t st = sb + r.slot * SLOT, fb = bar_full + r.slot * 8;
                    mbar_wait(bar_empty + r.slot * 8, r.phase);
                    mbar_arrive(fb);
                    mbar_expect_tx(fb, 8192 + 12288 + 8192 + 1536);
                    tma_2d(st + OFF_AX, &tm_x, kk * 32, row0, fb);
                    tma_3d_mc(st + 8192 + rank * 6144, &tm_qkv, j * 72, kk * 32 + rank * 16, 0, fb);
                    tma_3d_mc(st + OFF_TL + rank * 768, &tm_qkv8, j * 72 + 64, kk * 32 + rank * 16, 0, fb);
                    tma_2d_mc(st + rank * 4096, tw, j * 576 + 512, kk * 32, fb);
                    r.next();
                }
                int k0 = DM - NSTAGE * 32;
#pragma unroll 1
                for (int t = 0; t < 4; t++)
#pragma unroll 1
                    for (int kk = 0; kk < 18; kk++) {
                        const uint32_t st = sb + r.slot * SLOT, fb = bar_full + r.slot * 8;
                        mbar_wait(bar_empty + r.slot * 8, r.phase);
                        if (t == 0 && kk < 2) mbar_arrive(fb);
                        const bool have_x = kk < NSTAGE;
                        mbar_expect_tx(fb, have_x ? 16384 : 8192 + 16384);
                        tma_2d_mc(st + rank * 8192, tw, j * 576 + t * 128, k0, fb);
                        tma_2d_mc(st + rank * 8192 + 4096, tw, j * 576 + t * 128 + 64, k0, fb);
                        if (!have_x) tma_2d(st + OFF_AX, &tm_x, k0, row0, fb);
                        k0 += kk == 17 ? DM + 32 - NSTAGE * 32 : 32;
                        if (k0 >= DM) k0 -= DM;
                        r.next();
                    }
                const uint8_t* a2 = g_a2 + (size_t)m * A2_TILE;
                mbar_wait(bar_rdy + 4 * 8, 0);
#pragma unroll 1
                for (int n = 0; n < 48; n++) {
                    const int u = n >> 2, jj = n & 3;
                    const uint32_t st = sb + r.slot * SLOT, fb = bar_full + r.slot * 8;
                    mbar_wait(bar_empty + r.slot * 8, r.phase);
                    mbar_expect_tx(fb, 12288 + 12288 + STRIPB);
                    const int ks = (hf * 4 + jj) * 36 + u * 3;
#pragma unroll
                    for (int b = 0; b < 2; b++) tma_2d_mc(st + b * 6144 + rank * 3072, &tm_wd, nt * 128 + (b ^ hf) * 64, ks * 16 + rank * 24, fb);
                    tma_2d_mc(st + 12288 + rank * 3072, &tm_wd16, 512 + nt * 16, ks * 16 + rank * 24, fb);
                    if (jj == 0) { mbar_wait(bar_rdy + ((3 * u + 2) >> 3) * 8, 0); fence_async_global(); }
                    bulk_g2s(st + OFF_A2, a2 + ks * 4096, 12288, fb);
                    r.next();
                }
#pragma unroll 1
                for (int n = 0; n < 4; n++) {
                    const uint32_t st = sb + r.slot * SLOT, fb = bar_full + r.slot * 8;
                    mbar_wait(bar_empty + r.slot * 8, r.phase);
                    mbar_expect_tx(fb, 12288 + 12288 + STRIPB);
                    const int pr = hf * 2 + (n & 1), head = (pr * 2 + rank) * 4 + (n >> 1);
#pragma unroll
                    for (int b = 0; b < 2; b++) tma_2d_mc(st + b * 6144 + rank * 3072, &tm_wo, nt * 128 + (b ^ hf) * 64, head * 18, fb);
                    tma_2d_mc(st + 12288 + rank * 3072, &tm_wo16, 512 + nt * 16, head * 18, fb);
                    if (n == 0) { mbar_wait(bar_rdy + 5 * 8, 0); fence_async_global(); }
                    bulk_g2s(st + OFF_A2, a2 + (288 + ((n >> 1) * 4 + pr) * 3) * 4096, 12288, fb);
                    r.next();
                }
                mbar_expect_tx(bar_late, 4 * (6144 + STRIPB));
#pragma unroll 1
                for (int n = 0; n < 8; n++) {
                    const uint32_t st = sb + r.slot * SLOT, fb = bar_full + r.slot * 8;
                    mbar_wait(bar_empty + r.slot * 8, r.phase);
                    if (n >= 2) mbar_arrive(fb);
                    if (n < 4) mbar_expect_tx(fb, 12288 + 6144 + STRIPB);
                    const int head = ((n & 3) * 2 + rank) * 4 + 2 + (n >> 2);
                    tma_2d_mc(st + rank * 3072, &tm_wo, nt * 128 + hf * 64, head * 18, n < 4 ? fb : bar_late);
                    tma_2d_mc(st + 6144 + rank * 3072, &tm_wo16, 512 + nt * 16, head * 18, n < 4 ? fb : bar_late);
                    if (n < 4) bulk_g2s(st + OFF_A2, a2 + (288 + (8 + n) * 3) * 4096, 12288, fb);
                    r.next();
                }
                mbar_wait(bar_ep, 0);
                const uint32_t base = (lds32(s_epoch) - 1) * 0x04040404u;
                uint32_t todo = 0x04040404u, k = 2;
#pragma unroll 1
                while (todo) {
                    const uint32_t got = flag_wait_bits(&g_flags[FL_M + m * 64 + FM_LATE], base, todo) & todo;
                    fence_async_global();
#pragma unroll 1
                    for (int pr = 0; pr < 4; pr++)
                        if ((got >> (pr * 8)) & 4) {
                            sts32(s_order + k * 4, (2 + pr) * (SLOT >> 4));
                            mbar_expect_tx(bar_full + k * 8, 12288);
                            bulk_g2s(sb + k * SLOT + OFF_A2, a2 + (288 + (12 + pr) * 3) * 4096, 12288, bar_full + k * 8);
                            k++;
                        }
                    todo &= ~got;
                }
            }
        } else if (warp == 9) {
            if (elect_one()) {
                const uint32_t ep = g_flags[FL_E + cta * 32] + 1;
                g_flags[FL_E + cta * 32] = ep;
                sts32(s_epoch, ep);
                mbar_arrive(bar_ep);
                Ring r{0, 1};
                const uint8_t* kv = g_kv + (size_t)(j * 4) * HEAD_BYTES + rank * 2560;
                const int rot = (cta >> 4) * 4;
                uint32_t have = flag_wait_bits(&g_flags[FL_KV + j * 32], (ep - 1) * 0x44444444u, 4u << rot);
                fence_async_global();
#pragma unroll 1
                for (int it = 4; it < 124; it++) {
                    const uint32_t fb = bar_full + r.slot * 8;
                    if (it < 32 && !((have >> ((it + rot) & 28)) & 4)) {
                        have = flag_wait_bits(&g_flags[FL_KV + j * 32], (ep - 1) * 0x44444444u, 4u << ((it + rot) & 28));
                        fence_async_global();
                    }
                    if (it == 24) { flag_wait(&g_flags[FL_KV + j * 32 + 1], ep * 32); fence_async_global(); }
                    mbar_wait(bar_empty + r.slot * 8, r.phase);
                    mbar_expect_tx(fb, 5120);
                    bulk_g2s_mc(sb + r.slot * SLOT + OFF_KV + rank * 2560, kv + (it < 32 ? (it + rot) & 31 : it) * 5120, 2560, fb);
                    r.next();
                }
                flag_wait(&g_flags[FL_KV + j * 32 + 2], ep);
                mbar_arrive(bar_px);
                uint32_t* fr = &g_flags[FL_M + m * 64 + FM_R];
                mbar_wait(bar_ev + 6 * 8, 0);
                mbar_wait(bar_ev + 14 * 8, 0);
                flag_add(fr + j);
                flag_wait(fr + (j ^ 4), ep);
                mbar_arrive(bar_rdy + 6 * 8);
            }
        } else {
            const int w = warp - 10;
            if (elect_one()) {
                const uint32_t mine = 2 + rank * 2 + w, other = 2 + (rank ^ 1) * 2 + w;
                mbar_wait(bar_st + w * 8, 0);
                bulk_s2g(g_kv + (size_t)(j * 4) * HEAD_BYTES + (m * 16 + w * 8) * 640, sb + mine * SLOT + OFF_KV, 5120);
                asm volatile("cp.async.bulk.commit_group;" ::: "memory");
                mbar_arrive(bar_full + mine * 8);
                mbar_expect_tx(bar_full + other * 8, 5120);
#pragma unroll 1
                for (int i = 0; i < 2; i++) {
                    if (i == rank) {
                        mbar_wait(bar_empty + mine * 8, 0);
                        bulk_s2c(sb + mine * SLOT + OFF_KV, 5120, bar_full + mine * 8, rank ^ 1);
                    } else {
                        asm volatile("cp.async.bulk.wait_group 0;" ::: "memory");
                        flag_addv(&g_flags[FL_KV + j * 32], 1u << ((cta >> 4) * 4));
                    }
                }
                mbar_wait(bar_st + (2 + w) * 8, 0);
                __nanosleep(1500);
                bulk_s2g(g_q3 + cta * 4608 + w * 2304, sb + OFF_Q + 3 * 4608 + w * 2304, 2304);
#pragma unroll 1
                for (int h = 1; h < 4; h++) {
                    __nanosleep(200);
                    bulk_s2g(g_kv + (size_t)(j * 4 + h) * HEAD_BYTES + (m * 16 + w * 8) * 640, sb + (w * 3 + h - 1) * SLOT + OFF_GAP, 5120);
                    asm volatile("cp.async.bulk.commit_group;\ncp.async.bulk.wait_group 0;" ::: "memory");
                }
                mbar_arrive(bar_free + w * 8);
                flag_add(&g_flags[FL_KV + j * 32 + 1]);
            }
            __syncwarp();
            uint32_t* fm = &g_flags[FL_M + m * 64];
            mbar_wait(bar_ep, 0);
            const uint32_t ep = lds32(s_epoch);
            if (w == 1) {
                flag_wait(&g_flags[FL_G + (m >> 2) * 32], ep);
                const uint4 gv = __ldcg((const uint4*)(g_gate + m * 128) + lane);
                sts128(s_gate + lane * 16, gv.x, gv.y, gv.z, gv.w);
                __syncwarp();
                if (lane == 0) mbar_arrive(bar_gate);
            }
            if (elect_one()) {
#pragma unroll 1
                for (int i = 0; i < 6; i++) {
                    const int e = i == 0 ? 4 : i == 5 ? 5 : i - 1;
                    mbar_wait(bar_ev + (w * 8 + e) * 8, 0);
                    if (e < 3) {
                        uint8_t* hp = g_a2 + (size_t)m * A2_TILE + (j * 36 + e * 8) * 4096 + w * 2048;
#pragma unroll 1
                        for (int k = 0; k < 8; k++) {
                            const int g = (k * 11) >> 5;
                            bulk_s2g(hp + k * 4096, sb + (w * 3 + g) * SLOT + OFF_GAP + (k - g * 3) * 2048, 2048);
                        }
                        asm volatile("cp.async.bulk.commit_group;\ncp.async.bulk.wait_group 0;" ::: "memory");
                    }
                    uint32_t* fl = fm + FM_H + (e == 5 ? 5 : hf * 8 + e);
                    flag_add(fl);
                    if (w == 0) { flag_wait(fl, ep * (e == 5 ? 16 : 8)); mbar_arrive(bar_rdy + e * 8); }
                }
                if (w == 0) {
                    mbar_wait(bar_ev + 7 * 8, 0);
                    mbar_wait(bar_ev + 15 * 8, 0);
                    flag_addv(fm + FM_LATE, 2u << ((j >> 1) * 8));
                }
            }
        }
    } else {
        asm volatile("setmaxnreg.inc.sync.aligned.u32 240;");
        const int wq = warp & 3;
        const int c = lane & 3;
        const int tid = threadIdx.x & 127;
        const int grp = wg * 8 + wq * 2;
        const uint32_t sbd = (sb & 0x3FFFF) >> 4;
        uint32_t sd = sbd, pd = sbd, fb = bar_full, pb = bar_full, ph = 0;
#define STAGE_NEXT do { pd = sd; sd = (sd == sbd + (NSTAGE - 1) * (SLOT >> 4)) ? sbd : sd + (SLOT >> 4);           \
                        pb = fb; fb += 8; if (fb == bar_full + NSTAGE * 8) { fb = bar_full; ph ^= 1; } } while (0)
        auto release = [&]() { if (tid < 2) mbar_arrive_cluster(pb + 64, tid); };
        auto signal = [&](int e) { __syncwarp(); if (lane == 0) mbar_arrive(bar_ev + (wg * 8 + e) * 8); };
        if (cta >= NCTA) {
            {
                float wv[72];
#pragma unroll
                for (int i = 0; i < 9; i++) {
                    const uint4 t = __ldg((const uint4*)gate_w + (lane & 7) + i * 8);
                    const uint32_t u[4] = {t.x, t.y, t.z, t.w};
#pragma unroll
                    for (int e = 0; e < 4; e++) { wv[8 * i + 2 * e] = __uint_as_float(u[e] << 16); wv[8 * i + 2 * e + 1] = __uint_as_float(u[e] & 0xffff0000u); }
                }
                __nanosleep(1500);
#pragma unroll 1
                for (int b = 0; b < 8; b++) {
                    const int row = (cta - NCTA) * 512 + warp * 64 + b * 8 + (lane >> 3);
                    uint4 xa[2][9];
#pragma unroll
                    for (int r = 0; r < 2; r++)
#pragma unroll
                        for (int i = 0; i < 9; i++) xa[r][i] = __ldg((const uint4*)(x + (size_t)(row + r * 4) * DM) + (lane & 7) + i * 8);
#pragma unroll
                    for (int r = 0; r < 2; r++) {
                        float z = 0.f, y = 0.f;
#pragma unroll
                        for (int i = 0; i < 9; i++) {
                            const uint32_t u[4] = {xa[r][i].x, xa[r][i].y, xa[r][i].z, xa[r][i].w};
#pragma unroll
                            for (int e = 0; e < 4; e++) {
                                z = fmaf(__uint_as_float(u[e] << 16), wv[8 * i + 2 * e], z);
                                y = fmaf(__uint_as_float(u[e] & 0xffff0000u), wv[8 * i + 2 * e + 1], y);
                            }
                        }
                        z += y;
#pragma unroll
                        for (int d = 1; d < 8; d <<= 1) z += __shfl_xor_sync(0xffffffffu, z, d);
                        if ((lane & 7) == 0) g_gate[row + r * 4] = rcp_fast(1.f + ex2(-1.4426950408889634f * z));
                    }
                }
                signal(2);
            }
            float s0[64], s1[64], o[12];
            uint32_t p0[32], p1[32], q[8];
            q[6] = lds32(s_zero); q[7] = lds32(s_zero + 4);
#pragma unroll
            for (int i = 0; i < 12; i++) o[i] = 0.f;
            auto store_px = [&](int u) {
                const int src = ((u & 15) >> 1) * 16 + ((cta - NCTA) * 2 + (u >> 4)) * 2 + (u & 1);
                float4* dst = g_px + (size_t)(src * 2 + wg) * 3 * 128 + tid;
#pragma unroll
                for (int i = 0; i < 3; i++) __stcg(dst + i * 128, make_float4(o[4 * i], o[4 * i + 1], o[4 * i + 2], o[4 * i + 3]));
            };
            mbar_wait(bar_rdy, 0);
            load_q(q, sb + 40960 + warp * 576, lane);
            fence_regs(q); fence_regs(o);
            wg_fence();
            wgmma_rs_n128_t0<HI_K>(s0, q[0], q[1], q[2], q[3], sbd + dlo(0, 128), 0);
            wgmma_rs_n128_t0<HI_K>(s0, q[4], q[5], q[6], q[7], sbd + dlo(512, 0), 1);
            wg_commit();
            wg_wait<0>();
            fence_regs(s0);
#pragma unroll 1
            for (int u = 0; u < 32; u++) {
                const uint32_t kb = sbd + (u >> 4) * 1280;
                wg_fence();
                wgmma_rs_n128_t0<HI_K>(s1, q[0], q[1], q[2], q[3], kb + dlo(10240, 128), 0);
                wgmma_rs_n128_t0<HI_K>(s1, q[4], q[5], q[6], q[7], kb + dlo(10240 + 512, 0), 1);
                wg_commit();
#pragma unroll
                for (int i = 0; i < 32; i++) p0[i] = pack(ex2(s0[2 * i]), ex2(s0[2 * i + 1]));
                fence_regs(p0);
                wg_wait<0>();
                fence_regs(o); fence_regs(s1); fence_regs(q);
                store_px(u > 0 ? u - 1 : 0);
                if (u == 16) signal(0);
                if (u == 15) mbar_wait(bar_rdy + 8, 0);
                const int un = u < 31 ? u + 1 : u;
                load_q(q, sb + 40960 + un * 4608 + warp * 576, lane);
                fence_regs(q);
                const uint32_t kn = sbd + (un >> 4) * 1280;
                wg_fence();
#pragma unroll
                for (int i = 0; i < 8; i++) wgmma_rs_n24_t1<HI_V>(o, p0[4 * i], p0[4 * i + 1], p0[4 * i + 2], p0[4 * i + 3], kb + dlo(256, 640) + 80 * i, i != 0);
                wgmma_rs_n128_t0<HI_K>(s0, q[0], q[1], q[2], q[3], kn + dlo(0, 128), 0);
                wgmma_rs_n128_t0<HI_K>(s0, q[4], q[5], q[6], q[7], kn + dlo(512, 0), 1);
                wg_commit();
#pragma unroll
                for (int i = 0; i < 32; i++) p1[i] = pack(ex2(s1[2 * i]), ex2(s1[2 * i + 1]));
                fence_regs(p1);
                wg_fence();
#pragma unroll
                for (int i = 0; i < 8; i++) wgmma_rs_n24_t1<HI_V>(o, p1[4 * i], p1[4 * i + 1], p1[4 * i + 2], p1[4 * i + 3], kb + dlo(10240 + 256, 640) + 80 * i, 1);
                wg_commit();
                wg_wait<1>();
                fence_regs(s0); fence_regs(p0);
            }
            wg_wait<0>();
            fence_regs(o);
            store_px(31);
            signal(1);
            return;
        }
        Attn at;

        uint8_t* a2w = g_a2 + (size_t)m * A2_TILE + grp * 256 + lane * 4;
        const uint32_t qa = sb + OFF_Q + warp * 576;
        float acc[128];
        {
            float qkv[96], tl[12], gu[64];
            const uint32_t xrow = wg * 64 + wq * 16 + (lane & 15);
            const uint32_t xa0 = (sb & ~0x3FFFFu) + OFF_AX + xrow * 64 + (((lane >> 4) ^ ((xrow >> 1) & 3)) << 4);
            uint32_t xf[2][8];
#pragma unroll 1
            for (int k2 = 0; k2 < 18 - DEFER; k2 += 2) {
#pragma unroll
                for (int h = 0; h < 2; h++) {
                    const int kk = k2 + h;
                    mbar_wait(fb, ph);
                    ldsm4(&xf[h][0], xa0 + sd * 16);
                    ldsm4(&xf[h][4], (xa0 ^ 32) + sd * 16);
                    fence_regs(xf[h]);
                    const uint32_t db = sd + dlo(0, 4096), dt = sd + dlo(OFF_TL, 128);
                    wg_fence();
                    wgmma_rs_n192_t1<HI_W>(qkv, xf[h][0], xf[h][1], xf[h][2], xf[h][3], sd + QB0, kk != 0);
                    wgmma_rs_n24_t1<HI_T>(tl, xf[h][0], xf[h][1], xf[h][2], xf[h][3], dt, kk != 0);
                    wgmma_rs_n128_t1<HI_W>(gu, xf[h][0], xf[h][1], xf[h][2], xf[h][3], db, kk != 0);
                    wgmma_rs_n192_t1<HI_W>(qkv, xf[h][4], xf[h][5], xf[h][6], xf[h][7], sd + QB1, 1);
                    wgmma_rs_n24_t1<HI_T>(tl, xf[h][4], xf[h][5], xf[h][6], xf[h][7], dt + QT1, 1);
                    wgmma_rs_n128_t1<HI_W>(gu, xf[h][4], xf[h][5], xf[h][6], xf[h][7], db + 128, 1);
                    wg_commit();
                    wg_wait<1>();
                    if (kk > 0) release();
                    STAGE_NEXT;
                }
            }
#pragma unroll
            for (int kk = 0; kk < DEFER; kk++) {
                mbar_wait(fb + kk * 8, ph);
                const uint32_t st = sd + kk * (SLOT >> 4);
                const uint32_t da = st + wg * 256 + dlo(OFF_AX, 16), dt = st + dlo(OFF_TL, 128);
                wg_fence();
                wgmma_ss_n192_t1<HI_X, HI_W>(qkv, da, st + QB0, 1);
                wgmma_ss_n24_t1<HI_X, HI_T>(tl, da, dt, 1);
                wgmma_ss_n192_t1<HI_X, HI_W>(qkv, da + 2, st + QB1, 1);
                wgmma_ss_n24_t1<HI_X, HI_T>(tl, da + 2, dt + QT1, 1);
                wg_commit();
                if (kk == 0) { wg_wait<1>(); release(); }
            }
#pragma unroll
            for (int kk = 0; kk < DEFER; kk++) {
                const uint32_t st = sd + kk * (SLOT >> 4);
                const uint32_t da = st + wg * 256 + dlo(OFF_AX, 16), db = st + dlo(0, 4096);
                wgmma_ss_n128_t1<HI_X, HI_W>(gu, da, db, 1);
                wgmma_ss_n128_t1<HI_X, HI_W>(gu, da + 2, db + 128, 1);
            }
            wg_commit();
            wg_wait<1>();
            fence_regs(qkv); fence_regs(tl);
            constexpr float QS = 0.23570226039551584f * 1.4426950408889634f;
            uint32_t kp[9][2], vp[9][2];
#pragma unroll
            for (int i = 0; i < 9; i++) {
                const float* k4 = i < 8 ? &qkv[32 + 4 * i] : &tl[4];
                const float* v4 = i < 8 ? &qkv[64 + 4 * i] : &tl[8];
                kp[i][0] = pack(k4[0], k4[1]); kp[i][1] = pack(k4[2], k4[3]);
                vp[i][0] = pack(v4[0], v4[1]); vp[i][1] = pack(v4[2], v4[3]);
            }
            const int quad = lane & ~3;
            const uint32_t cst = c == 1 ? 0x3F80u : 0u;
            {
                const uint32_t a = sb + (2 + rank * 2 + wg) * SLOT + OFF_KV + wq * 1280 + lane * 4;
#pragma unroll
                for (int r = 0; r < 2; r++) {
                    const uint32_t kt = __shfl_sync(0xffffffffu, kp[2][r], quad);
                    sts32(a + r * 640, kp[0][r]);       sts32(a + r * 640 + 128, kp[1][r]);
                    sts32(a + r * 640 + 256, vp[0][r]); sts32(a + r * 640 + 384, vp[1][r]);
                    sts32(a + r * 640 + 512, c == 0 ? vp[2][r] : c == 2 ? kt : cst);
                }
                fence_async_shared();
                __syncwarp();
                if (lane == 0) mbar_arrive(bar_st + wg * 8);
            }
#pragma unroll
            for (int i = 0; i < 9; i++) {
                const float* q4 = i < 8 ? &qkv[4 * i] : &tl[0];
                const uint32_t q0 = pack(q4[0] * QS, q4[1] * QS), q1 = pack(q4[2] * QS, q4[3] * QS);
                if (i < 2) { at.q[2 * i] = q0; at.q[2 * i + 1] = q1; }
                else {
                    if (i == 2) {
                        const uint32_t t0 = __shfl_sync(0xffffffffu, q0, quad), t1 = __shfl_sync(0xffffffffu, q1, quad);
                        at.q[4] = c == 2 ? t0 : 0u; at.q[5] = c == 2 ? t1 : 0u;
                    }
                    const int lc = 8 * i + 2 * c;
                    const int hd = (lc * 3641) >> 16;
                    const int d = lc - hd * 18;
                    const bool last = (i & 1) == 0 && c == i / 2 - 1;
                    const uint32_t aq = qa + hd * 4608 + (last ? 512 + (lane >> 2) * 4 : (d >> 3) * 128 + (d & 7) * 2 + (lane >> 2) * 16);
                    if (i > 2 || c > 0) { sts32(aq, q0); sts32(aq + (last ? 32 : 256), q1); }
                }
            }
            mbar_wait(bar_st, 0);
            mbar_wait(bar_st + 8, 0);
#pragma unroll
            for (int i = 2; i < 9; i++) {
                const int lc = 8 * i + 2 * c;
                const int hd = (lc * 3641) >> 16;
                const int d = lc - hd * 18;
                const uint32_t ak = sb + (wg * 3 - 1 + hd) * SLOT + OFF_GAP + wq * 1280 + (lane >> 2) * 16;
                const uint32_t off = (d >> 3) * 128 + (d & 7) * 2;
                if ((i & 1) == 0 && c == i / 2 - 1) {
                    if (i > 2) { sts128(ak + 512, vp[i][0], 0x3F80u, kp[i][0], 0u); sts128(ak + 512 + 640, vp[i][1], 0x3F80u, kp[i][1], 0u); }
                } else {
                    sts32(ak + off, kp[i][0]); sts32(ak + off + 640, kp[i][1]); sts32(ak + off + 256, vp[i][0]); sts32(ak + off + 256 + 640, vp[i][1]);
                }
            }
            fence_async_shared();
            __syncwarp();
            if (lane == 0) mbar_arrive(bar_st + (2 + wg) * 8);
            wg_wait<0>();
            fence_regs(gu);
            if (tid < 2 * DEFER) mbar_arrive_cluster(fb + 64 + (tid >> 1) * 8, tid & 1);
#pragma unroll
            for (int kk = 0; kk < 2; kk++) {
                mbar_wait(bar_full + kk * 8, 1);
                const uint32_t st = sbd + kk * (SLOT >> 4);
                const uint32_t da = st + wg * 256 + dlo(OFF_AX, 16), db = st + dlo(0, 4096);
                wg_fence();
                wgmma_ss_n256_t1<HI_X, HI_W>(acc, da, db, kk);
                wgmma_ss_n256_t1<HI_X, HI_W>(acc, da + 2, db + 128, 1);
                wg_commit();
            }
            sd = sbd + 2 * (SLOT >> 4); fb = bar_full + 16; pb = bar_full; ph = 1;
            uint8_t* hp = a2w + (j * 36 + 32) * 4096;
#pragma unroll
            for (int i = 0; i < 16; i++)
                stg32(hp + (i >> 2) * 4096 + ((i >> 1) & 1) * 128 + (i & 1) * 256, pack(geglu2(gu[2 * i], gu[32 + 2 * i]), geglu2(gu[2 * i + 1], gu[32 + 2 * i + 1])));
            signal(4);
            wg_wait<1>();
            release();
            mbar_wait(fb, ph);
        }

        const uint32_t gaddr = s_gate + (grp * 8 + (lane >> 2)) * 4;
        at.q[6] = lds32(s_zero); at.q[7] = lds32(s_zero + 4);
#pragma unroll
        for (int i = 0; i < 16; i++) at.p[i] = 0u;
#pragma unroll
        for (int i = 0; i < 12; i++) at.o[i] = 0.f;
        fence_regs(at.q); fence_regs(at.p); fence_regs(at.o);
        pd = sd;
        uint32_t rel = bar_empty + 8;
        asm volatile("mapa.shared::cluster.u32 %0, %0, %1;" : "+r"(rel) : "r"(tid & 1));
        const uint32_t rel_off = rel - (bar_full + 8);

#define ISSUE_PV() do {                                                                                            \
            const uint32_t dv = pd + dlo(OFF_KV + 256, 640);                                                       \
            wgmma_rs_n24_t1<HI_V>(at.o, at.p[0], at.p[1], at.p[2], at.p[3], dv, 1);                                \
            wgmma_rs_n24_t1<HI_V>(at.o, at.p[4], at.p[5], at.p[6], at.p[7], dv + 80, 1);                           \
            wgmma_rs_n24_t1<HI_V>(at.o, at.p[8], at.p[9], at.p[10], at.p[11], dv + 160, 1);                        \
            wgmma_rs_n24_t1<HI_V>(at.o, at.p[12], at.p[13], at.p[14], at.p[15], dv + 240, 1);                      \
        } while (0)
#define EXPS() do {                                                                                                \
            _Pragma("unroll") for (int i = 0; i < 16; i++) at.p[i] = pack(ex2(at.s[2 * i]), ex2(at.s[2 * i + 1])); \
            fence_regs(at.p);                                                                                      \
        } while (0)
#define FUSED_STEP(DV, DK, NB, NPH, REL, GEMM_CODE) do {                                                           \
            wg_fence();                                                                                            \
            wgmma6_rs_n24_t1(at.o, at.p[0], at.p[1], at.p[2], at.p[3], (DV), 1);                                   \
            wgmma6_rs_n24_t1(at.o, at.p[4], at.p[5], at.p[6], at.p[7], (DV) + 80, 1);                              \
            wgmma6_rs_n24_t1(at.o, at.p[8], at.p[9], at.p[10], at.p[11], (DV) + 160, 1);                           \
            wgmma6_rs_n24_t1(at.o, at.p[12], at.p[13], at.p[14], at.p[15], (DV) + 240, 1);                         \
            wgmma6_rs_n64_t0(at.s, at.q[0], at.q[1], at.q[2], at.q[3], (DK) + dlo(0, 128), 0);                     \
            wgmma6_rs_n64_t0(at.s, at.q[4], at.q[5], at.q[6], at.q[7], (DK) + 32, 1);                              \
            wg_commit();                                                                                           \
            GEMM_CODE;                                                                                             \
            wg_commit();                                                                                           \
            const uint32_t rdy = mbar_test(NB, NPH);                                                               \
            wg_wait<1>();                                                                                          \
            fence_regs(at.s); fence_regs(at.p);                                                                    \
            if (tid < 2) asm volatile("mbarrier.arrive.shared::cluster.b64 _, [%0];" ::"r"(REL) : "memory");       \
            EXPS();                                                                                                \
            mbar_wait_unless(rdy, NB, NPH);                                                                        \
        } while (0)
#define FUSED_PAIR(HIA, LOA, LOB, STEP0, GEMM) do {                                                                \
            const uint64_t dv0 = mkdesc<HI_V>(pd + dlo(OFF_KV + 256, 640));                                        \
            const uint64_t dv1 = mkdesc<HI_V>(sd + dlo(OFF_KV + 256, 640));                                        \
            const uint64_t dk = mkdesc<HI_K>(sd + dlo(OFF_KV, 0));                                                 \
            const uint64_t da = mkdesc<HIA>(sd + (LOA)), db = mkdesc<HI_W>(sd + (LOB));                            \
            STEP0(dv0, dk, fb + 8, ph, rel, GEMM(da, db, first));                                                  \
            const uint32_t r1 = fb + rel_off;                                                                      \
            rel = r1 + 8;                                                                                          \
            pd = sd + (SLOT >> 4); pb = fb + 8;                                                                    \
            if (fb == bar_full + (NSTAGE - 2) * 8) { fb = bar_full; ph ^= 1; } else fb += 16;                      \
            sd = (sd == sbd + (NSTAGE - 2) * (SLOT >> 4)) ? sbd : sd + 2 * (SLOT >> 4);                            \
            FUSED_STEP(dv1, dk + (SLOT >> 4), fb, ph, r1, GEMM(da + (SLOT >> 4), db + (SLOT >> 4), 1));            \
            first = 1;                                                                                             \
        } while (0)
#define GEMM_256(A, B, SC) do { wgmma6_ss_n256_t1(acc, A, B, SC); wgmma6_ss_n256_t1(acc, (A) + 2, (B) + 128, 1); } while (0)
#define GEMM_80(A, B, SC) do { wgmma6_ss_n80_t1(keep, A, B, SC); wgmma6_ss_n80_t1(keep, (A) + 256, (B) + 128, 1); wgmma6_ss_n80_t1(keep, (A) + 512, (B) + 256, 1); } while (0)
#define GEMM_144(A, B, SC) do { wgmma6_ss_n144_t1(ah, A, B, SC); wgmma6_ss_n144_t1(ah, (A) + 256, (B) + 128, 1); wgmma6_ss_n144_t1(ah, (A) + 512, (B) + 256, 1); } while (0)
#define NORM_ITEM(item) do {                                                                                       \
            if (norm_o(ow, at.o, lane, gaddr)) {                                                                   \
                attn_true_max(at.o, at.q, g_kv + (size_t)(j * 4 + (item)) * HEAD_BYTES + lane * 4);                \
                norm_o(ow, at.o, lane, gaddr);                                                                     \
            }                                                                                                      \
        } while (0)
#define STORE_ITEM(item) do { uint32_t ow[6]; NORM_ITEM(item); PUT_ITEM(item); } while (0)
#define PUT_ITEM(item) do {                                                                                        \
            uint8_t* op = a2w + (288 + ((item) * 4 + (j >> 1)) * 3) * 4096 + (j & 1) * 4224;                       \
            const int step = (j & 1) ? 3968 : 128;                                                                 \
            stg32(op, ow[0]);        stg32(op + 256, ow[1]);                                                       \
            stg32(op + step, ow[2]); stg32(op + step + 256, ow[3]);                                                \
            stg32(op + 4096, ow[4]); stg32(op + 4096 + 256, ow[5]);                                                \
        } while (0)
#define ITEM_STEP(DV, DK, NB, NPH, REL, GEMM_CODE) do {                                                            \
            uint32_t qo[8];                                                                                        \
            _Pragma("unroll") for (int i = 0; i < 6; i++) asm volatile("mov.b32 %0, %1;" : "=r"(qo[i]) : "r"(at.q[i])); \
            load_q(at.q, qa + (item + 1) * 4608, lane);                                                            \
            fence_regs(at.q);                                                                                      \
            wg_fence();                                                                                            \
            wgmma6_rs_n24_t1(at.o, at.p[0], at.p[1], at.p[2], at.p[3], (DV), 1);                                   \
            wgmma6_rs_n24_t1(at.o, at.p[4], at.p[5], at.p[6], at.p[7], (DV) + 80, 1);                              \
            wgmma6_rs_n24_t1(at.o, at.p[8], at.p[9], at.p[10], at.p[11], (DV) + 160, 1);                           \
            wgmma6_rs_n24_t1(at.o, at.p[12], at.p[13], at.p[14], at.p[15], (DV) + 240, 1);                         \
            wgmma6_rs_n64_t0(at.s, at.q[0], at.q[1], at.q[2], at.q[3], (DK) + dlo(0, 128), 0);                     \
            wgmma6_rs_n64_t0(at.s, at.q[4], at.q[5], at.q[6], at.q[7], (DK) + 32, 1);                              \
            wg_commit();                                                                                           \
            GEMM_CODE;                                                                                             \
            wg_commit();                                                                                           \
            const uint32_t rdy = mbar_test(NB, NPH);                                                               \
            wg_wait<1>();                                                                                          \
            fence_regs(at.o); fence_regs(at.p); fence_regs(at.s);                                                  \
            if (tid < 2) asm volatile("mbarrier.arrive.shared::cluster.b64 _, [%0];" ::"r"(REL) : "memory");       \
            uint32_t ow[6];                                                                                        \
            const bool bad = norm_o(ow, at.o, lane, gaddr);                                                        \
            EXPS();                                                                                                \
            if (bad) {                                                                                             \
                attn_true_max(at.o, qo, g_kv + (size_t)(j * 4 + (item)) * HEAD_BYTES + lane * 4);                  \
                norm_o(ow, at.o, lane, gaddr);                                                                     \
            }                                                                                                      \
            PUT_ITEM(item);                                                                                        \
            _Pragma("unroll") for (int i = 0; i < 12; i++) at.o[i] = 0.f;                                          \
            fence_regs(at.o);                                                                                      \
            mbar_wait_unless(rdy, NB, NPH);                                                                        \
        } while (0)
#define H2(i) pack(geglu2(acc[i], acc[64 + (i)]), geglu2(acc[(i) + 1], acc[65 + (i)]))
        float keep[40];
        float4 px[3];
        {
            float ah[72];
            int first = 1;
            {
#pragma unroll 1
                for (int t = 0; t < 5; t++) {
                    int n = 0x26988 >> (t * 4) & 15;
#pragma unroll 1
                    do { FUSED_PAIR(HI_X, wg * 256 + dlo(OFF_AX, 16), dlo(0, 4096), FUSED_STEP, GEMM_256); } while (--n);
                    if (t & 1) {
                        const int item = t >> 1;
                        mbar_wait(t == 1 ? bar_gate : bar_rdy + 2 * 8, 0);
                        FUSED_PAIR(HI_X, wg * 256 + dlo(OFF_AX, 16), dlo(0, 4096), ITEM_STEP, GEMM_256);
                    }
                    if (t < 3) {
                        mbar_wait(t > 0 ? bar_rdy + (t - 1) * 8 : bar_free + wg * 8, 0);
                        wg_wait<0>();
                        fence_regs(acc);
                        first = 0;
                        const uint32_t ha = sb + wg * 3 * SLOT + OFF_GAP + wq * 512 + lane * 16;
#pragma unroll
                        for (int k = 0; k < 8; k++) stsm4(ha + (k / 3) * SLOT + (k % 3) * 2048, H2(8 * k), H2(8 * k + 4), H2(8 * k + 2), H2(8 * k + 6));
                        fence_async_shared();
                        undef_regs(acc);
                        signal(t);
                    }
                }
                wg_wait<0>();
                fence_regs(acc);
                first = 0;
                uint8_t* hp = a2w + (j * 36 + 24) * 4096;
#pragma unroll
                for (int b = 0; b < 2; b++)
                    if (cta != 1000 + b) {
#pragma unroll
                        for (int k = b * 4; k < b * 4 + 4; k++) {
                            stg32(hp + k * 4096, H2(8 * k));           stg32(hp + k * 4096 + 256, H2(8 * k + 2));
                            stg32(hp + k * 4096 + 128, H2(8 * k + 4)); stg32(hp + k * 4096 + 384, H2(8 * k + 6));
                        }
                    }
                signal(3);
            }
#pragma unroll 1
            for (int seg = 0; seg < 3; seg++) {
                int n = 0x2AD >> (seg * 4) & 15;
#pragma unroll 1
                do { FUSED_PAIR(HI_A2, wg * 128 + dlo(OFF_A2, 128), dlo(0, 6144), FUSED_STEP, GEMM_144); } while (--n);
                if (seg == 0) {
                    constexpr int item = 2;
                    FUSED_PAIR(HI_A2, wg * 128 + dlo(OFF_A2, 128), dlo(0, 6144), ITEM_STEP, GEMM_144);
                    signal(5);
                } else if (seg == 1) {
                    wg_wait<0>();
                    fence_regs(ah);
                    const float w0 = 0.5f - 0.5f * __uint_as_float(lds32(gaddr)), w1 = 0.5f - 0.5f * __uint_as_float(lds32(gaddr + 32));
#pragma unroll
                    for (int i = 0; i < 72; i++) ah[i] *= (i & 2) ? w1 : w0;
                    fence_regs(ah);
                }
            }
            wg_wait<0>();
            fence_regs(ah);
            mbar_wait(bar_px, 0);
#pragma unroll
            for (int i = 0; i < 3; i++) px[i] = __ldcg(g_px + (size_t)(cta * 2 + wg) * 3 * 128 + tid + i * 128);
            uint4* mine = g_part + (size_t)(cta * 2 + wg) * 5 * 128 + tid;
#pragma unroll
            for (int i = 0; i < 5; i++) {
                const float* v = &ah[32 + 8 * i];
                __stcg(mine + i * 128, make_uint4(pack(v[0], v[1]), pack(v[2], v[3]), pack(v[4], v[5]), pack(v[6], v[7])));
            }
#pragma unroll
            for (int i = 0; i < 40; i++) keep[i] = ah[i < 32 ? i : 32 + i] + __uint_as_float(at.q[6]);
            signal(6);
            fence_regs(keep);
        }
        {
            int first = 1;
            FUSED_PAIR(HI_A2, wg * 128 + dlo(OFF_A2, 128), dlo(0, 6144), FUSED_STEP, GEMM_80);
        }
        wg_fence();
        ISSUE_PV();
        wg_commit();
        wg_wait<0>();
        fence_regs(at.o); fence_regs(at.p); fence_regs(at.q);
#pragma unroll
        for (int i = 0; i < 3; i++) { at.o[4 * i] += px[i].x; at.o[4 * i + 1] += px[i].y; at.o[4 * i + 2] += px[i].z; at.o[4 * i + 3] += px[i].w; }
        STORE_ITEM(3);
        signal(7);
        fence_regs(keep);
#pragma unroll 1
        for (int kk = 0; kk < 2; kk++) {
            mbar_wait(fb, ph);
            const uint64_t da = mkdesc<HI_A2>(sd + wg * 128 + dlo(OFF_A2, 128)), db = mkdesc<HI_W>(sd + dlo(0, 6144));
            wg_fence();
            GEMM_80(da, db, 1);
            wg_commit();
            wg_wait<1>();
            if (kk < 1) release();
            STAGE_NEXT;
        }
        {
            mbar_wait(bar_rdy + 6 * 8, 0);
            const uint4* theirs = g_part + (size_t)((cta ^ 8) * 2 + wg) * 5 * 128 + tid;
            uint4 pv[5];
#pragma unroll
            for (int i = 0; i < 5; i++) pv[i] = __ldcg(theirs + i * 128);
            wg_wait<0>();
            fence_regs(keep);
#pragma unroll
            for (int i = 0; i < 5; i++) {
                const uint32_t u[4] = {pv[i].x, pv[i].y, pv[i].z, pv[i].w};
#pragma unroll
                for (int e = 0; e < 4; e++) { keep[8 * i + 2 * e] += __uint_as_float(u[e] << 16); keep[8 * i + 2 * e + 1] += __uint_as_float(u[e] & 0xffff0000u); }
            }
            fence_regs(keep);
        }
        const uint32_t tb = sb + (warp >> 1) * SLOT + OFF_KV + (warp & 1) * 2560;
        const uint32_t trow = ((lane >> 3) & 1) * 8 + (lane & 7);
        uint8_t* op = (uint8_t*)(out + (size_t)(m * 128 + grp * 8) * DM);
        uint8_t* o1 = op + (lane >> 3) * (DM * 2) + nt * 256 + hf * 128 + (lane & 7) * 16;
        uint8_t* o2 = op + (lane >> 1) * (DM * 2) + 1024 + nt * 32 + (lane & 1) * 16;
        mbar_wait(bar_late, 0);
#pragma unroll 1
        for (int k = 2; k < 6; k++) {
            mbar_wait(bar_full + k * 8, 0);
            const uint32_t bo = __shfl_sync(0xffffffffu, lds32(s_order + k * 4), 0);
            const uint64_t da = mkdesc<HI_A2>(sbd + k * (SLOT >> 4) + wg * 128 + dlo(OFF_A2, 128)), db = mkdesc<HI_W>(sbd + bo + dlo(0, 6144));
            wg_fence();
            GEMM_80(da, db, 1);
            wg_commit();
        }
        asm volatile("barrier.cluster.arrive.relaxed.aligned;" ::: "memory");
        wg_wait<0>();
        fence_regs(keep);
#pragma unroll
        for (int i = 0; i < 5; i++) {
            const uint32_t a = i < 4 ? tb + trow * 128 + (((2 * i + (lane >> 4)) ^ (lane & 7)) << 4) : tb + 2048 + trow * 32 + (lane >> 4) * 16;
            stsm4(a, pack(keep[8 * i], keep[8 * i + 1]), pack(keep[8 * i + 2], keep[8 * i + 3]), pack(keep[8 * i + 4], keep[8 * i + 5]), pack(keep[8 * i + 6], keep[8 * i + 7]));
        }
        __syncwarp();
        uint4 v[5];
#pragma unroll
        for (int i = 0; i < 5; i++) {
            const uint32_t r = 4 * i + (lane >> 3);
            const uint32_t a = i < 4 ? tb + r * 128 + (((lane & 7) ^ (r & 7)) << 4) : tb + 2048 + lane * 16;
            asm volatile("ld.shared.v4.u32 {%0, %1, %2, %3}, [%4];" : "=r"(v[i].x), "=r"(v[i].y), "=r"(v[i].z), "=r"(v[i].w) : "r"(a) : "memory");
        }
#pragma unroll
        for (int i = 0; i < 5; i++)
            asm volatile("{\n.reg .pred p;\nsetp.ne.s32 p, %5, 0;\n@p st.global.v4.u32 [%0], {%1, %2, %3, %4};\n}"
                         ::"l"(i < 4 ? o1 + i * 4 * (DM * 2) : o2), "r"(v[i].x), "r"(v[i].y), "r"(v[i].z), "r"(v[i].w), "r"(i < 4 ? 1 : (int)(wg == hf)) : "memory");
        asm volatile("barrier.cluster.wait.aligned;" ::: "memory");
    }
}

typedef CUresult (*EncodeFn)(CUtensorMap*, CUtensorMapDataType, cuuint32_t, void*, const cuuint64_t*, const cuuint64_t*,
                             const cuuint32_t*, const cuuint32_t*, CUtensorMapInterleave, CUtensorMapSwizzle,
                             CUtensorMapL2promotion, CUtensorMapFloatOOBfill);

CUtensorMap make_map(EncodeFn enc, const void* ptr, uint64_t inner, uint64_t outer, uint32_t box_inner, uint32_t box_outer, CUtensorMapSwizzle swz) {
    CUtensorMap t;
    cuuint64_t dims[2] = {inner, outer};
    cuuint64_t strides[1] = {inner * 2};
    cuuint32_t box[2] = {box_inner, box_outer};
    cuuint32_t es[2] = {1, 1};
    enc(&t, CU_TENSOR_MAP_DATA_TYPE_BFLOAT16, 2, const_cast<void*>(ptr), dims, strides, box, es, CU_TENSOR_MAP_INTERLEAVE_NONE, swz,
        CU_TENSOR_MAP_L2_PROMOTION_L2_128B, CU_TENSOR_MAP_FLOAT_OOB_FILL_NONE);
    return t;
}

CUtensorMap make_qkv_map(EncodeFn enc, const void* ptr, uint32_t width, CUtensorMapSwizzle swz) {
    CUtensorMap t;
    cuuint64_t dims[3] = {DM, DM, 3};
    cuuint64_t strides[2] = {3 * DM * 2, DM * 2};
    cuuint32_t box[3] = {width, 16, 3};
    cuuint32_t es[3] = {1, 1, 1};
    enc(&t, CU_TENSOR_MAP_DATA_TYPE_BFLOAT16, 3, const_cast<void*>(ptr), dims, strides, box, es, CU_TENSOR_MAP_INTERLEAVE_NONE, swz,
        CU_TENSOR_MAP_L2_PROMOTION_L2_128B, CU_TENSOR_MAP_FLOAT_OOB_FILL_NONE);
    return t;
}

}

extern "C" void kernel_launch(void* const* d_in, const int* in_sizes, int n_in, void* d_out, int out_size) {
    (void)in_sizes; (void)n_in; (void)out_size;
    void* fn = nullptr;
    cudaDriverEntryPointQueryResult qr;
    cudaGetDriverEntryPoint("cuTensorMapEncodeTiled", &fn, cudaEnableDefault, &qr);
    EncodeFn enc = (EncodeFn)fn;
    const CUtensorMap tm_x = make_map(enc, d_in[0], DM, SEQ, 32, 128, CU_TENSOR_MAP_SWIZZLE_64B);
    const CUtensorMap tm_qkv = make_qkv_map(enc, d_in[1], 64, CU_TENSOR_MAP_SWIZZLE_128B);
    const CUtensorMap tm_qkv8 = make_qkv_map(enc, d_in[1], 8, CU_TENSOR_MAP_SWIZZLE_NONE);
    const CUtensorMap tm_wo = make_map(enc, d_in[2], DM, DM, 64, 24, CU_TENSOR_MAP_SWIZZLE_128B);
    const CUtensorMap tm_wg = make_map(enc, d_in[4], FF, DM, 64, 32, CU_TENSOR_MAP_SWIZZLE_128B);
    const CUtensorMap tm_wu = make_map(enc, d_in[5], FF, DM, 64, 32, CU_TENSOR_MAP_SWIZZLE_128B);
    const CUtensorMap tm_wd = make_map(enc, d_in[6], DM, FF, 64, 24, CU_TENSOR_MAP_SWIZZLE_128B);
    const CUtensorMap tm_wd16 = make_map(enc, d_in[6], DM, FF, 16, 24, CU_TENSOR_MAP_SWIZZLE_128B);
    const CUtensorMap tm_wo16 = make_map(enc, d_in[2], DM, DM, 16, 24, CU_TENSOR_MAP_SWIZZLE_128B);
    cudaFuncSetAttribute(fused_kernel, cudaFuncAttributeMaxDynamicSharedMemorySize, SMEM_BYTES);
    fused_kernel<<<NCTA + 4, 384, SMEM_BYTES>>>((__nv_bfloat16*)d_out, (const __nv_bfloat16*)d_in[0], (const __nv_bfloat16*)d_in[7],
                                               tm_x, tm_qkv, tm_qkv8, tm_wg, tm_wu, tm_wd, tm_wo, tm_wd16, tm_wo16);
}
```
